```python
import torch

def _softmax(x, axis=-1):
    return torch.softmax(x, dim=axis)
def _gelu(x):
    return torch.nn.functional.gelu(x, approximate="tanh")
def _silu(x):
    return torch.nn.functional.silu(x)
def _sigmoid(x):
    return torch.sigmoid(x)
def _layernorm(x, axis=-1, eps=1e-5):
    m = x.mean(dim=axis, keepdim=True)
    v = x.var(dim=axis, keepdim=True, unbiased=False)
    return (x - m) / torch.sqrt(v + eps)
def _scatter_add(tgt, idx, src, axis=0):
    return tgt.clone().index_add_(axis, idx, src)
def _segment_sum(src, seg, n):
    out = torch.zeros((n,) + src.shape[1:], dtype=src.dtype)
    return out.index_add_(0, seg, src)
def _pad(x, pw):
    flat = tuple(v for pair in reversed(pw) for v in pair)
    return torch.nn.functional.pad(x, flat)

kernel_name = 'standalone__standard_2d_1d_3d_conv__vision'

def setup_inputs():

    _w = (lambda a: (lambda t: t.to(torch.bfloat16) if t.is_floating_point() else t)(torch.as_tensor(a)))
    H = W = 384
    C = 384
    K = 1
    return {
        "x": _w((lambda *s: torch.randn(*s, dtype=torch.bfloat16) * 0.05)(1, H, W, C)),
        "w": _w((lambda *s: torch.randn(*s, dtype=torch.bfloat16) * 0.05)(K, K, C, C)),
        "b": _w((lambda *s: torch.randn(*s, dtype=torch.bfloat16) * 0.05)(C)),
    }

def reference(x, w, b):
    B, H, W, Cin = x.shape
    K = w.shape[0]
    pl = (K - 1) // 2
    pr = K // 2
    xp = _pad(x, ((0, 0), (pl, pr), (pl, pr), (0, 0)))
    out = sum(
        torch.einsum('bhwc,cd->bhwd', xp[:, i:i+H, j:j+W, :], w[i, j])
        for i in range(K) for j in range(K)
    )
    return out + b[None, None, None, :]
```

```cpp
#include <cuda_runtime.h>
#include <cuda_bf16.h>
#include <cuda.h>
#include <stdint.h>

#define EARLY_AT 18
#define SMALL_AT 12

#define TUNABLES(F) \
    F(SPLIT_TILES, 66)     \
    F(EARLY_TILES, 132)    \
    F(EARLY_HEAD, 0)       \
    F(N_STATIC, 6)         \
    F(W_FIRST, 2)          \
    F(PM_FIRST, 24)        \
    F(PM_T0, 4200)         \
    F(PM_DT1, 177)         \
    F(PM_N1, 46) \
    F(PM_DT2, 600) \
    F(PM_N2, 24) \
    F(PM_DT3, 600) \
    F(PM_N3, 0) \
    F(EF_TAIL, 300)        \
    F(EF_HEAD, 0)          \
    F(RING3_AT, 16)        \
    F(LAG_SPREAD, 5)       \
    F(LAG_WG, 2)           \
    F(LAG_T1, 40)          \
    F(LAG_T2, 0)           \
    F(X0, 0) \
    F(X1, 0) \
    F(X2, 0) \
    F(X3, 0)

struct Tune {
#define F(n, v) static constexpr uint32_t n = v;
    TUNABLES(F)
#undef F
};
#define TP(n) (Tune::n)

#define TRV(slot, idx, v)
#define TR(slot, idx)
#define TRE(slot, idx)

namespace {

constexpr int C            = 384;
constexpr int TILE_PIX     = 64;
constexpr int SMALL_PIX    = 32;
constexpr int STAGES       = 4;
constexpr int STAGE_BYTES  = TILE_PIX * C * 2;
constexpr int HALF_BYTES   = STAGE_BYTES / 2;
constexpr int NUM_WG       = 3;
constexpr int THREADS      = (NUM_WG + 1) * 128;
constexpr int SMEM_OUT     = 3 * STAGE_BYTES;
constexpr int SMEM_BAR     = SMEM_OUT + 3 * HALF_BYTES;
constexpr int SMEM_TOTAL   = SMEM_BAR + 512 + 1024;
constexpr int ID_SLOTS     = 16;
constexpr int ID_BARS      = 4;
constexpr uint32_t SPIN_LIMIT = 1u << 24;
constexpr int BAR_W     = 0;
constexpr int BAR_FULL  = 32;
constexpr int BAR_EMPTY = BAR_FULL + 8 * STAGES;
constexpr int BAR_ID    = BAR_EMPTY + 8 * STAGES;
constexpr int BAR_OFREE = BAR_ID + 8 * ID_BARS;
constexpr int BAR_OFULL = BAR_OFREE + 8 * 12;
constexpr int ID_AT     = BAR_OFULL + 8 * 12;
constexpr int FRONT_AT  = ID_AT + 4 * ID_SLOTS;
constexpr uint64_t EVICT_NORMAL = 0x1000000000000000ull;
constexpr uint64_t EVICT_FIRST  = 0x12F0000000000000ull;

struct Maps {
    CUtensorMap w, x_tile, x_small, o_slice, o_tile, o_small;
};

__device__ unsigned int g_tile_counter;

#define ELECT "{\n.reg .pred e;\nelect.sync _|e, 0xffffffff;\n@e "

__device__ __forceinline__ uint32_t smem_u32(const void* p) {
    return (uint32_t)__cvta_generic_to_shared(p);
}
__device__ __forceinline__ void mbar_init_1(uint32_t bar, uint32_t count) {
    asm volatile(ELECT "mbarrier.init.shared::cta.b64 [%0], %1;\n}" ::"r"(bar), "r"(count) : "memory");
}
__device__ __forceinline__ void mbar_expect_tx_1(uint32_t bar, uint32_t bytes) {
    asm volatile(ELECT "mbarrier.arrive.expect_tx.shared::cta.b64 _, [%0], %1;\n}" ::"r"(bar), "r"(bytes) : "memory");
}
__device__ __forceinline__ void mbar_arrive_1(uint32_t bar) {
    asm volatile(ELECT "mbarrier.arrive.shared::cta.b64 _, [%0];\n}" ::"r"(bar) : "memory");
}
__device__ __forceinline__ void mbar_wait(uint32_t bar, uint32_t parity) {
    uint32_t done;
    uint32_t spins = 0;
    do {
        asm volatile(
            "{\n.reg .pred p;\n"
            "mbarrier.try_wait.parity.shared::cta.b64 p, [%1], %2;\n"
            "selp.u32 %0, 1, 0, p;\n}"
            : "=r"(done) : "r"(bar), "r"(parity) : "memory");
    } while (!done && ++spins < SPIN_LIMIT);
}
__device__ __forceinline__ void mbar_wait_w(uint32_t bar, uint32_t parity) {
    mbar_wait(bar, parity);
    __syncwarp();
}
__device__ __forceinline__ bool mbar_test_w(uint32_t bar, uint32_t parity) {
    uint32_t done;
    asm volatile(
        "{\n.reg .pred p;\n"
        "mbarrier.test_wait.parity.shared::cta.b64 p, [%1], %2;\n"
        "selp.u32 %0, 1, 0, p;\n}"
        : "=r"(done) : "r"(bar), "r"(parity) : "memory");
    return __all_sync(0xffffffffu, done);
}
__device__ __forceinline__ void mbar_arrive_cta(uint32_t bar, uint32_t cta) {
    asm volatile(
        "{\n.reg .b32 ra;\n"
        "mapa.shared::cluster.u32 ra, %0, %1;\n"
        "mbarrier.arrive.shared::cluster.b64 _, [ra];\n}"
        ::"r"(bar), "r"(cta) : "memory");
}
__device__ __forceinline__ void st_async_peer(uint32_t addr, uint32_t val, uint32_t bar) {
    asm volatile(
        "{\n.reg .b32 ra, rb;\n"
        "mapa.shared::cluster.u32 ra, %0, 1;\n"
        "mapa.shared::cluster.u32 rb, %2, 1;\n"
        "st.async.weak.shared::cluster.mbarrier::complete_tx::bytes.b32 [ra], %1, [rb];\n}"
        ::"r"(addr), "r"(val), "r"(bar) : "memory");
}
__device__ __forceinline__ uint32_t lds32(uint32_t addr) {
    uint32_t v;
    asm volatile("ld.shared.b32 %0, [%1];" : "=r"(v) : "r"(addr) : "memory");
    return v;
}
__device__ __forceinline__ uint32_t uniform(uint32_t v) {
    return __shfl_sync(0xffffffffu, v, 0);
}
__device__ __forceinline__ void sts32(uint32_t addr, uint32_t v) {
    asm volatile("st.shared.b32 [%0], %1;" ::"r"(addr), "r"(v) : "memory");
}
__device__ __forceinline__ void tma_load_w_1(uint32_t dst, const CUtensorMap* map, uint32_t bar, int n) {
    asm volatile(
        ELECT "cp.async.bulk.tensor.3d.shared::cluster.global.mbarrier::complete_tx::bytes [%0], [%1, {%3, %4, %4}], [%2];\n}"
        ::"r"(dst), "l"(map), "r"(bar), "r"(n), "r"(0) : "memory");
}
__device__ __forceinline__ void tma_load_x_1(uint32_t dst, const CUtensorMap* map, uint32_t bar, int group, uint64_t policy) {
    asm volatile(
        ELECT "cp.async.bulk.tensor.4d.shared::cluster.global.mbarrier::complete_tx::bytes.multicast::cluster.L2::cache_hint"
        " [%0], [%1, {%3, %3, %3, %4}], [%2], %5, %6;\n}"
        ::"r"(dst), "l"(map), "r"(bar), "r"(0), "r"(group), "h"((uint16_t)3), "l"(policy) : "memory");
}
__device__ __forceinline__ void tma_store_1(const CUtensorMap* map, uint32_t src, int pix, int wg, int rank) {
    asm volatile(
        ELECT "cp.async.bulk.tensor.4d.global.shared::cta.bulk_group [%0, {%2, %3, %4, %5}], [%1];\n}\n"
        "cp.async.bulk.commit_group;"
        ::"l"(map), "r"(src), "r"(0), "r"(pix), "r"(wg), "r"(rank) : "memory");
}
template <int N>
__device__ __forceinline__ void stores_read_wait() {
    asm volatile("cp.async.bulk.wait_group.read %0;" ::"n"(N) : "memory");
}
__device__ __forceinline__ void prefetch_map_1(const CUtensorMap* map) {
    asm volatile(ELECT "prefetch.tensormap [%0];\n}" ::"l"(map) : "memory");
}
__device__ __forceinline__ uint32_t timer_ns() {
    uint32_t t;
    asm volatile("mov.u32 %0, %%globaltimer_lo;" : "=r"(t)::"memory");
    return t;
}
__device__ __forceinline__ void cluster_arrive() {
    asm volatile("barrier.cluster.arrive.relaxed.aligned;" ::: "memory");
}
__device__ __forceinline__ void cluster_wait() {
    asm volatile("barrier.cluster.wait.aligned;" ::: "memory");
}
__device__ __forceinline__ void publish_barriers() {
    asm volatile("fence.mbarrier_init.release.cluster;" ::: "memory");
    asm volatile("fence.proxy.async.shared::cta;" ::: "memory");
}

__device__ __forceinline__ void wgmma_rs_n64(float (&d)[32], const uint32_t* a, uint64_t desc, int scale_d) {
    asm volatile(
        "{\n.reg .pred p;\n"
        "setp.ne.b32 p, %37, 0;\n"
        "wgmma.mma_async.sync.aligned.m64n64k16.f32.bf16.bf16 "
        "{%0, %1, %2, %3, %4, %5, %6, %7, %8, %9, %10, %11, %12, %13, %14, %15, "
        "%16, %17, %18, %19, %20, %21, %22, %23, %24, %25, %26, %27, %28, %29, %30, %31}, "
        "{%32, %33, %34, %35}, %36, p, 1, 1, 0;\n}"
        : "+f"(d[0]), "+f"(d[1]), "+f"(d[2]), "+f"(d[3]), "+f"(d[4]), "+f"(d[5]), "+f"(d[6]), "+f"(d[7]),
          "+f"(d[8]), "+f"(d[9]), "+f"(d[10]), "+f"(d[11]), "+f"(d[12]), "+f"(d[13]), "+f"(d[14]), "+f"(d[15]),
          "+f"(d[16]), "+f"(d[17]), "+f"(d[18]), "+f"(d[19]), "+f"(d[20]), "+f"(d[21]), "+f"(d[22]), "+f"(d[23]),
          "+f"(d[24]), "+f"(d[25]), "+f"(d[26]), "+f"(d[27]), "+f"(d[28]), "+f"(d[29]), "+f"(d[30]), "+f"(d[31])
        : "r"(a[0]), "r"(a[1]), "r"(a[2]), "r"(a[3]), "l"(desc), "r"(scale_d));
}

__device__ __forceinline__ void wgmma_rs_n32(float (&d)[32], const uint32_t* a, uint64_t desc, int scale_d) {
    asm volatile(
        "{\n.reg .pred p;\n"
        "setp.ne.b32 p, %21, 0;\n"
        "wgmma.mma_async.sync.aligned.m64n32k16.f32.bf16.bf16 "
        "{%0, %1, %2, %3, %4, %5, %6, %7, %8, %9, %10, %11, %12, %13, %14, %15}, "
        "{%16, %17, %18, %19}, %20, p, 1, 1, 0;\n}"
        : "+f"(d[0]), "+f"(d[1]), "+f"(d[2]), "+f"(d[3]), "+f"(d[4]), "+f"(d[5]), "+f"(d[6]), "+f"(d[7]),
          "+f"(d[8]), "+f"(d[9]), "+f"(d[10]), "+f"(d[11]), "+f"(d[12]), "+f"(d[13]), "+f"(d[14]), "+f"(d[15])
        : "r"(a[0]), "r"(a[1]), "r"(a[2]), "r"(a[3]), "l"(desc), "r"(scale_d));
}

__device__ __forceinline__ uint32_t pack_bias(float lo, float hi, uint32_t bias2) {
    uint32_t r;
    asm("{\n.reg .b32 t;\n"
        "cvt.rn.bf16x2.f32 t, %2, %1;\n"
        "add.rn.bf16x2 %0, t, %3;\n}"
        : "=r"(r) : "f"(lo), "f"(hi), "r"(bias2));
    return r;
}

__device__ __forceinline__ int slice_channel(uint32_t rank, int wg) {
    return (wg * 2 + rank) * 64;
}

struct Consumer {
    uint32_t wreg[96];
    uint32_t bias_lo, bias_hi, st_addr, bars;
    uint64_t desc_base;
    int wg, lane;
};
struct Ring {
    uint32_t s, ob, phase;
};
__device__ __forceinline__ uint32_t next_slot(const Tune& tune, uint32_t s, uint32_t next_i) {
    return (s == 3 || (s == 2 && next_i >= TP(RING3_AT))) ? 0 : s + 1;
}
__device__ __forceinline__ uint32_t next_buffer(const Tune& tune, uint32_t ob, uint32_t next_i) {
    return ob != 2 ? ob + 1 : next_i >= TP(RING3_AT) + 4 ? 0 : 2;
}

template <int PIX, int HAND_AT>
__device__ __forceinline__ void consume(const Tune& tune, const Consumer& c, Ring& r, float (&acc)[32], uint32_t i, bool early) {
    const int next_turn = 4 + (c.wg + 1) % NUM_WG;
    if ((i | c.wg) != 0) asm volatile("bar.sync %0, 256;" ::"r"(4 + c.wg) : "memory");
    TRE(1 + c.wg * 2, i);
    const uint64_t desc = c.desc_base + (uint64_t)(r.s * (STAGE_BYTES >> 4));
    asm volatile("wgmma.fence.sync.aligned;" ::: "memory");
#pragma unroll
    for (int ks = 0; ks < 24; ks++) {
        const uint64_t d = desc + (uint64_t)((ks >> 2) * 64 + (ks & 3) * 2);
        if (PIX == 64) wgmma_rs_n64(acc, &c.wreg[ks * 4], d, ks != 0);
        if (PIX == 32) wgmma_rs_n32(acc, &c.wreg[ks * 4], d, ks != 0);
        if (ks + 1 == HAND_AT && early) asm volatile("bar.arrive %0, 256;" ::"r"(next_turn) : "memory");
    }
    asm volatile("wgmma.commit_group.sync.aligned;" ::: "memory");
    asm volatile("wgmma.wait_group.sync.aligned 0;" ::: "memory");
#pragma unroll
    for (int j = 0; j < PIX / 2; j++) asm volatile("" : "+f"(acc[j])::"memory");
    if (!early) asm volatile("bar.arrive %0, 256;" ::"r"(next_turn) : "memory");
    TRE(2 + c.wg * 2, i);
    if (c.lane < 2) mbar_arrive_cta(c.bars + BAR_EMPTY + 8 * r.s, c.lane);
    const uint32_t obar = c.bars + (r.ob * 4 + c.wg) * 8;
    mbar_wait_w(obar + BAR_OFREE, (r.phase >> (4 + r.ob)) & 1);
    const uint32_t dst = c.st_addr + r.ob * HALF_BYTES + c.wg * (PIX * 128);
#pragma unroll
    for (int j = 0; j < PIX / 16; j++) {
        const uint32_t r0 = pack_bias(acc[8 * j + 0], acc[8 * j + 1], c.bias_lo);
        const uint32_t r1 = pack_bias(acc[8 * j + 2], acc[8 * j + 3], c.bias_hi);
        const uint32_t r2 = pack_bias(acc[8 * j + 4], acc[8 * j + 5], c.bias_lo);
        const uint32_t r3 = pack_bias(acc[8 * j + 6], acc[8 * j + 7], c.bias_hi);
        asm volatile("stmatrix.sync.aligned.m8n8.x4.trans.shared.b16 [%0], {%1, %2, %3, %4};"
                     ::"r"(dst + j * 2048), "r"(r0), "r"(r1), "r"(r2), "r"(r3) : "memory");
    }
    asm volatile("fence.proxy.async.shared::cta;" ::: "memory");
    __syncwarp();
    mbar_arrive_1(obar + BAR_OFULL);
    TRE(8 + c.wg, i);
    r.phase ^= (1u << r.s) | (16u << r.ob);
    r.s  = next_slot(tune, r.s, i + 1);
    r.ob = next_buffer(tune, r.ob, i + 1);
}

__device__ __forceinline__ void free_buffer_1(uint32_t bars, uint32_t ob) {
#pragma unroll
    for (int w = 0; w < NUM_WG; w++) mbar_arrive_1(bars + BAR_OFREE + ob * 32 + w * 8);
}

__global__ void __cluster_dims__(2, 1, 1) __launch_bounds__(THREADS, 1)
conv1x1_kernel(const __grid_constant__ Maps maps,
               const uint8_t* __restrict__ x_raw,
               const uint16_t* __restrict__ bias,
               uint32_t num_tiles,
               uint32_t num_full,
               const __grid_constant__ Tune tune) {
    extern __shared__ uint8_t smem_raw[];
    const uint32_t smem = (smem_u32(smem_raw) + 1023u) & ~1023u;
    const uint32_t bars = smem + SMEM_BAR;

    const int warp = uniform(threadIdx.x >> 5);
    const int lane = threadIdx.x & 31;
    const uint32_t rank         = blockIdx.x & 1;
    const uint32_t cluster      = blockIdx.x >> 1;
    const uint32_t num_clusters = gridDim.x >> 1;
    const uint32_t num_ids = 2 * num_tiles - num_full;

    if (warp < NUM_WG * 4) {
        cluster_arrive();
        asm volatile("setmaxnreg.inc.sync.aligned.u32 160;");
        const int wg = warp >> 2;
        const int wq = warp & 3;
        Consumer c;
        c.wg = wg;
        c.lane = lane;
        c.bars = bars;
        c.bias_lo = bias[slice_channel(rank, wg) + wq * 16 + (lane >> 2)] * 0x10001u;
        c.bias_hi = bias[slice_channel(rank, wg) + wq * 16 + (lane >> 2) + 8] * 0x10001u;

        cluster_wait();
        TRE(1 + wg, 63);
        mbar_wait_w(bars + BAR_W + 8 * wg, 0);
        TRE(4 + wg, 63);
        {
            const int r = lane & 7, m = lane >> 3;
            const uint32_t base = smem + wg * STAGE_BYTES + ((m >> 1) * 8 + r) * 128 + (((2 * wq + (m & 1)) ^ r) << 4);
#pragma unroll
            for (int ks = 0; ks < 24; ks++) {
                asm volatile("ldmatrix.sync.aligned.m8n8.x4.trans.shared.b16 {%0, %1, %2, %3}, [%4];"
                             : "=r"(c.wreg[ks * 4 + 0]), "=r"(c.wreg[ks * 4 + 1]), "=r"(c.wreg[ks * 4 + 2]), "=r"(c.wreg[ks * 4 + 3])
                             : "r"(base + ks * 2048) : "memory");
            }
        }
        uint32_t dep = 0;
#pragma unroll
        for (int ks = 0; ks < 24; ks++) dep ^= c.wreg[ks * 4];
        dep &= num_tiles >> 31;
        __syncwarp();
        if (lane < 6) mbar_arrive_cta(bars + BAR_EMPTY + 8 * wg + dep, lane & 1);
        TRE(1 + wg, 60);

        c.st_addr = smem + SMEM_OUT + ((lane >> 4) * 8 + (lane & 7)) * 128 + (((2 * wq + ((lane >> 3) & 1)) ^ (lane & 7)) << 4);
        c.desc_base = (uint64_t)((smem & 0x3FFFF) >> 4) | ((uint64_t)1 << 16) | ((uint64_t)(6144 >> 4) << 32) | ((uint64_t)1 << 62);

        float acc[32];
        uint32_t i = 0, id;
        Ring r = {3, 2, 0x70};
        for (;; i++) {
            mbar_wait(bars + BAR_FULL + 8 * r.s, (r.phase >> r.s) & 1);
            id = lds32(bars + ID_AT + 4 * (i & (ID_SLOTS - 1)));
            if (id >= num_full) break;
            consume<TILE_PIX, EARLY_AT>(tune, c, r, acc, i, id + TP(EARLY_TILES) >= num_full || id + 1 <= TP(EARLY_HEAD));
        }
        while (id < num_ids) {
            float acc_s[32];
#pragma unroll
            for (int j = 0; j < SMALL_PIX / 2; j++) acc_s[j] = 0.f;
            consume<SMALL_PIX, SMALL_AT>(tune, c, r, acc_s, i, true);
            i++;
            mbar_wait(bars + BAR_FULL + 8 * r.s, (r.phase >> r.s) & 1);
            id = lds32(bars + ID_AT + 4 * (i & (ID_SLOTS - 1)));
        }
        if (wg == 0) {
            mbar_wait_w(bars + BAR_OFREE + r.ob * 32, (r.phase >> (4 + r.ob)) & 1);
            mbar_arrive_1(bars + BAR_OFULL + r.ob * 32);
            asm volatile("bar.sync 4, 256;" ::: "memory");
        }
        TRE(1 + wg, 62);
    } else {
        asm volatile("setmaxnreg.dec.sync.aligned.u32 32;");
        if (warp == NUM_WG * 4) {
#pragma unroll
            for (int j = 0; j < NUM_WG; j++) mbar_init_1(bars + BAR_W + 8 * j, 1);
            publish_barriers();
            cluster_arrive();
            sts32(bars + ID_AT, cluster);
#pragma unroll
            for (int j = 0; j < NUM_WG; j++) {
                if (j == (int)TP(W_FIRST)) {
                    cluster_wait();
                    TR(0, 0);
                    mbar_expect_tx_1(bars + BAR_FULL + 8 * 3, STAGE_BYTES);
                    tma_load_x_1(smem + 3 * STAGE_BYTES + rank * HALF_BYTES, &maps.x_tile, bars + BAR_FULL + 8 * 3,
                                 cluster * 8 + rank * 4, TP(EF_HEAD) != 0 ? EVICT_FIRST : EVICT_NORMAL);
                }
                mbar_expect_tx_1(bars + BAR_W + 8 * j, STAGE_BYTES);
                tma_load_w_1(smem + j * STAGE_BYTES, &maps.w, bars + BAR_W + 8 * j, slice_channel(rank, j));
                if (j == 0) TR(2, 61);
            }
            const uint32_t first_dynamic = TP(N_STATIC) * num_clusters;
            const uint32_t wrap = num_ids - first_dynamic + num_clusters - 1;
            uint32_t s = 3, fph = 8, eph = 0, s1 = 3, s2 = 3;
#pragma unroll 1
            for (uint32_t i = 1;; i++) {
                s2 = s1;
                s1 = s;
                s = next_slot(tune, s, i);
                const uint32_t slot = bars + ID_AT + 4 * (i & (ID_SLOTS - 1));
                uint32_t id = cluster + i * num_clusters;
                if (i >= TP(N_STATIC)) {
                    const uint32_t b = bars + BAR_ID + 8 * ((i - TP(N_STATIC)) & (ID_BARS - 1));
                    if (rank == 0) {
                        if (i > TP(N_STATIC)) mbar_wait_w(bars + BAR_FULL + 8 * s2, ((fph >> s2) & 1) ^ 1);
                        if (lane == 0) {
                            id = first_dynamic + atomicInc(&g_tile_counter, wrap);
                            st_async_peer(slot, id, b);
                        }
                    } else {
                        mbar_expect_tx_1(b, 4);
                        mbar_wait_w(b, ((i - TP(N_STATIC)) / ID_BARS) & 1);
                        id = lds32(slot);
                    }
                    id = uniform(id);
                }
                sts32(slot, id);
                sts32(bars + FRONT_AT, id);
                TR(7, i);
                mbar_wait_w(bars + BAR_EMPTY + 8 * s, (eph >> s) & 1);
                eph ^= 1u << s;
                fph ^= 1u << s;
                const uint32_t full = bars + BAR_FULL + 8 * s;
                if (id >= num_ids) {
                    mbar_arrive_1(full);
#pragma unroll 1
                    for (uint32_t u = 0; u < STAGES; u++)
                        if (u != s) mbar_wait_w(bars + BAR_EMPTY + 8 * u, (eph >> u) & 1);
                    break;
                }
                TR(0, i);
                TRV(15, i, id);
                if (id < num_full) {
                    mbar_expect_tx_1(full, STAGE_BYTES);
                    tma_load_x_1(smem + s * STAGE_BYTES + rank * HALF_BYTES, &maps.x_tile, full, id * 8 + rank * 4,
                                 id + TP(EF_TAIL) >= num_tiles || id + 1 <= TP(EF_HEAD) ? EVICT_FIRST : EVICT_NORMAL);
                } else {
                    mbar_expect_tx_1(full, HALF_BYTES);
                    tma_load_x_1(smem + s * STAGE_BYTES + rank * (HALF_BYTES / 2), &maps.x_small, full,
                                 (id + num_full) * 4 + rank * 2, EVICT_FIRST);
                }
            }
        } else if (warp == NUM_WG * 4 + 1) {
            const uint32_t t_start = timer_ns();
#pragma unroll
            for (int s = 0; s < STAGES; s++) {
                mbar_init_1(bars + BAR_FULL + 8 * s, 1);
                mbar_init_1(bars + BAR_EMPTY + 8 * s, NUM_WG * 4 * 2);
            }
#pragma unroll
            for (int s = 0; s < ID_BARS; s++) mbar_init_1(bars + BAR_ID + 8 * s, 1);
            publish_barriers();
            cluster_arrive();
            TR(0, 61);
            cluster_wait();
            uint32_t due = t_start + TP(PM_T0);
#pragma unroll 1
            for (uint32_t q = 0; q < TP(PM_N1) + TP(PM_N2) + TP(PM_N3); q++) {
#pragma unroll 1
                for (uint32_t spins = 0; spins < 4096 && (int32_t)(timer_ns() - due) < 0; spins++) __nanosleep(32);
                due += q < TP(PM_N1) ? TP(PM_DT1) : q < TP(PM_N1) + TP(PM_N2) ? TP(PM_DT2) : TP(PM_DT3);
                const uint32_t piece = TP(PM_FIRST) + q;
                const uint32_t t = cluster + piece / 6 * num_clusters;
                if (t >= num_tiles) break;
                const uint8_t* p = x_raw + (size_t)t * STAGE_BYTES + rank * HALF_BYTES + (piece % 6) * 4096;
                asm volatile("prefetch.global.L2 [%0];" ::"l"(p + lane * 128) : "memory");
            }
        } else if (warp == NUM_WG * 4 + 2) {
#pragma unroll
            for (int b = 0; b < 3; b++) {
#pragma unroll
                for (int w = 0; w < NUM_WG; w++) {
                    mbar_init_1(bars + BAR_OFREE + b * 32 + w * 8, 1);
                    mbar_init_1(bars + BAR_OFULL + b * 32 + w * 8, 4);
                }
            }
            publish_barriers();
            cluster_arrive();
            cluster_wait();
            uint32_t j = 0, phase = 0, id = 0;
#pragma unroll 1
            for (; j < TP(RING3_AT) + 4; j++) {
                mbar_wait_w(bars + BAR_OFULL + 64, phase >> 2);
                id = uniform(lds32(bars + ID_AT + 4 * (j & (ID_SLOTS - 1))));
                if (id >= num_full) break;
#pragma unroll
                for (int w = 0; w < NUM_WG; w++) {
                    if (w != 0) mbar_wait_w(bars + BAR_OFULL + 64 + w * 8, phase >> 2);
                    TR(11 + w, j);
                    tma_store_1(&maps.o_slice, smem + SMEM_OUT + 2 * HALF_BYTES + w * (TILE_PIX * 128), id * TILE_PIX, w, rank);
                    stores_read_wait<1>();
                    if ((j | w) != 0) mbar_arrive_1(bars + BAR_OFREE + 64 + (w + 2) % NUM_WG * 8);
                }
                phase ^= 4;
            }
            stores_read_wait<0>();
            if (j != 0) mbar_arrive_1(bars + BAR_OFREE + 64 + 2 * 8);
            const uint32_t lag_at = TP(RING3_AT) + 4 + cluster % TP(LAG_SPREAD);
            uint32_t ob = next_buffer(tune, 2, j), open = 3;
#pragma unroll 1
            for (;; j++) {
                uint32_t lag = (j >= lag_at) + (j >= lag_at + TP(LAG_SPREAD));
#pragma unroll 1
                for (uint32_t spins = 0; spins < SPIN_LIMIT; spins++) {
                    const uint32_t front = uniform(lds32(bars + FRONT_AT));
                    if (front + TP(LAG_T1) >= num_ids && lag > 1) lag = 1;
                    if (front + TP(LAG_T2) >= num_ids) lag = 0;
                    uint32_t b = ob + lag;
                    if (b >= 3) b -= 3;
                    if (mbar_test_w(bars + BAR_OFULL + b * 32 + (lag != 0 ? TP(LAG_WG) * 8 : 0), (phase >> b) & 1)) break;
                    if (open != 3) {
                        stores_read_wait<0>();
                        free_buffer_1(bars, open);
                        open = 3;
                    } else if (lag == 0) {
                        break;
                    } else {
                        __nanosleep(32);
                    }
                }
                const uint32_t obar = bars + BAR_OFULL + ob * 32;
                mbar_wait_w(obar, (phase >> ob) & 1);
                id = uniform(lds32(bars + ID_AT + 4 * (j & (ID_SLOTS - 1))));
                if (id >= num_ids) break;
                if (open != 3 && !mbar_test_w(obar + 16, (phase >> ob) & 1)) {
                    stores_read_wait<0>();
                    free_buffer_1(bars, open);
                    open = 3;
                }
                mbar_wait_w(obar + 8, (phase >> ob) & 1);
                mbar_wait_w(obar + 16, (phase >> ob) & 1);
                TR(11, j);
                const uint32_t src = smem + SMEM_OUT + ob * HALF_BYTES;
                if (id < num_full) tma_store_1(&maps.o_tile, src, id * TILE_PIX, 0, rank);
                else tma_store_1(&maps.o_small, src, (id + num_full) * SMALL_PIX, 0, rank);
                if (open != 3) {
                    stores_read_wait<1>();
                    free_buffer_1(bars, open);
                }
                open = ob;
                phase ^= 1u << ob;
                ob = next_buffer(tune, ob, j + 1);
            }
            stores_read_wait<0>();
            TR(4, 62);
        } else {
            cluster_arrive();
            prefetch_map_1(&maps.x_tile);
            prefetch_map_1(&maps.o_slice);
            cluster_wait();
            prefetch_map_1(&maps.o_tile);
            prefetch_map_1(&maps.x_small);
            prefetch_map_1(&maps.o_small);
        }
    }
}

typedef CUresult (*EncodeTiledFn)(CUtensorMap*, CUtensorMapDataType, cuuint32_t, void*, const cuuint64_t*,
                                  const cuuint64_t*, const cuuint32_t*, const cuuint32_t*, CUtensorMapInterleave,
                                  CUtensorMapSwizzle, CUtensorMapL2promotion, CUtensorMapFloatOOBfill);

}

extern "C" void kernel_launch(void* const* d_in, const int* in_sizes, int n_in, void* d_out, int out_size) {
    (void)n_in;
    (void)out_size;
    void* x = d_in[0];
    void* w = d_in[1];
    const uint16_t* b = (const uint16_t*)d_in[2];
    const int M = in_sizes[0] / C;
    const int num_tiles = M / TILE_PIX;

    static EncodeTiledFn encode = nullptr;
    static int sms = 0;
    if (!encode) {
        void* fn = nullptr;
        cudaDriverEntryPointQueryResult q;
        cudaGetDriverEntryPoint("cuTensorMapEncodeTiled", &fn, cudaEnableDefault, &q);
        encode = (EncodeTiledFn)fn;
        cudaDeviceGetAttribute(&sms, cudaDevAttrMultiProcessorCount, 0);
        cudaFuncSetAttribute(conv1x1_kernel, cudaFuncAttributeMaxDynamicSharedMemorySize, SMEM_TOTAL);
    }

    Maps maps;
    const cuuint32_t ones[4] = {1, 1, 1, 1};
    auto make = [&](CUtensorMap* map, int rank, void* base, const cuuint64_t* dims, const cuuint64_t* strides,
                    const cuuint32_t* box, CUtensorMapL2promotion promo) {
        encode(map, CU_TENSOR_MAP_DATA_TYPE_BFLOAT16, rank, base, dims, strides, box, ones, CU_TENSOR_MAP_INTERLEAVE_NONE,
               CU_TENSOR_MAP_SWIZZLE_128B, promo, CU_TENSOR_MAP_FLOAT_OOB_FILL_NONE);
    };
    {
        const cuuint64_t dims[4]    = {64, 8, 6, (cuuint64_t)(M / 8)};
        const cuuint64_t strides[3] = {C * 2, 128, 8 * C * 2};
        const cuuint32_t tile[4]    = {64, 8, 6, TILE_PIX / 16};
        const cuuint32_t small[4]   = {64, 8, 6, SMALL_PIX / 16};
        make(&maps.x_tile, 4, x, dims, strides, tile, CU_TENSOR_MAP_L2_PROMOTION_L2_128B);
        make(&maps.x_small, 4, x, dims, strides, small, CU_TENSOR_MAP_L2_PROMOTION_L2_128B);
    }
    {
        const cuuint64_t dims[3]    = {C, C / 2, 2};
        const cuuint64_t strides[2] = {C * 2, C * C};
        const cuuint32_t box[3]     = {64, C / 2, 2};
        make(&maps.w, 3, w, dims, strides, box, CU_TENSOR_MAP_L2_PROMOTION_L2_128B);
    }
    {
        const cuuint64_t dims[4]    = {64, (cuuint64_t)M, NUM_WG, 2};
        const cuuint64_t strides[3] = {C * 2, 256, 128};
        const cuuint32_t slice[4]   = {64, TILE_PIX, 1, 1};
        const cuuint32_t tile[4]    = {64, TILE_PIX, NUM_WG, 1};
        const cuuint32_t small[4]   = {64, SMALL_PIX, NUM_WG, 1};
        make(&maps.o_slice, 4, d_out, dims, strides, slice, CU_TENSOR_MAP_L2_PROMOTION_NONE);
        make(&maps.o_tile, 4, d_out, dims, strides, tile, CU_TENSOR_MAP_L2_PROMOTION_NONE);
        make(&maps.o_small, 4, d_out, dims, strides, small, CU_TENSOR_MAP_L2_PROMOTION_NONE);
    }

    const Tune tune;
    int clusters = sms / 2;
    if (clusters > num_tiles / (int)TP(N_STATIC)) clusters = num_tiles / (int)TP(N_STATIC);
    int num_full = num_tiles - (int)TP(SPLIT_TILES);
    if (num_full < clusters * (int)TP(N_STATIC)) num_full = clusters * (int)TP(N_STATIC);
    conv1x1_kernel<<<clusters * 2, THREADS, SMEM_TOTAL>>>(maps, (const uint8_t*)x, b, (uint32_t)num_tiles,
                                                          (uint32_t)num_full, tune);
}
```

```cpp
#include <cuda_runtime.h>
#include <cuda_bf16.h>
#include <cuda.h>
#include <stdint.h>

#define EARLY_AT 18

#define TUNABLES(F) \
    F(EARLY_TILES, 232)    \
    F(EARLY_HEAD, 0)       \
    F(N_STATIC, 14)        \
    F(W_FIRST, 2)          \
    F(PM_FIRST, 0)         \
    F(PM_T0, 100)            \
    F(PM_DT1, 150)         \
    F(PM_E1, 56) \
    F(PM_DT2, 175) \
    F(PM_E2, 70) \
    F(PM_DT3, 420) \
    F(PM_E3, 79) \
    F(PM_DT4, 450) \
    F(PM_E4, 120) \
    F(EF_TAIL, 300)        \
    F(EF_HEAD, 0)          \
    F(RING3_AT, 16)        \
    F(LAG_AT, 6)           \
    F(LAG_SPREAD, 2)       \
    F(LAG_GAP, 5)          \
    F(LAG_WG, 2)           \
    F(LAG_T1, 20)          \
    F(LAG_T2, 6)           \
    F(DEEP_AT, 120)          \
    F(X0, 0) \
    F(X1, 0) \
    F(X2, 0) \
    F(X3, 0)

struct Tune {
#define F(n, v) static constexpr uint32_t n = v;
    TUNABLES(F)
#undef F
};
#define TP(n) (Tune::n)

#define TRV(slot, idx, v)
#define TR(slot, idx)
#define TRE(slot, idx)

namespace {

constexpr int C            = 384;
constexpr int TILE_PIX     = 64;
constexpr int STAGES       = 4;
constexpr int STAGE_BYTES  = TILE_PIX * C * 2;
constexpr int HALF_BYTES   = STAGE_BYTES / 2;
constexpr int SLICE_BYTES  = TILE_PIX * 128;
constexpr int NUM_WG       = 3;
constexpr int THREADS      = (NUM_WG + 1) * 128;
constexpr int SMEM_OUT     = 3 * STAGE_BYTES;
constexpr int SMEM_BAR     = SMEM_OUT + 3 * HALF_BYTES;
constexpr int SMEM_TOTAL   = SMEM_BAR + 512 + 1024;
constexpr int ID_SLOTS     = 16;
constexpr int ID_BARS      = 4;
constexpr uint32_t SPIN_LIMIT = 1u << 24;
constexpr int BAR_W     = 0;
constexpr int BAR_FULL  = 32;
constexpr int BAR_EMPTY = BAR_FULL + 8 * STAGES;
constexpr int BAR_ID    = BAR_EMPTY + 8 * STAGES;
constexpr int BAR_OFREE = BAR_ID + 8 * ID_BARS;
constexpr int BAR_OFULL = BAR_OFREE + 8 * 12;
constexpr int ID_AT     = BAR_OFULL + 8 * 12;
constexpr int FRONT_AT  = ID_AT + 4 * ID_SLOTS;
constexpr uint64_t EVICT_NORMAL = 0x1000000000000000ull;
constexpr uint64_t EVICT_FIRST  = 0x12F0000000000000ull;

struct Maps {
    CUtensorMap w, x, out;
};

__device__ unsigned int g_tile_counter;

#define ELECT "{\n.reg .pred e;\nelect.sync _|e, 0xffffffff;\n@e "

__device__ __forceinline__ uint32_t smem_u32(const void* p) {
    return (uint32_t)__cvta_generic_to_shared(p);
}
__device__ __forceinline__ void mbar_init_1(uint32_t bar, uint32_t count) {
    asm volatile(ELECT "mbarrier.init.shared::cta.b64 [%0], %1;\n}" ::"r"(bar), "r"(count) : "memory");
}
__device__ __forceinline__ void mbar_expect_tx_1(uint32_t bar, uint32_t bytes) {
    asm volatile(ELECT "mbarrier.arrive.expect_tx.shared::cta.b64 _, [%0], %1;\n}" ::"r"(bar), "r"(bytes) : "memory");
}
__device__ __forceinline__ void mbar_arrive_1(uint32_t bar) {
    asm volatile(ELECT "mbarrier.arrive.shared::cta.b64 _, [%0];\n}" ::"r"(bar) : "memory");
}
__device__ __forceinline__ void mbar_wait(uint32_t bar, uint32_t parity) {
    uint32_t done;
    uint32_t spins = 0;
    do {
        asm volatile(
            "{\n.reg .pred p;\n"
            "mbarrier.try_wait.parity.shared::cta.b64 p, [%1], %2;\n"
            "selp.u32 %0, 1, 0, p;\n}"
            : "=r"(done) : "r"(bar), "r"(parity) : "memory");
    } while (!done && ++spins < SPIN_LIMIT);
}
__device__ __forceinline__ void mbar_wait_w(uint32_t bar, uint32_t parity) {
    mbar_wait(bar, parity);
    __syncwarp();
}
__device__ __forceinline__ bool mbar_test_w(uint32_t bar, uint32_t parity) {
    uint32_t done;
    asm volatile(
        "{\n.reg .pred p;\n"
        "mbarrier.test_wait.parity.shared::cta.b64 p, [%1], %2;\n"
        "selp.u32 %0, 1, 0, p;\n}"
        : "=r"(done) : "r"(bar), "r"(parity) : "memory");
    return __all_sync(0xffffffffu, done);
}
__device__ __forceinline__ bool mbar_try_w(uint32_t bar, uint32_t parity, uint32_t ns) {
    uint32_t done;
    asm volatile(
        "{\n.reg .pred p;\n"
        "mbarrier.try_wait.parity.shared::cta.b64 p, [%1], %2, %3;\n"
        "selp.u32 %0, 1, 0, p;\n}"
        : "=r"(done) : "r"(bar), "r"(parity), "r"(ns) : "memory");
    return __all_sync(0xffffffffu, done);
}
__device__ __forceinline__ void mbar_arrive_cta(uint32_t bar, uint32_t cta) {
    asm volatile(
        "{\n.reg .b32 ra;\n"
        "mapa.shared::cluster.u32 ra, %0, %1;\n"
        "mbarrier.arrive.shared::cluster.b64 _, [ra];\n}"
        ::"r"(bar), "r"(cta) : "memory");
}
__device__ __forceinline__ void st_async_peer(uint32_t addr, uint32_t val, uint32_t bar) {
    asm volatile(
        "{\n.reg .b32 ra, rb;\n"
        "mapa.shared::cluster.u32 ra, %0, 1;\n"
        "mapa.shared::cluster.u32 rb, %2, 1;\n"
        "st.async.weak.shared::cluster.mbarrier::complete_tx::bytes.b32 [ra], %1, [rb];\n}"
        ::"r"(addr), "r"(val), "r"(bar) : "memory");
}
__device__ __forceinline__ uint32_t lds32(uint32_t addr) {
    uint32_t v;
    asm volatile("ld.shared.b32 %0, [%1];" : "=r"(v) : "r"(addr) : "memory");
    return v;
}
__device__ __forceinline__ uint32_t uniform(uint32_t v) {
    return __shfl_sync(0xffffffffu, v, 0);
}
__device__ __forceinline__ void sts32(uint32_t addr, uint32_t v) {
    asm volatile("st.shared.b32 [%0], %1;" ::"r"(addr), "r"(v) : "memory");
}
__device__ __forceinline__ void tma_load_w_1(uint32_t dst, const CUtensorMap* map, uint32_t bar, int n) {
    asm volatile(
        ELECT "cp.async.bulk.tensor.3d.shared::cluster.global.mbarrier::complete_tx::bytes [%0], [%1, {%3, %4, %4}], [%2];\n}"
        ::"r"(dst), "l"(map), "r"(bar), "r"(n), "r"(0) : "memory");
}
__device__ __forceinline__ void tma_load_x_1(uint32_t dst, const CUtensorMap* map, uint32_t bar, int group, uint64_t policy) {
    asm volatile(
        ELECT "cp.async.bulk.tensor.4d.shared::cluster.global.mbarrier::complete_tx::bytes.multicast::cluster.L2::cache_hint"
        " [%0], [%1, {%3, %3, %3, %4}], [%2], %5, %6;\n}"
        ::"r"(dst), "l"(map), "r"(bar), "r"(0), "r"(group), "h"((uint16_t)3), "l"(policy) : "memory");
}
__device__ __forceinline__ void tma_store_1(const CUtensorMap* map, uint32_t src, int ch, int pix) {
    asm volatile(
        ELECT "cp.async.bulk.tensor.2d.global.shared::cta.bulk_group [%0, {%2, %3}], [%1];\n}\n"
        "cp.async.bulk.commit_group;"
        ::"l"(map), "r"(src), "r"(ch), "r"(pix) : "memory");
}
template <int N>
__device__ __forceinline__ void stores_read_wait() {
    asm volatile("cp.async.bulk.wait_group.read %0;" ::"n"(N) : "memory");
}
__device__ __forceinline__ void prefetch_map_1(const CUtensorMap* map) {
    asm volatile(ELECT "prefetch.tensormap [%0];\n}" ::"l"(map) : "memory");
}
__device__ __forceinline__ uint32_t timer_ns() {
    uint32_t t;
    asm volatile("mov.u32 %0, %%globaltimer_lo;" : "=r"(t)::"memory");
    return t;
}
__device__ __forceinline__ void cluster_arrive() {
    asm volatile("barrier.cluster.arrive.relaxed.aligned;" ::: "memory");
}
__device__ __forceinline__ void cluster_wait() {
    asm volatile("barrier.cluster.wait.aligned;" ::: "memory");
}
__device__ __forceinline__ void publish_barriers() {
    asm volatile("fence.mbarrier_init.release.cluster;" ::: "memory");
    asm volatile("fence.proxy.async.shared::cta;" ::: "memory");
}

__device__ __forceinline__ void wgmma_rs_n64(float (&d)[32], const uint32_t* a, uint64_t desc, int scale_d) {
    asm volatile(
        "{\n.reg .pred p;\n"
        "setp.ne.b32 p, %37, 0;\n"
        "wgmma.mma_async.sync.aligned.m64n64k16.f32.bf16.bf16 "
        "{%0, %1, %2, %3, %4, %5, %6, %7, %8, %9, %10, %11, %12, %13, %14, %15, "
        "%16, %17, %18, %19, %20, %21, %22, %23, %24, %25, %26, %27, %28, %29, %30, %31}, "
        "{%32, %33, %34, %35}, %36, p, 1, 1, 0;\n}"
        : "+f"(d[0]), "+f"(d[1]), "+f"(d[2]), "+f"(d[3]), "+f"(d[4]), "+f"(d[5]), "+f"(d[6]), "+f"(d[7]),
          "+f"(d[8]), "+f"(d[9]), "+f"(d[10]), "+f"(d[11]), "+f"(d[12]), "+f"(d[13]), "+f"(d[14]), "+f"(d[15]),
          "+f"(d[16]), "+f"(d[17]), "+f"(d[18]), "+f"(d[19]), "+f"(d[20]), "+f"(d[21]), "+f"(d[22]), "+f"(d[23]),
          "+f"(d[24]), "+f"(d[25]), "+f"(d[26]), "+f"(d[27]), "+f"(d[28]), "+f"(d[29]), "+f"(d[30]), "+f"(d[31])
        : "r"(a[0]), "r"(a[1]), "r"(a[2]), "r"(a[3]), "l"(desc), "r"(scale_d));
}

__device__ __forceinline__ uint32_t pack_bias(float lo, float hi, uint32_t bias2) {
    uint32_t r;
    asm("{\n.reg .b32 t;\n"
        "cvt.rn.bf16x2.f32 t, %2, %1;\n"
        "add.rn.bf16x2 %0, t, %3;\n}"
        : "=r"(r) : "f"(lo), "f"(hi), "r"(bias2));
    return r;
}

__device__ __forceinline__ int slice_channel(uint32_t rank, int wg) {
    return (wg * 2 + rank) * 64;
}

struct Consumer {
    uint32_t wreg[96];
    uint32_t bias_lo, bias_hi, st_addr, bars;
    uint64_t desc_base;
    int wg, lane;
};
struct Ring {
    uint32_t s, ob, phase;
};
__device__ __forceinline__ uint32_t next_slot(const Tune& tune, uint32_t s, uint32_t next_i) {
    return (s == 3 || (s == 2 && next_i >= TP(RING3_AT))) ? 0 : s + 1;
}
__device__ __forceinline__ uint32_t next_buffer(const Tune& tune, uint32_t ob, uint32_t next_i) {
    return ob != 2 ? ob + 1 : next_i >= TP(RING3_AT) ? 0 : 2;
}

__device__ __forceinline__ void consume(const Tune& tune, const Consumer& c, Ring& r, float (&acc)[32], uint32_t i, bool early) {
    const int next_turn = 4 + (c.wg + 1) % NUM_WG;
    if ((i | c.wg) != 0) asm volatile("bar.sync %0, 256;" ::"r"(4 + c.wg) : "memory");
    TRE(1 + c.wg * 2, i);
    const uint64_t desc = c.desc_base + (uint64_t)(r.s * (STAGE_BYTES >> 4));
    asm volatile("wgmma.fence.sync.aligned;" ::: "memory");
#pragma unroll
    for (int ks = 0; ks < 24; ks++) {
        const uint64_t d = desc + (uint64_t)((ks >> 2) * 64 + (ks & 3) * 2);
        wgmma_rs_n64(acc, &c.wreg[ks * 4], d, ks != 0);
        if (ks + 1 == EARLY_AT && early) asm volatile("bar.arrive %0, 256;" ::"r"(next_turn) : "memory");
    }
    asm volatile("wgmma.commit_group.sync.aligned;" ::: "memory");
    asm volatile("wgmma.wait_group.sync.aligned 0;" ::: "memory");
#pragma unroll
    for (int j = 0; j < 32; j++) asm volatile("" : "+f"(acc[j])::"memory");
    if (!early) asm volatile("bar.arrive %0, 256;" ::"r"(next_turn) : "memory");
    TRE(2 + c.wg * 2, i);
    if (c.lane < 2) mbar_arrive_cta(c.bars + BAR_EMPTY + 8 * r.s, c.lane);
    const uint32_t obar = c.bars + (r.ob * 4 + c.wg) * 8;
    mbar_wait_w(obar + BAR_OFREE, (r.phase >> (4 + r.ob)) & 1);
    const uint32_t dst = c.st_addr + r.ob * HALF_BYTES;
#pragma unroll
    for (int j = 0; j < 4; j++) {
        const uint32_t r0 = pack_bias(acc[8 * j + 0], acc[8 * j + 1], c.bias_lo);
        const uint32_t r1 = pack_bias(acc[8 * j + 2], acc[8 * j + 3], c.bias_hi);
        const uint32_t r2 = pack_bias(acc[8 * j + 4], acc[8 * j + 5], c.bias_lo);
        const uint32_t r3 = pack_bias(acc[8 * j + 6], acc[8 * j + 7], c.bias_hi);
        asm volatile("stmatrix.sync.aligned.m8n8.x4.trans.shared.b16 [%0], {%1, %2, %3, %4};"
                     ::"r"(dst + j * 2048), "r"(r0), "r"(r1), "r"(r2), "r"(r3) : "memory");
    }
    asm volatile("fence.proxy.async.shared::cta;" ::: "memory");
    __syncwarp();
    mbar_arrive_1(obar + BAR_OFULL);
    TRE(8 + c.wg, i);
    r.phase ^= (1u << r.s) | (16u << r.ob);
    r.s  = next_slot(tune, r.s, i + 1);
    r.ob = next_buffer(tune, r.ob, i + 1);
}

struct StoreQueue {
    uint32_t items, count;
};
__device__ __forceinline__ void release_oldest(StoreQueue& q, uint32_t bars) {
    if (q.count == 1) stores_read_wait<0>();
    else if (q.count == 2) stores_read_wait<1>();
    else if (q.count == 3) stores_read_wait<2>();
    else stores_read_wait<3>();
    mbar_arrive_1(bars + BAR_OFREE + (q.items & 15) * 8);
    q.items >>= 4;
    q.count--;
}

__global__ void __cluster_dims__(2, 1, 1) __launch_bounds__(THREADS, 1)
conv1x1_kernel(const __grid_constant__ Maps maps,
               const uint8_t* __restrict__ x_raw,
               const uint16_t* __restrict__ bias,
               uint32_t num_tiles,
               const __grid_constant__ Tune tune) {
    extern __shared__ uint8_t smem_raw[];
    const uint32_t smem = (smem_u32(smem_raw) + 1023u) & ~1023u;
    const uint32_t bars = smem + SMEM_BAR;

    const int warp = uniform(threadIdx.x >> 5);
    const int lane = threadIdx.x & 31;
    const uint32_t rank         = blockIdx.x & 1;
    const uint32_t cluster      = blockIdx.x >> 1;
    const uint32_t num_clusters = gridDim.x >> 1;

    if (warp < NUM_WG * 4) {
        cluster_arrive();
        asm volatile("setmaxnreg.inc.sync.aligned.u32 160;");
        const int wg = warp >> 2;
        const int wq = warp & 3;
        Consumer c;
        c.wg = wg;
        c.lane = lane;
        c.bars = bars;
        c.bias_lo = bias[slice_channel(rank, wg) + wq * 16 + (lane >> 2)] * 0x10001u;
        c.bias_hi = bias[slice_channel(rank, wg) + wq * 16 + (lane >> 2) + 8] * 0x10001u;

        cluster_wait();
        TRE(1 + wg, 63);
        mbar_wait_w(bars + BAR_W + 8 * wg, 0);
        TRE(4 + wg, 63);
        {
            const int r = lane & 7, m = lane >> 3;
            const uint32_t base = smem + wg * STAGE_BYTES + ((m >> 1) * 8 + r) * 128 + (((2 * wq + (m & 1)) ^ r) << 4);
#pragma unroll
            for (int ks = 0; ks < 24; ks++) {
                asm volatile("ldmatrix.sync.aligned.m8n8.x4.trans.shared.b16 {%0, %1, %2, %3}, [%4];"
                             : "=r"(c.wreg[ks * 4 + 0]), "=r"(c.wreg[ks * 4 + 1]), "=r"(c.wreg[ks * 4 + 2]), "=r"(c.wreg[ks * 4 + 3])
                             : "r"(base + ks * 2048) : "memory");
            }
        }
        uint32_t dep = 0;
#pragma unroll
        for (int ks = 0; ks < 24; ks++) dep ^= c.wreg[ks * 4];
        dep &= num_tiles >> 31;
        __syncwarp();
        if (lane < 6) mbar_arrive_cta(bars + BAR_EMPTY + 8 * wg + dep, lane & 1);
        TRE(1 + wg, 60);

        c.st_addr = smem + SMEM_OUT + wg * SLICE_BYTES + ((lane >> 4) * 8 + (lane & 7)) * 128 + (((2 * wq + ((lane >> 3) & 1)) ^ (lane & 7)) << 4);
        c.desc_base = (uint64_t)((smem & 0x3FFFF) >> 4) | ((uint64_t)1 << 16) | ((uint64_t)(6144 >> 4) << 32) | ((uint64_t)1 << 62);

        float acc[32];
        Ring r = {3, 2, 0x70};
        for (uint32_t i = 0;; i++) {
            mbar_wait(bars + BAR_FULL + 8 * r.s, (r.phase >> r.s) & 1);
            const uint32_t id = lds32(bars + ID_AT + 4 * (i & (ID_SLOTS - 1)));
            if (id >= num_tiles) break;
            consume(tune, c, r, acc, i, id + TP(EARLY_TILES) >= num_tiles || id + 1 <= TP(EARLY_HEAD));
        }
        if (wg == 0) {
            mbar_wait_w(bars + BAR_OFREE + r.ob * 32, (r.phase >> (4 + r.ob)) & 1);
            mbar_arrive_1(bars + BAR_OFULL + r.ob * 32);
            asm volatile("bar.sync 4, 256;" ::: "memory");
        }
        TRE(1 + wg, 62);
    } else {
        asm volatile("setmaxnreg.dec.sync.aligned.u32 32;");
        if (warp == NUM_WG * 4) {
#pragma unroll
            for (int j = 0; j < NUM_WG; j++) mbar_init_1(bars + BAR_W + 8 * j, 1);
            publish_barriers();
            cluster_arrive();
            sts32(bars + ID_AT, cluster);
#pragma unroll
            for (int j = 0; j < NUM_WG; j++) {
                if (j == (int)TP(W_FIRST)) {
                    cluster_wait();
                    TR(0, 0);
                    mbar_expect_tx_1(bars + BAR_FULL + 8 * 3, STAGE_BYTES);
                    tma_load_x_1(smem + 3 * STAGE_BYTES + rank * HALF_BYTES, &maps.x, bars + BAR_FULL + 8 * 3,
                                 cluster * 8 + rank * 4, TP(EF_HEAD) != 0 ? EVICT_FIRST : EVICT_NORMAL);
                }
                mbar_expect_tx_1(bars + BAR_W + 8 * j, STAGE_BYTES);
                tma_load_w_1(smem + j * STAGE_BYTES, &maps.w, bars + BAR_W + 8 * j, slice_channel(rank, j));
                if (j == 0) TR(2, 61);
            }
            const uint32_t first_dynamic = TP(N_STATIC) * num_clusters;
            const uint32_t wrap = num_tiles - first_dynamic + num_clusters - 1;
            uint32_t s = 3, fph = 8, eph = 0, s1 = 3, s2 = 3, id = 0;
#pragma unroll 1
            for (uint32_t i = 1;; i++) {
                s2 = s1;
                s1 = s;
                s = next_slot(tune, s, i);
                const uint32_t slot = bars + ID_AT + 4 * (i & (ID_SLOTS - 1));
                const bool deep = id + TP(DEEP_AT) >= num_tiles;
                id = cluster + i * num_clusters;
                if (i >= TP(N_STATIC)) {
                    const uint32_t b = bars + BAR_ID + 8 * ((i - TP(N_STATIC)) & (ID_BARS - 1));
                    if (rank == 0) {
                        if (deep) mbar_wait_w(bars + BAR_EMPTY + 8 * s, (eph >> s) & 1);
                        else if (i > TP(N_STATIC)) mbar_wait_w(bars + BAR_FULL + 8 * s2, ((fph >> s2) & 1) ^ 1);
                        if (lane == 0) {
                            id = first_dynamic + atomicInc(&g_tile_counter, wrap);
                            st_async_peer(slot, id, b);
                        }
                    } else {
                        mbar_expect_tx_1(b, 4);
                        mbar_wait_w(b, ((i - TP(N_STATIC)) / ID_BARS) & 1);
                        id = lds32(slot);
                    }
                    id = uniform(id);
                }
                sts32(slot, id);
                sts32(bars + FRONT_AT, id);
                TR(7, i);
                mbar_wait_w(bars + BAR_EMPTY + 8 * s, (eph >> s) & 1);
                eph ^= 1u << s;
                fph ^= 1u << s;
                const uint32_t full = bars + BAR_FULL + 8 * s;
                if (id >= num_tiles) {
                    mbar_arrive_1(full);
#pragma unroll 1
                    for (uint32_t u = 0; u < STAGES; u++)
                        if (u != s) mbar_wait_w(bars + BAR_EMPTY + 8 * u, (eph >> u) & 1);
                    break;
                }
                TR(0, i);
                TRV(15, i, id);
                mbar_expect_tx_1(full, STAGE_BYTES);
                tma_load_x_1(smem + s * STAGE_BYTES + rank * HALF_BYTES, &maps.x, full, id * 8 + rank * 4,
                             id + TP(EF_TAIL) >= num_tiles || id + 1 <= TP(EF_HEAD) ? EVICT_FIRST : EVICT_NORMAL);
            }
        } else if (warp == NUM_WG * 4 + 1) {
#pragma unroll
            for (int s = 0; s < STAGES; s++) {
                mbar_init_1(bars + BAR_FULL + 8 * s, 1);
                mbar_init_1(bars + BAR_EMPTY + 8 * s, NUM_WG * 4 * 2);
            }
#pragma unroll
            for (int s = 0; s < ID_BARS; s++) mbar_init_1(bars + BAR_ID + 8 * s, 1);
            publish_barriers();
            cluster_arrive();
            TR(0, 61);
            cluster_wait();
            prefetch_map_1(&maps.out);
        } else if (warp == NUM_WG * 4 + 2) {
#pragma unroll
            for (int b = 0; b < 3; b++) {
#pragma unroll
                for (int w = 0; w < NUM_WG; w++) {
                    mbar_init_1(bars + BAR_OFREE + b * 32 + w * 8, 1);
                    mbar_init_1(bars + BAR_OFULL + b * 32 + w * 8, 4);
                }
            }
            publish_barriers();
            cluster_arrive();
            cluster_wait();
            const uint32_t lag_at = TP(RING3_AT) + TP(LAG_AT) + cluster % TP(LAG_SPREAD);
            StoreQueue q = {0, 0};
            uint32_t ob = 2, phase = 0;
#pragma unroll 1
            for (uint32_t j = 0;; j++) {
                uint32_t lag = (j >= lag_at) + (j >= lag_at + TP(LAG_GAP));
#pragma unroll 1
                for (uint32_t spins = 0; lag != 0 && spins < SPIN_LIMIT; spins++) {
                    const uint32_t front = uniform(lds32(bars + FRONT_AT));
                    if (front + TP(LAG_T2) >= num_tiles) break;
                    if (front + TP(LAG_T1) >= num_tiles) lag = 1;
                    uint32_t b = ob + lag;
                    if (b >= 3) b -= 3;
                    const uint32_t gate = bars + BAR_OFULL + b * 32 + TP(LAG_WG) * 8;
                    if (q.count != 0) {
                        if (mbar_test_w(gate, (phase >> b) & 1)) break;
                        release_oldest(q, bars);
                    } else if (mbar_try_w(gate, (phase >> b) & 1, 100)) {
                        break;
                    }
                }
                const uint32_t parity = (phase >> ob) & 1;
                uint32_t id = 0;
#pragma unroll 1
                for (uint32_t w = 0; w < NUM_WG; w++) {
                    const uint32_t slice = ob * 4 + w;
#pragma unroll 1
                    while (q.count != 0 && !mbar_test_w(bars + BAR_OFULL + slice * 8, parity)) release_oldest(q, bars);
                    if (q.count == 0) mbar_wait_w(bars + BAR_OFULL + slice * 8, parity);
                    if (w == 0) {
                        id = uniform(lds32(bars + ID_AT + 4 * (j & (ID_SLOTS - 1))));
                        if (id >= num_tiles) break;
                    }
                    TR(11 + w, j);
                    tma_store_1(&maps.out, smem + SMEM_OUT + ob * HALF_BYTES + w * SLICE_BYTES, slice_channel(rank, w), id * TILE_PIX);
                    q.items |= slice << (4 * q.count);
                    if (++q.count == 4) release_oldest(q, bars);
                }
                if (id >= num_tiles) break;
                phase ^= 1u << ob;
                ob = next_buffer(tune, ob, j + 1);
            }
            stores_read_wait<0>();
            TR(4, 62);
        } else {
            const uint32_t t_start = timer_ns();
            cluster_arrive();
            prefetch_map_1(&maps.x);
            uint32_t due = t_start + TP(PM_T0);
#pragma unroll 1
            for (uint32_t piece = TP(PM_FIRST); piece < TP(PM_E4); piece++) {
#pragma unroll 1
                for (uint32_t spins = 0; spins < 4096 && (int32_t)(timer_ns() - due) < 0; spins++) __nanosleep(32);
                due += piece < TP(PM_E1) ? TP(PM_DT1) : piece < TP(PM_E2) ? TP(PM_DT2) : piece < TP(PM_E3) ? TP(PM_DT3) : TP(PM_DT4);
                const uint32_t t = cluster + piece / 6 * num_clusters;
                if (t >= num_tiles) break;
                const uint8_t* p = x_raw + (size_t)t * STAGE_BYTES + rank * HALF_BYTES + (piece % 6) * 4096;
                asm volatile("prefetch.global.L2 [%0];" ::"l"(p + lane * 128) : "memory");
            }
            cluster_wait();
        }
    }
}

typedef CUresult (*EncodeTiledFn)(CUtensorMap*, CUtensorMapDataType, cuuint32_t, void*, const cuuint64_t*,
                                  const cuuint64_t*, const cuuint32_t*, const cuuint32_t*, CUtensorMapInterleave,
                                  CUtensorMapSwizzle, CUtensorMapL2promotion, CUtensorMapFloatOOBfill);

}

extern "C" void kernel_launch(void* const* d_in, const int* in_sizes, int n_in, void* d_out, int out_size) {
    (void)n_in;
    (void)out_size;
    void* x = d_in[0];
    void* w = d_in[1];
    const uint16_t* b = (const uint16_t*)d_in[2];
    const int M = in_sizes[0] / C;
    const int num_tiles = M / TILE_PIX;

    static EncodeTiledFn encode = nullptr;
    static int sms = 0;
    if (!encode) {
        void* fn = nullptr;
        cudaDriverEntryPointQueryResult q;
        cudaGetDriverEntryPoint("cuTensorMapEncodeTiled", &fn, cudaEnableDefault, &q);
        encode = (EncodeTiledFn)fn;
        cudaDeviceGetAttribute(&sms, cudaDevAttrMultiProcessorCount, 0);
        cudaFuncSetAttribute(conv1x1_kernel, cudaFuncAttributeMaxDynamicSharedMemorySize, SMEM_TOTAL);
    }

    Maps maps;
    const cuuint32_t ones[4] = {1, 1, 1, 1};
    auto make = [&](CUtensorMap* map, int rank, void* base, const cuuint64_t* dims, const cuuint64_t* strides,
                    const cuuint32_t* box, CUtensorMapL2promotion promo) {
        encode(map, CU_TENSOR_MAP_DATA_TYPE_BFLOAT16, rank, base, dims, strides, box, ones, CU_TENSOR_MAP_INTERLEAVE_NONE,
               CU_TENSOR_MAP_SWIZZLE_128B, promo, CU_TENSOR_MAP_FLOAT_OOB_FILL_NONE);
    };
    {
        const cuuint64_t dims[4]    = {64, 8, 6, (cuuint64_t)(M / 8)};
        const cuuint64_t strides[3] = {C * 2, 128, 8 * C * 2};
        const cuuint32_t box[4]     = {64, 8, 6, TILE_PIX / 16};
        make(&maps.x, 4, x, dims, strides, box, CU_TENSOR_MAP_L2_PROMOTION_L2_128B);
    }
    {
        const cuuint64_t dims[3]    = {C, C / 2, 2};
        const cuuint64_t strides[2] = {C * 2, C * C};
        const cuuint32_t box[3]     = {64, C / 2, 2};
        make(&maps.w, 3, w, dims, strides, box, CU_TENSOR_MAP_L2_PROMOTION_L2_128B);
    }
    {
        const cuuint64_t dims[2]    = {C, (cuuint64_t)M};
        const cuuint64_t strides[1] = {C * 2};
        const cuuint32_t box[2]     = {64, TILE_PIX};
        make(&maps.out, 2, d_out, dims, strides, box, CU_TENSOR_MAP_L2_PROMOTION_NONE);
    }

    const Tune tune;
    int clusters = sms / 2;
    if (clusters > num_tiles / (int)TP(N_STATIC)) clusters = num_tiles / (int)TP(N_STATIC);
    conv1x1_kernel<<<clusters * 2, THREADS, SMEM_TOTAL>>>(maps, (const uint8_t*)x, b, (uint32_t)num_tiles, tune);
}
```

```cpp
#include <cuda_runtime.h>
#include <cuda_bf16.h>
#include <cuda.h>
#include <stdint.h>

#define EARLY_AT 18

#define W_FIRST 2
#define PRE_X 1
#define PRE_W 64
#define W_LSU 0
#define W_DELAY 0
#define PRE_DELAY 0
#define PRE_MAP 1

#define TUNABLES(F) \
    F(EARLY_TILES, 198)    \
    F(EARLY_HEAD, 0)       \
    F(N_STATIC, 21)        \
    F(PM_T0, 0)            \
    F(PM_DT1, 465)         \
    F(PM_E1, 15) \
    F(PM_DT2, 375) \
    F(PM_E2, 22) \
    F(PM_DT3, 940) \
    F(PM_E3, 51) \
    F(PM_DT4, 800) \
    F(PM_E4, 72) \
    F(PM_STAG, 150)        \
    F(LEAD_A, 280)        \
    F(LEAD_F, 400)         \
    F(LEAD_S, 3)           \
    F(LEAD_B, 134)        \
    F(PM_SLACK, 450)    \
    F(EAGER_TO, 2200)         \
    F(EF_TAIL, 300)        \
    F(RING3_AT, 4)        \
    F(LAG_AT, 0)           \
    F(LAG_SPREAD, 3)       \
    F(LAG_GAP, 5)          \
    F(LAG_WG, 2)           \
    F(LAG_T1, 32)          \
    F(LAG_T2, 18)           \
    F(DEEP_AT, 90)          \
    F(X0, 0) \
    F(X1, 0) \
    F(X2, 0) \
    F(X3, 0)

struct Tune {
#define F(n, v) static constexpr uint32_t n = v;
    TUNABLES(F)
#undef F
};
#define TP(n) (Tune::n)

#define TRV(slot, idx, v)
#define TR(slot, idx)
#define TRE(slot, idx)

namespace {

constexpr int C            = 384;
constexpr int TILE_PIX     = 64;
constexpr int STAGES       = 4;
constexpr int STAGE_BYTES  = TILE_PIX * C * 2;
constexpr int HALF_BYTES   = STAGE_BYTES / 2;
constexpr int SLICE_BYTES  = TILE_PIX * 128;
constexpr int W_LINES      = C * C * 2 / 128;
constexpr int NUM_WG       = 3;
constexpr int THREADS      = (NUM_WG + 1) * 128;
constexpr int SMEM_OUT     = 3 * STAGE_BYTES;
constexpr int SMEM_BAR     = SMEM_OUT + 3 * HALF_BYTES;
constexpr int SMEM_TOTAL   = SMEM_BAR + 512 + 1024;
constexpr int ID_SLOTS     = 16;
constexpr int ID_BARS      = 4;
constexpr uint32_t SPIN_LIMIT = 1u << 24;
constexpr int BAR_W     = 0;
constexpr int BAR_FULL  = 32;
constexpr int BAR_EMPTY = BAR_FULL + 8 * STAGES;
constexpr int BAR_ID    = BAR_EMPTY + 8 * STAGES;
constexpr int BAR_OFREE = BAR_ID + 8 * ID_BARS;
constexpr int BAR_OFULL = BAR_OFREE + 8 * 12;
constexpr int ID_AT     = BAR_OFULL + 8 * 12;
constexpr int FRONT_AT  = ID_AT + 4 * ID_SLOTS;
constexpr int ISSUED_AT = FRONT_AT + 4;
constexpr uint64_t EVICT_NORMAL = 0x1000000000000000ull;
constexpr uint64_t EVICT_FIRST  = 0x12F0000000000000ull;

struct Maps {
    CUtensorMap w, x, out;
};

__device__ unsigned int g_tile_counter;

#define ELECT "{\n.reg .pred e;\nelect.sync _|e, 0xffffffff;\n@e "

__device__ __forceinline__ uint32_t smem_u32(const void* p) {
    return (uint32_t)__cvta_generic_to_shared(p);
}
__device__ __forceinline__ void mbar_init_1(uint32_t bar, uint32_t count) {
    asm volatile(ELECT "mbarrier.init.shared::cta.b64 [%0], %1;\n}" ::"r"(bar), "r"(count) : "memory");
}
__device__ __forceinline__ void mbar_expect_tx_1(uint32_t bar, uint32_t bytes) {
    asm volatile(ELECT "mbarrier.arrive.expect_tx.shared::cta.b64 _, [%0], %1;\n}" ::"r"(bar), "r"(bytes) : "memory");
}
__device__ __forceinline__ void mbar_arrive_1(uint32_t bar) {
    asm volatile(ELECT "mbarrier.arrive.shared::cta.b64 _, [%0];\n}" ::"r"(bar) : "memory");
}
__device__ __forceinline__ void mbar_wait(uint32_t bar, uint32_t parity) {
    uint32_t done;
    uint32_t spins = 0;
    do {
        asm volatile(
            "{\n.reg .pred p;\n"
            "mbarrier.try_wait.parity.shared::cta.b64 p, [%1], %2;\n"
            "selp.u32 %0, 1, 0, p;\n}"
            : "=r"(done) : "r"(bar), "r"(parity) : "memory");
    } while (!done && ++spins < SPIN_LIMIT);
}
__device__ __forceinline__ void mbar_wait_w(uint32_t bar, uint32_t parity) {
    mbar_wait(bar, parity);
    __syncwarp();
}
__device__ __forceinline__ bool mbar_test_w(uint32_t bar, uint32_t parity) {
    uint32_t done;
    asm volatile(
        "{\n.reg .pred p;\n"
        "mbarrier.test_wait.parity.shared::cta.b64 p, [%1], %2;\n"
        "selp.u32 %0, 1, 0, p;\n}"
        : "=r"(done) : "r"(bar), "r"(parity) : "memory");
    return __all_sync(0xffffffffu, done);
}
__device__ __forceinline__ bool mbar_try_w(uint32_t bar, uint32_t parity, uint32_t ns) {
    uint32_t done;
    asm volatile(
        "{\n.reg .pred p;\n"
        "mbarrier.try_wait.parity.shared::cta.b64 p, [%1], %2, %3;\n"
        "selp.u32 %0, 1, 0, p;\n}"
        : "=r"(done) : "r"(bar), "r"(parity), "r"(ns) : "memory");
    return __all_sync(0xffffffffu, done);
}
__device__ __forceinline__ void mbar_arrive_cta(uint32_t bar, uint32_t cta) {
    asm volatile(
        "{\n.reg .b32 ra;\n"
        "mapa.shared::cluster.u32 ra, %0, %1;\n"
        "mbarrier.arrive.shared::cluster.b64 _, [ra];\n}"
        ::"r"(bar), "r"(cta) : "memory");
}
__device__ __forceinline__ void st_async_peer(uint32_t addr, uint32_t val, uint32_t bar) {
    asm volatile(
        "{\n.reg .b32 ra, rb;\n"
        "mapa.shared::cluster.u32 ra, %0, 1;\n"
        "mapa.shared::cluster.u32 rb, %2, 1;\n"
        "st.async.weak.shared::cluster.mbarrier::complete_tx::bytes.b32 [ra], %1, [rb];\n}"
        ::"r"(addr), "r"(val), "r"(bar) : "memory");
}
__device__ __forceinline__ uint32_t lds32(uint32_t addr) {
    uint32_t v;
    asm volatile("ld.shared.b32 %0, [%1];" : "=r"(v) : "r"(addr) : "memory");
    return v;
}
__device__ __forceinline__ uint32_t uniform(uint32_t v) {
    return __shfl_sync(0xffffffffu, v, 0);
}
__device__ __forceinline__ void sts32(uint32_t addr, uint32_t v) {
    asm volatile("st.shared.b32 [%0], %1;" ::"r"(addr), "r"(v) : "memory");
}
__device__ __forceinline__ void tma_load_w_1(uint32_t dst, const CUtensorMap* map, uint32_t bar, int n) {
    asm volatile(
        ELECT "cp.async.bulk.tensor.3d.shared::cluster.global.mbarrier::complete_tx::bytes [%0], [%1, {%3, %4, %4}], [%2];\n}"
        ::"r"(dst), "l"(map), "r"(bar), "r"(n), "r"(0) : "memory");
}
__device__ __forceinline__ void tma_load_x_1(uint32_t dst, const CUtensorMap* map, uint32_t bar, int group, uint64_t policy) {
    asm volatile(
        ELECT "cp.async.bulk.tensor.4d.shared::cluster.global.mbarrier::complete_tx::bytes.multicast::cluster.L2::cache_hint"
        " [%0], [%1, {%3, %3, %3, %4}], [%2], %5, %6;\n}"
        ::"r"(dst), "l"(map), "r"(bar), "r"(0), "r"(group), "h"((uint16_t)3), "l"(policy) : "memory");
}
__device__ __forceinline__ void tma_store_1(const CUtensorMap* map, uint32_t src, int ch, int pix) {
    asm volatile(
        ELECT "cp.async.bulk.tensor.2d.global.shared::cta.bulk_group [%0, {%2, %3}], [%1];\n}\n"
        "cp.async.bulk.commit_group;"
        ::"l"(map), "r"(src), "r"(ch), "r"(pix) : "memory");
}
template <int N>
__device__ __forceinline__ void stores_read_wait() {
    asm volatile("cp.async.bulk.wait_group.read %0;" ::"n"(N) : "memory");
}
__device__ __forceinline__ void prefetch_map_1(const CUtensorMap* map) {
    asm volatile(ELECT "prefetch.tensormap [%0];\n}" ::"l"(map) : "memory");
}
__device__ __forceinline__ uint32_t timer_ns() {
    uint32_t t;
    asm volatile("mov.u32 %0, %%globaltimer_lo;" : "=r"(t)::"memory");
    return t;
}
__device__ __forceinline__ void cluster_arrive() {
    asm volatile("barrier.cluster.arrive.relaxed.aligned;" ::: "memory");
}
__device__ __forceinline__ void cluster_wait() {
    asm volatile("barrier.cluster.wait.aligned;" ::: "memory");
}
__device__ __forceinline__ void publish_barriers() {
    asm volatile("fence.mbarrier_init.release.cluster;" ::: "memory");
    asm volatile("fence.proxy.async.shared::cta;" ::: "memory");
}

__device__ __forceinline__ void wgmma_rs_n64(float (&d)[32], const uint32_t* a, uint64_t desc, int scale_d) {
    asm volatile(
        "{\n.reg .pred p;\n"
        "setp.ne.b32 p, %37, 0;\n"
        "wgmma.mma_async.sync.aligned.m64n64k16.f32.bf16.bf16 "
        "{%0, %1, %2, %3, %4, %5, %6, %7, %8, %9, %10, %11, %12, %13, %14, %15, "
        "%16, %17, %18, %19, %20, %21, %22, %23, %24, %25, %26, %27, %28, %29, %30, %31}, "
        "{%32, %33, %34, %35}, %36, p, 1, 1, 0;\n}"
        : "+f"(d[0]), "+f"(d[1]), "+f"(d[2]), "+f"(d[3]), "+f"(d[4]), "+f"(d[5]), "+f"(d[6]), "+f"(d[7]),
          "+f"(d[8]), "+f"(d[9]), "+f"(d[10]), "+f"(d[11]), "+f"(d[12]), "+f"(d[13]), "+f"(d[14]), "+f"(d[15]),
          "+f"(d[16]), "+f"(d[17]), "+f"(d[18]), "+f"(d[19]), "+f"(d[20]), "+f"(d[21]), "+f"(d[22]), "+f"(d[23]),
          "+f"(d[24]), "+f"(d[25]), "+f"(d[26]), "+f"(d[27]), "+f"(d[28]), "+f"(d[29]), "+f"(d[30]), "+f"(d[31])
        : "r"(a[0]), "r"(a[1]), "r"(a[2]), "r"(a[3]), "l"(desc), "r"(scale_d));
}

__device__ __forceinline__ uint32_t pack_bias(float lo, float hi, uint32_t bias2) {
    uint32_t r;
    asm("{\n.reg .b32 t;\n"
        "cvt.rn.bf16x2.f32 t, %2, %1;\n"
        "add.rn.bf16x2 %0, t, %3;\n}"
        : "=r"(r) : "f"(lo), "f"(hi), "r"(bias2));
    return r;
}

__device__ __forceinline__ int slice_channel(uint32_t rank, int wg) {
    return (wg * 2 + rank) * 64;
}

struct Consumer {
    uint32_t wreg[96];
    uint32_t bias_lo, bias_hi, st_addr, bars;
    uint64_t desc_base;
    int wg, lane;
};
struct Ring {
    uint32_t s, ob, phase;
};
__device__ __forceinline__ uint32_t next_slot(const Tune& tune, uint32_t s, uint32_t next_i) {
    return (s == 3 || (s == 2 && next_i >= TP(RING3_AT))) ? 0 : s + 1;
}
__device__ __forceinline__ uint32_t next_buffer(const Tune& tune, uint32_t ob, uint32_t next_i) {
    return ob != 2 ? ob + 1 : next_i >= TP(RING3_AT) ? 0 : 2;
}

__device__ __forceinline__ void consume(const Tune& tune, const Consumer& c, Ring& r, float (&acc)[32], uint32_t i, bool early) {
    const int next_turn = 4 + (c.wg + 1) % NUM_WG;
    if ((i | c.wg) != 0) asm volatile("bar.sync %0, 256;" ::"r"(4 + c.wg) : "memory");
    TRE(1 + c.wg * 2, i);
    const uint64_t desc = c.desc_base + (uint64_t)(r.s * (STAGE_BYTES >> 4));
    asm volatile("wgmma.fence.sync.aligned;" ::: "memory");
#pragma unroll
    for (int ks = 0; ks < 24; ks++) {
        const uint64_t d = desc + (uint64_t)((ks >> 2) * 64 + (ks & 3) * 2);
        wgmma_rs_n64(acc, &c.wreg[ks * 4], d, ks != 0);
        if (ks + 1 == EARLY_AT && early) asm volatile("bar.arrive %0, 256;" ::"r"(next_turn) : "memory");
    }
    asm volatile("wgmma.commit_group.sync.aligned;" ::: "memory");
    asm volatile("wgmma.wait_group.sync.aligned 0;" ::: "memory");
#pragma unroll
    for (int j = 0; j < 32; j++) asm volatile("" : "+f"(acc[j])::"memory");
    if (!early) asm volatile("bar.arrive %0, 256;" ::"r"(next_turn) : "memory");
    TRE(2 + c.wg * 2, i);
    if (c.lane < 2) mbar_arrive_cta(c.bars + BAR_EMPTY + 8 * r.s, c.lane);
    const uint32_t obar = c.bars + (r.ob * 4 + c.wg) * 8;
    mbar_wait_w(obar + BAR_OFREE, (r.phase >> (4 + r.ob)) & 1);
    const uint32_t dst = c.st_addr + r.ob * HALF_BYTES;
#pragma unroll
    for (int j = 0; j < 4; j++) {
        const uint32_t r0 = pack_bias(acc[8 * j + 0], acc[8 * j + 1], c.bias_lo);
        const uint32_t r1 = pack_bias(acc[8 * j + 2], acc[8 * j + 3], c.bias_hi);
        const uint32_t r2 = pack_bias(acc[8 * j + 4], acc[8 * j + 5], c.bias_lo);
        const uint32_t r3 = pack_bias(acc[8 * j + 6], acc[8 * j + 7], c.bias_hi);
        asm volatile("stmatrix.sync.aligned.m8n8.x4.trans.shared.b16 [%0], {%1, %2, %3, %4};"
                     ::"r"(dst + j * 2048), "r"(r0), "r"(r1), "r"(r2), "r"(r3) : "memory");
    }
    asm volatile("fence.proxy.async.shared::cta;" ::: "memory");
    __syncwarp();
    mbar_arrive_1(obar + BAR_OFULL);
    TRE(8 + c.wg, i);
    r.phase ^= (1u << r.s) | (16u << r.ob);
    r.s  = next_slot(tune, r.s, i + 1);
    r.ob = next_buffer(tune, r.ob, i + 1);
}

struct StoreQueue {
    uint32_t items, count;
};
__device__ __forceinline__ void release_oldest(StoreQueue& q, uint32_t bars) {
    if (q.count == 1) stores_read_wait<0>();
    else if (q.count == 2) stores_read_wait<1>();
    else if (q.count == 3) stores_read_wait<2>();
    else stores_read_wait<3>();
    mbar_arrive_1(bars + BAR_OFREE + (q.items & 15) * 8);
    q.items >>= 4;
    q.count--;
}

__global__ void __cluster_dims__(2, 1, 1) __launch_bounds__(THREADS, 1)
conv1x1_kernel(const uint8_t* __restrict__ x_raw,
               const uint8_t* __restrict__ w_raw,
               const uint16_t* __restrict__ bias,
               uint32_t num_tiles,
               uint32_t num_clusters,
               const __grid_constant__ Maps maps,
               const __grid_constant__ Tune tune) {
    if (threadIdx.x < 96) {
        const uint32_t line = blockIdx.x % (W_LINES / PRE_W) * PRE_W + threadIdx.x;
        if (threadIdx.x < PRE_W) asm volatile("prefetch.global.L2 [%0];" ::"l"(w_raw + line * 128) : "memory");
    } else if (threadIdx.x < 128) {
        if (PRE_MAP) {
            if (!W_LSU) prefetch_map_1(&maps.w);
            prefetch_map_1(&maps.x);
        }
    } else if (threadIdx.x < 128 + PRE_X * 96) {
        const uint8_t* p = x_raw + (size_t)blockIdx.x * HALF_BYTES + (threadIdx.x - 128) * 128;
        if (PRE_DELAY != 0) {
            asm volatile("" : "+l"(p));
            const uint32_t c0 = clock();
            while (clock() - c0 < PRE_DELAY) {}
        }
        asm volatile("prefetch.global.L2 [%0];" ::"l"(p) : "memory");
    }
    extern __shared__ uint8_t smem_raw[];
    const uint32_t smem = (smem_u32(smem_raw) + 1023u) & ~1023u;
    const uint32_t bars = smem + SMEM_BAR;

    const int warp = uniform(threadIdx.x >> 5);
    const int lane = threadIdx.x & 31;
    const uint32_t rank         = blockIdx.x & 1;
    const uint32_t cluster      = blockIdx.x >> 1;

    if (warp < NUM_WG * 4) {
        const int wg = warp >> 2;
        const int wq = warp & 3;
        cluster_arrive();
        if (W_LSU) {
            const int row = wq * 4 + (lane >> 3), chunk = lane & 7;
            const uint8_t* src = w_raw + row * (C * 2) + slice_channel(rank, wg) * 2 + chunk * 16;
            const uint32_t dst = smem + wg * STAGE_BYTES + row * 128 + ((chunk ^ (row & 7)) << 4);
            if (W_DELAY != 0 && wg != 0) __nanosleep(W_DELAY * wg);
#pragma unroll
            for (int ks = 0; ks < 24; ks++)
                asm volatile("cp.async.cg.shared.global [%0], [%1], 16;" ::"r"(dst + ks * 2048), "l"(src + ks * 16 * C * 2) : "memory");
        }
        asm volatile("setmaxnreg.inc.sync.aligned.u32 160;");
        Consumer c;
        c.wg = wg;
        c.lane = lane;
        c.bars = bars;
        c.bias_lo = bias[slice_channel(rank, wg) + wq * 16 + (lane >> 2)] * 0x10001u;
        c.bias_hi = bias[slice_channel(rank, wg) + wq * 16 + (lane >> 2) + 8] * 0x10001u;

        cluster_wait();
        TRE(1 + wg, 63);
        if (W_LSU) {
            asm volatile("cp.async.wait_all;" ::: "memory");
            asm volatile("bar.sync %0, 128;" ::"r"(1 + wg) : "memory");
        } else {
            mbar_wait_w(bars + BAR_W + 8 * wg, 0);
        }
        TRE(4 + wg, 63);
        {
            const int r = lane & 7, m = lane >> 3;
            const uint32_t base = smem + wg * STAGE_BYTES + ((m >> 1) * 8 + r) * 128 + (((2 * wq + (m & 1)) ^ r) << 4);
#pragma unroll
            for (int ks = 0; ks < 24; ks++) {
                asm volatile("ldmatrix.sync.aligned.m8n8.x4.trans.shared.b16 {%0, %1, %2, %3}, [%4];"
                             : "=r"(c.wreg[ks * 4 + 0]), "=r"(c.wreg[ks * 4 + 1]), "=r"(c.wreg[ks * 4 + 2]), "=r"(c.wreg[ks * 4 + 3])
                             : "r"(base + ks * 2048) : "memory");
            }
        }
        uint32_t dep = 0;
#pragma unroll
        for (int ks = 0; ks < 24; ks++) dep ^= c.wreg[ks * 4];
        dep &= num_tiles >> 31;
        if (W_LSU) asm volatile("fence.proxy.async.shared::cta;" ::: "memory");
        __syncwarp();
        if (lane < 6) mbar_arrive_cta(bars + BAR_EMPTY + 8 * wg + dep, lane & 1);
        TRE(1 + wg, 60);

        c.st_addr = smem + SMEM_OUT + wg * SLICE_BYTES + ((lane >> 4) * 8 + (lane & 7)) * 128 + (((2 * wq + ((lane >> 3) & 1)) ^ (lane & 7)) << 4);
        c.desc_base = (uint64_t)((smem & 0x3FFFF) >> 4) | ((uint64_t)1 << 16) | ((uint64_t)(6144 >> 4) << 32) | ((uint64_t)1 << 62);

        float acc[32];
        Ring r = {3, 2, 0x70};
        for (uint32_t i = 0;; i++) {
            mbar_wait(bars + BAR_FULL + 8 * r.s, (r.phase >> r.s) & 1);
            const uint32_t id = lds32(bars + ID_AT + 4 * (i & (ID_SLOTS - 1)));
            if (id >= num_tiles) break;
            consume(tune, c, r, acc, i, id + TP(EARLY_TILES) >= num_tiles || id + 1 <= TP(EARLY_HEAD));
        }
        if (wg == 0) {
            mbar_wait_w(bars + BAR_OFREE + r.ob * 32, (r.phase >> (4 + r.ob)) & 1);
            mbar_arrive_1(bars + BAR_OFULL + r.ob * 32);
            asm volatile("bar.sync 4, 256;" ::: "memory");
        }
        TRE(1 + wg, 62);
    } else {
        asm volatile("setmaxnreg.dec.sync.aligned.u32 32;");
        if (warp == NUM_WG * 4) {
#pragma unroll
            for (int j = 0; j < NUM_WG; j++) if (!W_LSU) mbar_init_1(bars + BAR_W + 8 * j, 1);
            if (!W_LSU) publish_barriers();
            cluster_arrive();
            sts32(bars + ID_AT, cluster);
#pragma unroll
            for (int j = 0; j < NUM_WG; j++) {
                if (j == W_FIRST) {
                    cluster_wait();
                    TR(0, 0);
                    mbar_expect_tx_1(bars + BAR_FULL + 8 * 3, STAGE_BYTES);
                    tma_load_x_1(smem + 3 * STAGE_BYTES + rank * HALF_BYTES, &maps.x, bars + BAR_FULL + 8 * 3,
                                 cluster * 8 + rank * 4, EVICT_NORMAL);
                }
                if (W_LSU) continue;
                mbar_expect_tx_1(bars + BAR_W + 8 * j, STAGE_BYTES);
                tma_load_w_1(smem + j * STAGE_BYTES, &maps.w, bars + BAR_W + 8 * j, slice_channel(rank, j));
                if (j == 0) TR(2, 61);
            }
            const uint32_t first_dynamic = TP(N_STATIC) * num_clusters;
            const uint32_t wrap = num_tiles - first_dynamic + num_clusters - 1;
            uint32_t s = 3, fph = 8, eph = 0, s1 = 3, s2 = 3, id = 0;
#pragma unroll 1
            for (uint32_t i = 1;; i++) {
                s2 = s1;
                s1 = s;
                s = next_slot(tune, s, i);
                const uint32_t slot = bars + ID_AT + 4 * (i & (ID_SLOTS - 1));
                const bool deep = id + TP(DEEP_AT) >= num_tiles;
                const bool eager = id + 1 <= TP(EAGER_TO);
                id = cluster + i * num_clusters;
                if (i >= TP(N_STATIC)) {
                    const uint32_t b = bars + BAR_ID + 8 * ((i - TP(N_STATIC)) & (ID_BARS - 1));
                    if (rank == 0) {
                        if (deep) mbar_wait_w(bars + BAR_EMPTY + 8 * s, (eph >> s) & 1);
                        else if (i > TP(N_STATIC) && !eager) mbar_wait_w(bars + BAR_FULL + 8 * s2, ((fph >> s2) & 1) ^ 1);
                        if (lane == 0) {
                            id = first_dynamic + atomicInc(&g_tile_counter, wrap);
                            st_async_peer(slot, id, b);
                        }
                    } else {
                        mbar_expect_tx_1(b, 4);
                        mbar_wait_w(b, ((i - TP(N_STATIC)) / ID_BARS) & 1);
                        id = lds32(slot);
                    }
                    id = uniform(id);
                }
                sts32(slot, id);
                sts32(bars + FRONT_AT, id);
                TR(7, i);
                mbar_wait_w(bars + BAR_EMPTY + 8 * s, (eph >> s) & 1);
                eph ^= 1u << s;
                fph ^= 1u << s;
                const uint32_t full = bars + BAR_FULL + 8 * s;
                if (id >= num_tiles) {
                    sts32(bars + ISSUED_AT, id);
                    mbar_arrive_1(full);
#pragma unroll 1
                    for (uint32_t u = 0; u < STAGES; u++)
                        if (u != s) mbar_wait_w(bars + BAR_EMPTY + 8 * u, (eph >> u) & 1);
                    break;
                }
                sts32(bars + ISSUED_AT, id);
                TR(0, i);
                TRV(15, i, id);
                mbar_expect_tx_1(full, STAGE_BYTES);
                tma_load_x_1(smem + s * STAGE_BYTES + rank * HALF_BYTES, &maps.x, full, id * 8 + rank * 4,
                             id + TP(EF_TAIL) >= num_tiles ? EVICT_FIRST : EVICT_NORMAL);
            }
        } else if (warp == NUM_WG * 4 + 1) {
#pragma unroll
            for (int s = 0; s < STAGES; s++) {
                mbar_init_1(bars + BAR_FULL + 8 * s, 1);
                mbar_init_1(bars + BAR_EMPTY + 8 * s, NUM_WG * 4 * 2);
            }
#pragma unroll
            for (int s = 0; s < ID_BARS; s++) mbar_init_1(bars + BAR_ID + 8 * s, 1);
            publish_barriers();
            cluster_arrive();
            TR(0, 61);
            cluster_wait();
            prefetch_map_1(&maps.out);
        } else if (warp == NUM_WG * 4 + 2) {
#pragma unroll
            for (int b = 0; b < 3; b++) {
#pragma unroll
                for (int w = 0; w < NUM_WG; w++) {
                    mbar_init_1(bars + BAR_OFREE + b * 32 + w * 8, 1);
                    mbar_init_1(bars + BAR_OFULL + b * 32 + w * 8, 4);
                }
            }
            publish_barriers();
            cluster_arrive();
            cluster_wait();
            const uint32_t lag_at = TP(RING3_AT) + TP(LAG_AT) + cluster % TP(LAG_SPREAD);
            StoreQueue q = {0, 0};
            uint32_t ob = 2, phase = 0;
#pragma unroll 1
            for (uint32_t j = 0;; j++) {
                uint32_t lag = (j >= lag_at) + (j >= lag_at + TP(LAG_GAP));
#pragma unroll 1
                for (uint32_t spins = 0; lag != 0 && spins < SPIN_LIMIT; spins++) {
                    const uint32_t front = uniform(lds32(bars + FRONT_AT));
                    if (front + TP(LAG_T2) >= num_tiles) break;
                    if (front + TP(LAG_T1) >= num_tiles) lag = 1;
                    uint32_t b = ob + lag;
                    if (b >= 3) b -= 3;
                    const uint32_t gate = bars + BAR_OFULL + b * 32 + TP(LAG_WG) * 8;
                    if (q.count != 0) {
                        if (mbar_test_w(gate, (phase >> b) & 1)) break;
                        release_oldest(q, bars);
                    } else if (mbar_try_w(gate, (phase >> b) & 1, 100)) {
                        break;
                    }
                }
                const uint32_t parity = (phase >> ob) & 1;
                uint32_t id = 0;
#pragma unroll 1
                for (uint32_t w = 0; w < NUM_WG; w++) {
                    const uint32_t slice = ob * 4 + w;
#pragma unroll 1
                    while (q.count != 0 && !mbar_test_w(bars + BAR_OFULL + slice * 8, parity)) release_oldest(q, bars);
                    if (q.count == 0) mbar_wait_w(bars + BAR_OFULL + slice * 8, parity);
                    if (w == 0) {
                        id = uniform(lds32(bars + ID_AT + 4 * (j & (ID_SLOTS - 1))));
                        if (id >= num_tiles) break;
                    }
                    TR(11 + w, j);
                    tma_store_1(&maps.out, smem + SMEM_OUT + ob * HALF_BYTES + w * SLICE_BYTES, slice_channel(rank, w), id * TILE_PIX);
                    q.items |= slice << (4 * q.count);
                    if (++q.count == 4) release_oldest(q, bars);
                }
                if (id >= num_tiles) break;
                phase ^= 1u << ob;
                ob = next_buffer(tune, ob, j + 1);
            }
            stores_read_wait<0>();
            TR(4, 62);
        } else {
            uint32_t due = timer_ns() + TP(PM_T0) + (blockIdx.x & 3) * TP(PM_STAG);
            sts32(bars + ISSUED_AT, 0);
            cluster_arrive();
            if (!PRE_MAP) prefetch_map_1(&maps.x);
            const uint32_t step = num_clusters / 2;
#pragma unroll 1
            for (uint32_t piece = PRE_X; piece < TP(PM_E4); piece++) {
                const uint32_t t = cluster + piece / 2 * num_clusters;
                if (t >= num_tiles) break;
                uint32_t now, issued;
#pragma unroll 1
                for (uint32_t spins = 0; spins < 16384; spins++) {
                    issued = uniform(lds32(bars + ISSUED_AT));
                    now = timer_ns();
                    const int lead = max((int)TP(LEAD_B), (int)TP(LEAD_A) - (max((int)issued - (int)TP(LEAD_F), 0) * (int)TP(LEAD_S) >> 4));
                    if ((int32_t)(now - due) >= 0 && cluster + piece * step <= issued + lead) break;
                    __nanosleep(20);
                }
                if (TP(X0) != 0 && t <= issued && piece >= TP(X0)) continue;
                if ((int32_t)(now - TP(PM_SLACK) - due) > 0) due = now - TP(PM_SLACK);
                due += piece < TP(PM_E1) ? TP(PM_DT1) : piece < TP(PM_E2) ? TP(PM_DT2) : piece < TP(PM_E3) ? TP(PM_DT3) : TP(PM_DT4);
                const uint8_t* p = x_raw + (size_t)t * STAGE_BYTES + rank * HALF_BYTES + (piece % 2) * 12288 + lane * 128;
#pragma unroll
                for (int k = 0; k < 3; k++) asm volatile("prefetch.global.L2 [%0];" ::"l"(p + k * 4096) : "memory");
                if (piece % 2 == 0) TR(14, piece / 2);
            }
            cluster_wait();
        }
    }
}

typedef CUresult (*EncodeTiledFn)(CUtensorMap*, CUtensorMapDataType, cuuint32_t, void*, const cuuint64_t*,
                                  const cuuint64_t*, const cuuint32_t*, const cuuint32_t*, CUtensorMapInterleave,
                                  CUtensorMapSwizzle, CUtensorMapL2promotion, CUtensorMapFloatOOBfill);

}

extern "C" void kernel_launch(void* const* d_in, const int* in_sizes, int n_in, void* d_out, int out_size) {
    (void)n_in;
    (void)out_size;
    void* x = d_in[0];
    void* w = d_in[1];
    const uint16_t* b = (const uint16_t*)d_in[2];
    const int M = in_sizes[0] / C;
    const int num_tiles = M / TILE_PIX;

    static EncodeTiledFn encode = nullptr;
    static int sms = 0;
    if (!encode) {
        void* fn = nullptr;
        cudaDriverEntryPointQueryResult q;
        cudaGetDriverEntryPoint("cuTensorMapEncodeTiled", &fn, cudaEnableDefault, &q);
        encode = (EncodeTiledFn)fn;
        cudaDeviceGetAttribute(&sms, cudaDevAttrMultiProcessorCount, 0);
        cudaFuncSetAttribute(conv1x1_kernel, cudaFuncAttributeMaxDynamicSharedMemorySize, SMEM_TOTAL);
    }

    Maps maps;
    const cuuint32_t ones[4] = {1, 1, 1, 1};
    auto make = [&](CUtensorMap* map, int rank, void* base, const cuuint64_t* dims, const cuuint64_t* strides,
                    const cuuint32_t* box, CUtensorMapL2promotion promo) {
        encode(map, CU_TENSOR_MAP_DATA_TYPE_BFLOAT16, rank, base, dims, strides, box, ones, CU_TENSOR_MAP_INTERLEAVE_NONE,
               CU_TENSOR_MAP_SWIZZLE_128B, promo, CU_TENSOR_MAP_FLOAT_OOB_FILL_NONE);
    };
    {
        const cuuint64_t dims[4]    = {64, 8, 6, (cuuint64_t)(M / 8)};
        const cuuint64_t strides[3] = {C * 2, 128, 8 * C * 2};
        const cuuint32_t box[4]     = {64, 8, 6, TILE_PIX / 16};
        make(&maps.x, 4, x, dims, strides, box, CU_TENSOR_MAP_L2_PROMOTION_L2_128B);
    }
    {
        const cuuint64_t dims[3]    = {C, C / 2, 2};
        const cuuint64_t strides[2] = {C * 2, C * C};
        const cuuint32_t box[3]     = {64, C / 2, 2};
        make(&maps.w, 3, w, dims, strides, box, CU_TENSOR_MAP_L2_PROMOTION_L2_128B);
    }
    {
        const cuuint64_t dims[2]    = {C, (cuuint64_t)M};
        const cuuint64_t strides[1] = {C * 2};
        const cuuint32_t box[2]     = {64, TILE_PIX};
        make(&maps.out, 2, d_out, dims, strides, box, CU_TENSOR_MAP_L2_PROMOTION_NONE);
    }

    const Tune tune;
    int clusters = sms / 2;
    if (clusters > num_tiles / (int)TP(N_STATIC)) clusters = num_tiles / (int)TP(N_STATIC);
    conv1x1_kernel<<<clusters * 2, THREADS, SMEM_TOTAL>>>((const uint8_t*)x, (const uint8_t*)w, b, (uint32_t)num_tiles,
                                                          (uint32_t)clusters, maps, tune);
}
```

```cpp
#include <cuda_runtime.h>
#include <cuda_bf16.h>
#include <cuda.h>
#include <stdint.h>

#define EARLY_AT 18

#define W_FIRST 2
#define PRE_X 1
#define PRE_W 64

#define TUNABLES(F) \
    F(EARLY_TILES, 198)    \
    F(EARLY_HEAD, 660)       \
    F(N_STATIC, 19)        \
    F(PM_T0, 0)            \
    F(PM_DT1, 450)         \
    F(PM_E1, 12) \
    F(PM_DT2, 375) \
    F(PM_E2, 24) \
    F(PM_DT3, 940) \
    F(PM_E3, 57) \
    F(PM_DT4, 750) \
    F(PM_E4, 72) \
    F(PM_STAG, 150)        \
    F(LEAD_A, 280)        \
    F(LEAD_F, 450)         \
    F(LEAD_S, 3)           \
    F(LEAD_B, 134)        \
    F(PM_SLACK, 450)    \
    F(EAGER_TO, 2200)         \
    F(EF_TAIL, 300)        \
    F(LAG_AT, 3)           \
    F(LAG_SPREAD, 2)       \
    F(LAG_GAP, 4)          \
    F(LAG_WG, 2)           \
    F(LAG_T1, 32)          \
    F(LAG_T2, 18)           \
    F(DEEP_AT, 60)          \
    F(X0, 0) \
    F(X1, 0) \
    F(X2, 0) \
    F(X3, 0)

struct Tune {
#define F(n, v) static constexpr uint32_t n = v;
    TUNABLES(F)
#undef F
};
#define TP(n) (Tune::n)

#define TRV(slot, idx, v)
#define TR(slot, idx)
#define TRE(slot, idx)

namespace {

constexpr int C            = 384;
constexpr int TILE_PIX     = 64;
constexpr int STAGES       = 3;
constexpr int STAGE_BYTES  = TILE_PIX * C * 2;
constexpr int HALF_BYTES   = STAGE_BYTES / 2;
constexpr int SLICE_BYTES  = TILE_PIX * 128;
constexpr int W_LINES      = C * C * 2 / 128;
constexpr int NUM_WG       = 3;
constexpr int THREADS      = (NUM_WG + 1) * 128;
constexpr int SMEM_OUT     = STAGES * STAGE_BYTES;
constexpr int SMEM_BAR     = SMEM_OUT + STAGES * HALF_BYTES;
constexpr int SMEM_TOTAL   = SMEM_BAR + 512 + 1024;
constexpr int ID_SLOTS     = 16;
constexpr int ID_BARS      = 4;
constexpr uint32_t SPIN_LIMIT = 1u << 24;
constexpr int BAR_W     = 0;
constexpr int BAR_FULL  = 32;
constexpr int BAR_EMPTY = BAR_FULL + 32;
constexpr int BAR_ID    = BAR_EMPTY + 32;
constexpr int BAR_OFREE = BAR_ID + 8 * ID_BARS;
constexpr int BAR_OFULL = BAR_OFREE + 8 * 12;
constexpr int ID_AT     = BAR_OFULL + 8 * 12;
constexpr int FRONT_AT  = ID_AT + 4 * ID_SLOTS;
constexpr int ISSUED_AT = FRONT_AT + 4;
constexpr uint64_t EVICT_NORMAL = 0x1000000000000000ull;
constexpr uint64_t EVICT_FIRST  = 0x12F0000000000000ull;

struct Maps {
    CUtensorMap w, x, out;
};

__device__ unsigned int g_tile_counter;

#define ELECT "{\n.reg .pred e;\nelect.sync _|e, 0xffffffff;\n@e "

__device__ __forceinline__ uint32_t smem_u32(const void* p) {
    return (uint32_t)__cvta_generic_to_shared(p);
}
__device__ __forceinline__ void mbar_init_1(uint32_t bar, uint32_t count) {
    asm volatile(ELECT "mbarrier.init.shared::cta.b64 [%0], %1;\n}" ::"r"(bar), "r"(count) : "memory");
}
__device__ __forceinline__ void mbar_expect_tx_1(uint32_t bar, uint32_t bytes) {
    asm volatile(ELECT "mbarrier.arrive.expect_tx.shared::cta.b64 _, [%0], %1;\n}" ::"r"(bar), "r"(bytes) : "memory");
}
__device__ __forceinline__ void mbar_arrive_1(uint32_t bar) {
    asm volatile(ELECT "mbarrier.arrive.shared::cta.b64 _, [%0];\n}" ::"r"(bar) : "memory");
}
__device__ __forceinline__ void mbar_wait(uint32_t bar, uint32_t parity) {
    uint32_t done;
    uint32_t spins = 0;
    do {
        asm volatile(
            "{\n.reg .pred p;\n"
            "mbarrier.try_wait.parity.shared::cta.b64 p, [%1], %2;\n"
            "selp.u32 %0, 1, 0, p;\n}"
            : "=r"(done) : "r"(bar), "r"(parity) : "memory");
    } while (!done && ++spins < SPIN_LIMIT);
}
__device__ __forceinline__ void mbar_wait_w(uint32_t bar, uint32_t parity) {
    mbar_wait(bar, parity);
    __syncwarp();
}
__device__ __forceinline__ bool mbar_test_w(uint32_t bar, uint32_t parity) {
    uint32_t done;
    asm volatile(
        "{\n.reg .pred p;\n"
        "mbarrier.test_wait.parity.shared::cta.b64 p, [%1], %2;\n"
        "selp.u32 %0, 1, 0, p;\n}"
        : "=r"(done) : "r"(bar), "r"(parity) : "memory");
    return __all_sync(0xffffffffu, done);
}
__device__ __forceinline__ bool mbar_try_w(uint32_t bar, uint32_t parity, uint32_t ns) {
    uint32_t done;
    asm volatile(
        "{\n.reg .pred p;\n"
        "mbarrier.try_wait.parity.shared::cta.b64 p, [%1], %2, %3;\n"
        "selp.u32 %0, 1, 0, p;\n}"
        : "=r"(done) : "r"(bar), "r"(parity), "r"(ns) : "memory");
    return __all_sync(0xffffffffu, done);
}
__device__ __forceinline__ void mbar_arrive_cta(uint32_t bar, uint32_t cta) {
    asm volatile(
        "{\n.reg .b32 ra;\n"
        "mapa.shared::cluster.u32 ra, %0, %1;\n"
        "mbarrier.arrive.shared::cluster.b64 _, [ra];\n}"
        ::"r"(bar), "r"(cta) : "memory");
}
__device__ __forceinline__ void st_async_peer(uint32_t addr, uint32_t val, uint32_t bar) {
    asm volatile(
        "{\n.reg .b32 ra, rb;\n"
        "mapa.shared::cluster.u32 ra, %0, 1;\n"
        "mapa.shared::cluster.u32 rb, %2, 1;\n"
        "st.async.weak.shared::cluster.mbarrier::complete_tx::bytes.b32 [ra], %1, [rb];\n}"
        ::"r"(addr), "r"(val), "r"(bar) : "memory");
}
__device__ __forceinline__ uint32_t lds32(uint32_t addr) {
    uint32_t v;
    asm volatile("ld.shared.b32 %0, [%1];" : "=r"(v) : "r"(addr) : "memory");
    return v;
}
__device__ __forceinline__ uint32_t uniform(uint32_t v) {
    return __shfl_sync(0xffffffffu, v, 0);
}
__device__ __forceinline__ void sts32(uint32_t addr, uint32_t v) {
    asm volatile("st.shared.b32 [%0], %1;" ::"r"(addr), "r"(v) : "memory");
}
__device__ __forceinline__ void tma_load_w_1(uint32_t dst, const CUtensorMap* map, uint32_t bar, int n) {
    asm volatile(
        ELECT "cp.async.bulk.tensor.3d.shared::cluster.global.mbarrier::complete_tx::bytes [%0], [%1, {%3, %4, %4}], [%2];\n}"
        ::"r"(dst), "l"(map), "r"(bar), "r"(n), "r"(0) : "memory");
}
__device__ __forceinline__ void tma_load_x_1(uint32_t dst, const CUtensorMap* map, uint32_t bar, int group, uint64_t policy) {
    asm volatile(
        ELECT "cp.async.bulk.tensor.4d.shared::cluster.global.mbarrier::complete_tx::bytes.multicast::cluster.L2::cache_hint"
        " [%0], [%1, {%3, %3, %3, %4}], [%2], %5, %6;\n}"
        ::"r"(dst), "l"(map), "r"(bar), "r"(0), "r"(group), "h"((uint16_t)3), "l"(policy) : "memory");
}
__device__ __forceinline__ void tma_store_1(const CUtensorMap* map, uint32_t src, int ch, int pix) {
    asm volatile(
        ELECT "cp.async.bulk.tensor.2d.global.shared::cta.bulk_group [%0, {%2, %3}], [%1];\n}\n"
        "cp.async.bulk.commit_group;"
        ::"l"(map), "r"(src), "r"(ch), "r"(pix) : "memory");
}
template <int N>
__device__ __forceinline__ void stores_read_wait() {
    asm volatile("cp.async.bulk.wait_group.read %0;" ::"n"(N) : "memory");
}
__device__ __forceinline__ void prefetch_map_1(const CUtensorMap* map) {
    asm volatile(ELECT "prefetch.tensormap [%0];\n}" ::"l"(map) : "memory");
}
__device__ __forceinline__ uint32_t timer_ns() {
    uint32_t t;
    asm volatile("mov.u32 %0, %%globaltimer_lo;" : "=r"(t)::"memory");
    return t;
}
__device__ __forceinline__ void cluster_arrive() {
    asm volatile("barrier.cluster.arrive.relaxed.aligned;" ::: "memory");
}
__device__ __forceinline__ void cluster_wait() {
    asm volatile("barrier.cluster.wait.aligned;" ::: "memory");
}
__device__ __forceinline__ void publish_barriers() {
    asm volatile("fence.mbarrier_init.release.cluster;" ::: "memory");
    asm volatile("fence.proxy.async.shared::cta;" ::: "memory");
}

__device__ __forceinline__ void wgmma_rs_n64(float (&d)[32], const uint32_t* a, uint64_t desc, int scale_d) {
    asm volatile(
        "{\n.reg .pred p;\n"
        "setp.ne.b32 p, %37, 0;\n"
        "wgmma.mma_async.sync.aligned.m64n64k16.f32.bf16.bf16 "
        "{%0, %1, %2, %3, %4, %5, %6, %7, %8, %9, %10, %11, %12, %13, %14, %15, "
        "%16, %17, %18, %19, %20, %21, %22, %23, %24, %25, %26, %27, %28, %29, %30, %31}, "
        "{%32, %33, %34, %35}, %36, p, 1, 1, 0;\n}"
        : "+f"(d[0]), "+f"(d[1]), "+f"(d[2]), "+f"(d[3]), "+f"(d[4]), "+f"(d[5]), "+f"(d[6]), "+f"(d[7]),
          "+f"(d[8]), "+f"(d[9]), "+f"(d[10]), "+f"(d[11]), "+f"(d[12]), "+f"(d[13]), "+f"(d[14]), "+f"(d[15]),
          "+f"(d[16]), "+f"(d[17]), "+f"(d[18]), "+f"(d[19]), "+f"(d[20]), "+f"(d[21]), "+f"(d[22]), "+f"(d[23]),
          "+f"(d[24]), "+f"(d[25]), "+f"(d[26]), "+f"(d[27]), "+f"(d[28]), "+f"(d[29]), "+f"(d[30]), "+f"(d[31])
        : "r"(a[0]), "r"(a[1]), "r"(a[2]), "r"(a[3]), "l"(desc), "r"(scale_d));
}

__device__ __forceinline__ uint32_t pack_bias(float lo, float hi, uint32_t bias2) {
    uint32_t r;
    asm("{\n.reg .b32 t;\n"
        "cvt.rn.bf16x2.f32 t, %2, %1;\n"
        "add.rn.bf16x2 %0, t, %3;\n}"
        : "=r"(r) : "f"(lo), "f"(hi), "r"(bias2));
    return r;
}

__device__ __forceinline__ int slice_channel(uint32_t rank, int wg) {
    return (wg * 2 + rank) * 64;
}

struct Consumer {
    uint32_t wreg[96];
    uint32_t bias_lo, bias_hi, st_addr, bars;
    uint64_t desc_base;
    int wg, lane;
};
struct Ring {
    uint32_t s, parity;
    __device__ __forceinline__ void advance() {
        if (++s == STAGES) {
            s = 0;
            parity ^= 1;
        }
    }
};
__device__ __forceinline__ uint32_t w_stage(int wg) {
    return (wg + 1) * STAGE_BYTES + (wg == 2 ? HALF_BYTES : 0);
}

__device__ __forceinline__ void consume(const Consumer& c, const Ring& r, float (&acc)[32], uint32_t i, bool early) {
    const int next_turn = 4 + (c.wg + 1) % NUM_WG;
    if ((i | c.wg) != 0) asm volatile("bar.sync %0, 256;" ::"r"(4 + c.wg) : "memory");
    TRE(1 + c.wg * 2, i);
    const uint64_t desc = c.desc_base + (uint64_t)(r.s * (STAGE_BYTES >> 4));
    asm volatile("wgmma.fence.sync.aligned;" ::: "memory");
#pragma unroll
    for (int ks = 0; ks < 24; ks++) {
        const uint64_t d = desc + (uint64_t)((ks >> 2) * 64 + (ks & 3) * 2);
        wgmma_rs_n64(acc, &c.wreg[ks * 4], d, ks != 0);
        if (ks + 1 == EARLY_AT && early) asm volatile("bar.arrive %0, 256;" ::"r"(next_turn) : "memory");
    }
    asm volatile("wgmma.commit_group.sync.aligned;" ::: "memory");
    asm volatile("wgmma.wait_group.sync.aligned 0;" ::: "memory");
#pragma unroll
    for (int j = 0; j < 32; j++) asm volatile("" : "+f"(acc[j])::"memory");
    if (!early) asm volatile("bar.arrive %0, 256;" ::"r"(next_turn) : "memory");
    TRE(2 + c.wg * 2, i);
    if (c.lane < 2) mbar_arrive_cta(c.bars + BAR_EMPTY + 8 * r.s, c.lane);
    const uint32_t obar = c.bars + (r.s * 4 + c.wg) * 8;
    mbar_wait_w(obar + BAR_OFREE, r.parity ^ 1);
    const uint32_t dst = c.st_addr + r.s * HALF_BYTES;
#pragma unroll
    for (int j = 0; j < 4; j++) {
        const uint32_t r0 = pack_bias(acc[8 * j + 0], acc[8 * j + 1], c.bias_lo);
        const uint32_t r1 = pack_bias(acc[8 * j + 2], acc[8 * j + 3], c.bias_hi);
        const uint32_t r2 = pack_bias(acc[8 * j + 4], acc[8 * j + 5], c.bias_lo);
        const uint32_t r3 = pack_bias(acc[8 * j + 6], acc[8 * j + 7], c.bias_hi);
        asm volatile("stmatrix.sync.aligned.m8n8.x4.trans.shared.b16 [%0], {%1, %2, %3, %4};"
                     ::"r"(dst + j * 2048), "r"(r0), "r"(r1), "r"(r2), "r"(r3) : "memory");
    }
    asm volatile("fence.proxy.async.shared::cta;" ::: "memory");
    __syncwarp();
    mbar_arrive_1(obar + BAR_OFULL);
    TRE(8 + c.wg, i);
}

struct StoreQueue {
    uint32_t items, count;
};
__device__ __forceinline__ void release_oldest(StoreQueue& q, uint32_t bars) {
    if (q.count == 1) stores_read_wait<0>();
    else if (q.count == 2) stores_read_wait<1>();
    else if (q.count == 3) stores_read_wait<2>();
    else stores_read_wait<3>();
    mbar_arrive_1(bars + BAR_OFREE + (q.items & 15) * 8);
    q.items >>= 4;
    q.count--;
}

__global__ void __cluster_dims__(2, 1, 1) __launch_bounds__(THREADS, 1)
conv1x1_kernel(const uint8_t* __restrict__ x_raw,
               const uint8_t* __restrict__ w_raw,
               const uint16_t* __restrict__ bias,
               uint32_t num_tiles,
               uint32_t num_clusters,
               const __grid_constant__ Maps maps,
               const __grid_constant__ Tune tune) {
    if (threadIdx.x < 96) {
        const uint32_t line = blockIdx.x % (W_LINES / PRE_W) * PRE_W + threadIdx.x;
        if (threadIdx.x < PRE_W) asm volatile("prefetch.global.L2 [%0];" ::"l"(w_raw + line * 128) : "memory");
    } else if (threadIdx.x < 128) {
        prefetch_map_1(&maps.w);
        prefetch_map_1(&maps.x);
    } else if (threadIdx.x < 128 + PRE_X * 96) {
        const uint8_t* p = x_raw + (size_t)blockIdx.x * HALF_BYTES + (threadIdx.x - 128) * 128;
        asm volatile("prefetch.global.L2 [%0];" ::"l"(p) : "memory");
    }
    extern __shared__ uint8_t smem_raw[];
    const uint32_t smem = (smem_u32(smem_raw) + 1023u) & ~1023u;
    const uint32_t bars = smem + SMEM_BAR;

    const int warp = uniform(threadIdx.x >> 5);
    const int lane = threadIdx.x & 31;
    const uint32_t rank         = blockIdx.x & 1;
    const uint32_t cluster      = blockIdx.x >> 1;

    if (warp < NUM_WG * 4) {
        const int wg = warp >> 2;
        const int wq = warp & 3;
        cluster_arrive();
        asm volatile("setmaxnreg.inc.sync.aligned.u32 160;");
        Consumer c;
        c.wg = wg;
        c.lane = lane;
        c.bars = bars;
        c.bias_lo = bias[slice_channel(rank, wg) + wq * 16 + (lane >> 2)] * 0x10001u;
        c.bias_hi = bias[slice_channel(rank, wg) + wq * 16 + (lane >> 2) + 8] * 0x10001u;

        cluster_wait();
        TRE(1 + wg, 63);
        mbar_wait_w(bars + BAR_W + 8 * wg, 0);
        TRE(4 + wg, 63);
        {
            const int r = lane & 7, m = lane >> 3;
            const uint32_t base = smem + w_stage(wg) + ((m >> 1) * 8 + r) * 128 + (((2 * wq + (m & 1)) ^ r) << 4);
#pragma unroll
            for (int ks = 0; ks < 24; ks++) {
                asm volatile("ldmatrix.sync.aligned.m8n8.x4.trans.shared.b16 {%0, %1, %2, %3}, [%4];"
                             : "=r"(c.wreg[ks * 4 + 0]), "=r"(c.wreg[ks * 4 + 1]), "=r"(c.wreg[ks * 4 + 2]), "=r"(c.wreg[ks * 4 + 3])
                             : "r"(base + ks * 2048) : "memory");
            }
        }
        uint32_t dep = 0;
#pragma unroll
        for (int ks = 0; ks < 24; ks++) dep ^= c.wreg[ks * 4];
        dep &= num_tiles >> 31;
        __syncwarp();
        if (lane < 6 && wg < 2) mbar_arrive_cta(bars + BAR_EMPTY + 8 * (wg + 1) + dep, lane & 1);
        TRE(1 + wg, 60);

        c.st_addr = smem + SMEM_OUT + wg * SLICE_BYTES + ((lane >> 4) * 8 + (lane & 7)) * 128 + (((2 * wq + ((lane >> 3) & 1)) ^ (lane & 7)) << 4);
        c.desc_base = (uint64_t)((smem & 0x3FFFF) >> 4) | ((uint64_t)1 << 16) | ((uint64_t)(6144 >> 4) << 32) | ((uint64_t)1 << 62);

        float acc[32];
        Ring r = {0, 0};
        for (uint32_t i = 0;; i++, r.advance()) {
            mbar_wait(bars + BAR_FULL + 8 * r.s, r.parity);
            const uint32_t id = lds32(bars + ID_AT + 4 * (i & (ID_SLOTS - 1)));
            if (id >= num_tiles) break;
            consume(c, r, acc, i, id + TP(EARLY_TILES) >= num_tiles || id + 1 <= TP(EARLY_HEAD));
        }
        if (wg == 0) {
            mbar_wait_w(bars + BAR_OFREE + r.s * 32, r.parity ^ 1);
            mbar_arrive_1(bars + BAR_OFULL + r.s * 32);
            asm volatile("bar.sync 4, 256;" ::: "memory");
        }
        TRE(1 + wg, 62);
    } else {
        asm volatile("setmaxnreg.dec.sync.aligned.u32 32;");
        if (warp == NUM_WG * 4) {
#pragma unroll
            for (int j = 0; j < NUM_WG; j++) mbar_init_1(bars + BAR_W + 8 * j, 1);
            publish_barriers();
            cluster_arrive();
            sts32(bars + ID_AT, cluster);
#pragma unroll
            for (int j = 0; j < NUM_WG; j++) {
                if (j == W_FIRST) {
                    cluster_wait();
                    TR(0, 0);
                    mbar_expect_tx_1(bars + BAR_FULL, STAGE_BYTES);
                    tma_load_x_1(smem + rank * HALF_BYTES, &maps.x, bars + BAR_FULL, cluster * 8 + rank * 4, EVICT_NORMAL);
                }
                mbar_expect_tx_1(bars + BAR_W + 8 * j, STAGE_BYTES);
                tma_load_w_1(smem + w_stage(j), &maps.w, bars + BAR_W + 8 * j, slice_channel(rank, j));
                if (j == 0) TR(2, 61);
            }
            const uint32_t first_dynamic = TP(N_STATIC) * num_clusters;
            const uint32_t wrap = num_tiles - first_dynamic + num_clusters - 1;
            uint32_t s = 0, fph = 1, eph = 0, s1 = 0, s2 = 0, id = 0;
#pragma unroll 1
            for (uint32_t i = 1;; i++) {
                s2 = s1;
                s1 = s;
                s = s == STAGES - 1 ? 0 : s + 1;
                const uint32_t slot = bars + ID_AT + 4 * (i & (ID_SLOTS - 1));
                const bool deep = id + TP(DEEP_AT) >= num_tiles;
                const bool eager = id + 1 <= TP(EAGER_TO);
                id = cluster + i * num_clusters;
                if (i >= TP(N_STATIC)) {
                    const uint32_t b = bars + BAR_ID + 8 * ((i - TP(N_STATIC)) & (ID_BARS - 1));
                    if (rank == 0) {
                        if (deep) mbar_wait_w(bars + BAR_EMPTY + 8 * s, (eph >> s) & 1);
                        else if (i > TP(N_STATIC) && !eager) mbar_wait_w(bars + BAR_FULL + 8 * s2, ((fph >> s2) & 1) ^ 1);
                        if (lane == 0) {
                            id = first_dynamic + atomicInc(&g_tile_counter, wrap);
                            st_async_peer(slot, id, b);
                        }
                    } else {
                        mbar_expect_tx_1(b, 4);
                        mbar_wait_w(b, ((i - TP(N_STATIC)) / ID_BARS) & 1);
                        id = lds32(slot);
                    }
                    id = uniform(id);
                }
                sts32(slot, id);
                sts32(bars + FRONT_AT, id);
                TR(7, i);
                mbar_wait_w(bars + BAR_EMPTY + 8 * s, (eph >> s) & 1);
                eph ^= 1u << s;
                fph ^= 1u << s;
                const uint32_t full = bars + BAR_FULL + 8 * s;
                if (id >= num_tiles) {
                    sts32(bars + ISSUED_AT, id);
                    mbar_arrive_1(full);
#pragma unroll 1
                    for (uint32_t u = 0; u < STAGES; u++)
                        if (u != s) mbar_wait_w(bars + BAR_EMPTY + 8 * u, (eph >> u) & 1);
                    break;
                }
                sts32(bars + ISSUED_AT, id);
                TR(0, i);
                TRV(15, i, id);
                mbar_expect_tx_1(full, STAGE_BYTES);
                tma_load_x_1(smem + s * STAGE_BYTES + rank * HALF_BYTES, &maps.x, full, id * 8 + rank * 4,
                             id + TP(EF_TAIL) >= num_tiles ? EVICT_FIRST : EVICT_NORMAL);
            }
        } else if (warp == NUM_WG * 4 + 1) {
#pragma unroll
            for (int s = 0; s < STAGES; s++) {
                mbar_init_1(bars + BAR_FULL + 8 * s, 1);
                mbar_init_1(bars + BAR_EMPTY + 8 * s, NUM_WG * 4 * 2);
            }
#pragma unroll
            for (int s = 0; s < ID_BARS; s++) mbar_init_1(bars + BAR_ID + 8 * s, 1);
            publish_barriers();
            cluster_arrive();
            TR(0, 61);
            cluster_wait();
            prefetch_map_1(&maps.out);
        } else if (warp == NUM_WG * 4 + 2) {
#pragma unroll
            for (int b = 0; b < 3; b++) {
#pragma unroll
                for (int w = 0; w < NUM_WG; w++) {
                    mbar_init_1(bars + BAR_OFREE + b * 32 + w * 8, 1);
                    mbar_init_1(bars + BAR_OFULL + b * 32 + w * 8, 4);
                }
            }
            publish_barriers();
            cluster_arrive();
            cluster_wait();
            const uint32_t lag_at = TP(LAG_AT) + cluster % TP(LAG_SPREAD);
            StoreQueue q = {0, 0};
            uint32_t ob = 0, phase = 0;
#pragma unroll 1
            for (uint32_t j = 0;; j++) {
                uint32_t lag = (j >= lag_at) + (j >= lag_at + TP(LAG_GAP));
#pragma unroll 1
                for (uint32_t spins = 0; lag != 0 && spins < SPIN_LIMIT; spins++) {
                    const uint32_t front = uniform(lds32(bars + FRONT_AT));
                    if (front + TP(LAG_T2) >= num_tiles) break;
                    if (front + TP(LAG_T1) >= num_tiles) lag = 1;
                    uint32_t b = ob + lag;
                    if (b >= 3) b -= 3;
                    const uint32_t gate = bars + BAR_OFULL + b * 32 + TP(LAG_WG) * 8;
                    if (q.count != 0) {
                        if (mbar_test_w(gate, (phase >> b) & 1)) break;
                        release_oldest(q, bars);
                    } else if (mbar_try_w(gate, (phase >> b) & 1, 100)) {
                        break;
                    }
                }
                const uint32_t parity = (phase >> ob) & 1;
                uint32_t id = 0;
#pragma unroll 1
                for (uint32_t w = 0; w < NUM_WG; w++) {
                    const uint32_t slice = ob * 4 + w;
#pragma unroll 1
                    while (q.count != 0 && !mbar_test_w(bars + BAR_OFULL + slice * 8, parity)) release_oldest(q, bars);
                    if (q.count == 0) mbar_wait_w(bars + BAR_OFULL + slice * 8, parity);
                    if (w == 0) {
                        id = uniform(lds32(bars + ID_AT + 4 * (j & (ID_SLOTS - 1))));
                        if (id >= num_tiles) break;
                    }
                    TR(11 + w, j);
                    tma_store_1(&maps.out, smem + SMEM_OUT + ob * HALF_BYTES + w * SLICE_BYTES, slice_channel(rank, w), id * TILE_PIX);
                    q.items |= slice << (4 * q.count);
                    if (++q.count == 4) release_oldest(q, bars);
                }
                if (id >= num_tiles) break;
                phase ^= 1u << ob;
                ob = ob == STAGES - 1 ? 0 : ob + 1;
            }
            stores_read_wait<0>();
            TR(4, 62);
        } else {
            uint32_t due = timer_ns() + TP(PM_T0) + (blockIdx.x & 3) * TP(PM_STAG);
            sts32(bars + ISSUED_AT, 0);
            cluster_arrive();
            const uint32_t step = num_clusters / 2;
#pragma unroll 1
            for (uint32_t piece = PRE_X; piece < TP(PM_E4); piece++) {
                const uint32_t t = cluster + piece / 2 * num_clusters;
                if (t >= num_tiles) break;
                uint32_t now, issued;
#pragma unroll 1
                for (uint32_t spins = 0; spins < 16384; spins++) {
                    issued = uniform(lds32(bars + ISSUED_AT));
                    now = timer_ns();
                    const int lead = max((int)TP(LEAD_B), (int)TP(LEAD_A) - (max((int)issued - (int)TP(LEAD_F), 0) * (int)TP(LEAD_S) >> 4));
                    if ((int32_t)(now - due) >= 0 && cluster + piece * step <= issued + lead) break;
                    __nanosleep(20);
                }
                if (TP(X0) != 0 && t <= issued && piece >= TP(X0)) continue;
                if ((int32_t)(now - TP(PM_SLACK) - due) > 0) due = now - TP(PM_SLACK);
                due += piece < TP(PM_E1) ? TP(PM_DT1) : piece < TP(PM_E2) ? TP(PM_DT2) : piece < TP(PM_E3) ? TP(PM_DT3) : TP(PM_DT4);
                const uint8_t* p = x_raw + (size_t)t * STAGE_BYTES + rank * HALF_BYTES + (piece % 2) * 12288 + lane * 128;
#pragma unroll
                for (int k = 0; k < 3; k++) asm volatile("prefetch.global.L2 [%0];" ::"l"(p + k * 4096) : "memory");
                if (piece % 2 == 0) TR(14, piece / 2);
            }
            cluster_wait();
        }
    }
}

typedef CUresult (*EncodeTiledFn)(CUtensorMap*, CUtensorMapDataType, cuuint32_t, void*, const cuuint64_t*,
                                  const cuuint64_t*, const cuuint32_t*, const cuuint32_t*, CUtensorMapInterleave,
                                  CUtensorMapSwizzle, CUtensorMapL2promotion, CUtensorMapFloatOOBfill);

}

extern "C" void kernel_launch(void* const* d_in, const int* in_sizes, int n_in, void* d_out, int out_size) {
    (void)n_in;
    (void)out_size;
    void* x = d_in[0];
    void* w = d_in[1];
    const uint16_t* b = (const uint16_t*)d_in[2];
    const int M = in_sizes[0] / C;
    const int num_tiles = M / TILE_PIX;

    static EncodeTiledFn encode = nullptr;
    static int sms = 0;
    if (!encode) {
        void* fn = nullptr;
        cudaDriverEntryPointQueryResult q;
        cudaGetDriverEntryPoint("cuTensorMapEncodeTiled", &fn, cudaEnableDefault, &q);
        encode = (EncodeTiledFn)fn;
        cudaDeviceGetAttribute(&sms, cudaDevAttrMultiProcessorCount, 0);
        cudaFuncSetAttribute(conv1x1_kernel, cudaFuncAttributeMaxDynamicSharedMemorySize, SMEM_TOTAL);
    }

    Maps maps;
    const cuuint32_t ones[4] = {1, 1, 1, 1};
    auto make = [&](CUtensorMap* map, int rank, void* base, const cuuint64_t* dims, const cuuint64_t* strides,
                    const cuuint32_t* box, CUtensorMapL2promotion promo) {
        encode(map, CU_TENSOR_MAP_DATA_TYPE_BFLOAT16, rank, base, dims, strides, box, ones, CU_TENSOR_MAP_INTERLEAVE_NONE,
               CU_TENSOR_MAP_SWIZZLE_128B, promo, CU_TENSOR_MAP_FLOAT_OOB_FILL_NONE);
    };
    {
        const cuuint64_t dims[4]    = {64, 8, 6, (cuuint64_t)(M / 8)};
        const cuuint64_t strides[3] = {C * 2, 128, 8 * C * 2};
        const cuuint32_t box[4]     = {64, 8, 6, TILE_PIX / 16};
        make(&maps.x, 4, x, dims, strides, box, CU_TENSOR_MAP_L2_PROMOTION_L2_128B);
    }
    {
        const cuuint64_t dims[3]    = {C, C / 2, 2};
        const cuuint64_t strides[2] = {C * 2, C * C};
        const cuuint32_t box[3]     = {64, C / 2, 2};
        make(&maps.w, 3, w, dims, strides, box, CU_TENSOR_MAP_L2_PROMOTION_L2_128B);
    }
    {
        const cuuint64_t dims[2]    = {C, (cuuint64_t)M};
        const cuuint64_t strides[1] = {C * 2};
        const cuuint32_t box[2]     = {64, TILE_PIX};
        make(&maps.out, 2, d_out, dims, strides, box, CU_TENSOR_MAP_L2_PROMOTION_NONE);
    }

    const Tune tune;
    int clusters = sms / 2;
    if (clusters > num_tiles / (int)TP(N_STATIC)) clusters = num_tiles / (int)TP(N_STATIC);
    conv1x1_kernel<<<clusters * 2, THREADS, SMEM_TOTAL>>>((const uint8_t*)x, (const uint8_t*)w, b, (uint32_t)num_tiles,
                                                          (uint32_t)clusters, maps, tune);
}
```

```cpp
#include <cuda_runtime.h>
#include <cuda_bf16.h>
#include <cuda.h>
#include <stdint.h>

#define EARLY_AT 18

#define W_FIRST 2
#define PRE_X 1
#define PRE_D0 200
#define PRE_DT 300
#define PRE_W 64

#define TUNABLES(F) \
    F(EARLY_TILES, 198)    \
    F(EARLY_HEAD, 660)       \
    F(N_STATIC, 19)        \
    F(PM_T0, 0)            \
    F(PM_DT1, 450)         \
    F(PM_E1, 12) \
    F(PM_DT2, 350) \
    F(PM_E2, 21) \
    F(PM_DT3, 940) \
    F(PM_E3, 57) \
    F(PM_DT4, 650) \
    F(PM_E4, 72) \
    F(PM_STAG, 60)        \
    F(LEAD_A, 280)        \
    F(LEAD_F, 500)         \
    F(LEAD_S, 3)           \
    F(LEAD_B, 134)        \
    F(PM_SLACK, 450)    \
    F(EAGER_TO, 2200)         \
    F(EF_TAIL, 260)        \
    F(LAG_AT, 3)           \
    F(LAG_SPREAD, 3)       \
    F(LAG_GAP, 4)          \
    F(LAG_WG, 2)           \
    F(LAG_T1, 32)          \
    F(LAG_T2, 18)           \
    F(DEEP_AT, 120)          \
    F(X0, 0) \
    F(X1, 0) \
    F(X2, 0) \
    F(X3, 0)

struct Tune {
#define F(n, v) static constexpr uint32_t n = v;
    TUNABLES(F)
#undef F
};
#define TP(n) (Tune::n)

#define TRV(slot, idx, v)
#define TR(slot, idx)
#define TRE(slot, idx)

namespace {

constexpr int C            = 384;
constexpr int TILE_PIX     = 64;
constexpr int STAGES       = 3;
constexpr int STAGE_BYTES  = TILE_PIX * C * 2;
constexpr int HALF_BYTES   = STAGE_BYTES / 2;
constexpr int SLICE_BYTES  = TILE_PIX * 128;
constexpr int W_LINES      = C * C * 2 / 128;
constexpr int NUM_WG       = 3;
constexpr int THREADS      = (NUM_WG + 1) * 128;
constexpr int SMEM_OUT     = STAGES * STAGE_BYTES;
constexpr int SMEM_BAR     = SMEM_OUT + STAGES * HALF_BYTES;
constexpr int SMEM_TOTAL   = SMEM_BAR + 512 + 1024;
constexpr int ID_SLOTS     = 16;
constexpr int ID_BARS      = 4;
constexpr uint32_t SPIN_LIMIT = 1u << 24;
constexpr int BAR_W     = 0;
constexpr int BAR_FULL  = 32;
constexpr int BAR_EMPTY = BAR_FULL + 32;
constexpr int BAR_ID    = BAR_EMPTY + 32;
constexpr int BAR_OFREE = BAR_ID + 8 * ID_BARS;
constexpr int BAR_OFULL = BAR_OFREE + 8 * 12;
constexpr int ID_AT     = BAR_OFULL + 8 * 12;
constexpr int FRONT_AT  = ID_AT + 4 * ID_SLOTS;
constexpr int ISSUED_AT = FRONT_AT + 4;
constexpr uint64_t EVICT_NORMAL = 0x1000000000000000ull;
constexpr uint64_t EVICT_FIRST  = 0x12F0000000000000ull;

struct Maps {
    CUtensorMap w, x, out;
};

__device__ unsigned int g_tile_counter;

#define ELECT "{\n.reg .pred e;\nelect.sync _|e, 0xffffffff;\n@e "

__device__ __forceinline__ uint32_t smem_u32(const void* p) {
    return (uint32_t)__cvta_generic_to_shared(p);
}
__device__ __forceinline__ void mbar_init_1(uint32_t bar, uint32_t count) {
    asm volatile(ELECT "mbarrier.init.shared::cta.b64 [%0], %1;\n}" ::"r"(bar), "r"(count) : "memory");
}
__device__ __forceinline__ void mbar_expect_tx_1(uint32_t bar, uint32_t bytes) {
    asm volatile(ELECT "mbarrier.arrive.expect_tx.shared::cta.b64 _, [%0], %1;\n}" ::"r"(bar), "r"(bytes) : "memory");
}
__device__ __forceinline__ void mbar_arrive_1(uint32_t bar) {
    asm volatile(ELECT "mbarrier.arrive.shared::cta.b64 _, [%0];\n}" ::"r"(bar) : "memory");
}
__device__ __forceinline__ void mbar_wait(uint32_t bar, uint32_t parity) {
    uint32_t done;
    uint32_t spins = 0;
    do {
        asm volatile(
            "{\n.reg .pred p;\n"
            "mbarrier.try_wait.parity.shared::cta.b64 p, [%1], %2;\n"
            "selp.u32 %0, 1, 0, p;\n}"
            : "=r"(done) : "r"(bar), "r"(parity) : "memory");
    } while (!done && ++spins < SPIN_LIMIT);
}
__device__ __forceinline__ void mbar_wait_w(uint32_t bar, uint32_t parity) {
    mbar_wait(bar, parity);
    __syncwarp();
}
__device__ __forceinline__ bool mbar_test_w(uint32_t bar, uint32_t parity) {
    uint32_t done;
    asm volatile(
        "{\n.reg .pred p;\n"
        "mbarrier.test_wait.parity.shared::cta.b64 p, [%1], %2;\n"
        "selp.u32 %0, 1, 0, p;\n}"
        : "=r"(done) : "r"(bar), "r"(parity) : "memory");
    return __all_sync(0xffffffffu, done);
}
__device__ __forceinline__ bool mbar_try_w(uint32_t bar, uint32_t parity, uint32_t ns) {
    uint32_t done;
    asm volatile(
        "{\n.reg .pred p;\n"
        "mbarrier.try_wait.parity.shared::cta.b64 p, [%1], %2, %3;\n"
        "selp.u32 %0, 1, 0, p;\n}"
        : "=r"(done) : "r"(bar), "r"(parity), "r"(ns) : "memory");
    return __all_sync(0xffffffffu, done);
}
__device__ __forceinline__ void mbar_arrive_cta(uint32_t bar, uint32_t cta) {
    asm volatile(
        "{\n.reg .b32 ra;\n"
        "mapa.shared::cluster.u32 ra, %0, %1;\n"
        "mbarrier.arrive.shared::cluster.b64 _, [ra];\n}"
        ::"r"(bar), "r"(cta) : "memory");
}
__device__ __forceinline__ void st_async_peer(uint32_t addr, uint32_t val, uint32_t bar) {
    asm volatile(
        "{\n.reg .b32 ra, rb;\n"
        "mapa.shared::cluster.u32 ra, %0, 1;\n"
        "mapa.shared::cluster.u32 rb, %2, 1;\n"
        "st.async.weak.shared::cluster.mbarrier::complete_tx::bytes.b32 [ra], %1, [rb];\n}"
        ::"r"(addr), "r"(val), "r"(bar) : "memory");
}
__device__ __forceinline__ uint32_t lds32(uint32_t addr) {
    uint32_t v;
    asm volatile("ld.shared.b32 %0, [%1];" : "=r"(v) : "r"(addr) : "memory");
    return v;
}
__device__ __forceinline__ uint32_t uniform(uint32_t v) {
    return __shfl_sync(0xffffffffu, v, 0);
}
__device__ __forceinline__ void sts32(uint32_t addr, uint32_t v) {
    asm volatile("st.shared.b32 [%0], %1;" ::"r"(addr), "r"(v) : "memory");
}
__device__ __forceinline__ void tma_load_w_1(uint32_t dst, const CUtensorMap* map, uint32_t bar, int n) {
    asm volatile(
        ELECT "cp.async.bulk.tensor.3d.shared::cluster.global.mbarrier::complete_tx::bytes [%0], [%1, {%3, %4, %4}], [%2];\n}"
        ::"r"(dst), "l"(map), "r"(bar), "r"(n), "r"(0) : "memory");
}
__device__ __forceinline__ void tma_load_x_1(uint32_t dst, const CUtensorMap* map, uint32_t bar, int group, uint64_t policy) {
    asm volatile(
        ELECT "cp.async.bulk.tensor.4d.shared::cluster.global.mbarrier::complete_tx::bytes.multicast::cluster.L2::cache_hint"
        " [%0], [%1, {%3, %3, %3, %4}], [%2], %5, %6;\n}"
        ::"r"(dst), "l"(map), "r"(bar), "r"(0), "r"(group), "h"((uint16_t)3), "l"(policy) : "memory");
}
__device__ __forceinline__ void tma_store_1(const CUtensorMap* map, uint32_t src, int ch, int pix) {
    asm volatile(
        ELECT "cp.async.bulk.tensor.2d.global.shared::cta.bulk_group [%0, {%2, %3}], [%1];\n}\n"
        "cp.async.bulk.commit_group;"
        ::"l"(map), "r"(src), "r"(ch), "r"(pix) : "memory");
}
template <int N>
__device__ __forceinline__ void stores_read_wait() {
    asm volatile("cp.async.bulk.wait_group.read %0;" ::"n"(N) : "memory");
}
__device__ __forceinline__ void prefetch_map_1(const CUtensorMap* map) {
    asm volatile(ELECT "prefetch.tensormap [%0];\n}" ::"l"(map) : "memory");
}
__device__ __forceinline__ uint32_t timer_ns() {
    uint32_t t;
    asm volatile("mov.u32 %0, %%globaltimer_lo;" : "=r"(t)::"memory");
    return t;
}
__device__ __forceinline__ void cluster_arrive() {
    asm volatile("barrier.cluster.arrive.relaxed.aligned;" ::: "memory");
}
__device__ __forceinline__ void cluster_wait() {
    asm volatile("barrier.cluster.wait.aligned;" ::: "memory");
}
__device__ __forceinline__ void publish_barriers() {
    asm volatile("fence.mbarrier_init.release.cluster;" ::: "memory");
    asm volatile("fence.proxy.async.shared::cta;" ::: "memory");
}

__device__ __forceinline__ void wgmma_rs_n64(float (&d)[32], const uint32_t* a, uint64_t desc, int scale_d) {
    asm volatile(
        "{\n.reg .pred p;\n"
        "setp.ne.b32 p, %37, 0;\n"
        "wgmma.mma_async.sync.aligned.m64n64k16.f32.bf16.bf16 "
        "{%0, %1, %2, %3, %4, %5, %6, %7, %8, %9, %10, %11, %12, %13, %14, %15, "
        "%16, %17, %18, %19, %20, %21, %22, %23, %24, %25, %26, %27, %28, %29, %30, %31}, "
        "{%32, %33, %34, %35}, %36, p, 1, 1, 0;\n}"
        : "+f"(d[0]), "+f"(d[1]), "+f"(d[2]), "+f"(d[3]), "+f"(d[4]), "+f"(d[5]), "+f"(d[6]), "+f"(d[7]),
          "+f"(d[8]), "+f"(d[9]), "+f"(d[10]), "+f"(d[11]), "+f"(d[12]), "+f"(d[13]), "+f"(d[14]), "+f"(d[15]),
          "+f"(d[16]), "+f"(d[17]), "+f"(d[18]), "+f"(d[19]), "+f"(d[20]), "+f"(d[21]), "+f"(d[22]), "+f"(d[23]),
          "+f"(d[24]), "+f"(d[25]), "+f"(d[26]), "+f"(d[27]), "+f"(d[28]), "+f"(d[29]), "+f"(d[30]), "+f"(d[31])
        : "r"(a[0]), "r"(a[1]), "r"(a[2]), "r"(a[3]), "l"(desc), "r"(scale_d));
}

__device__ __forceinline__ uint32_t pack_bias(float lo, float hi, uint32_t bias2) {
    uint32_t r;
    asm("{\n.reg .b32 t;\n"
        "cvt.rn.bf16x2.f32 t, %2, %1;\n"
        "add.rn.bf16x2 %0, t, %3;\n}"
        : "=r"(r) : "f"(lo), "f"(hi), "r"(bias2));
    return r;
}

__device__ __forceinline__ int slice_channel(uint32_t rank, int wg) {
    return (wg * 2 + rank) * 64;
}

struct Consumer {
    uint32_t wreg[96];
    uint32_t bias_lo, bias_hi, st_addr, bars;
    uint64_t desc_base;
    int wg, lane;
};
struct Ring {
    uint32_t s, parity;
    __device__ __forceinline__ void advance() {
        if (++s == STAGES) {
            s = 0;
            parity ^= 1;
        }
    }
};
__device__ __forceinline__ uint32_t w_stage(int wg) {
    return (wg + 1) * STAGE_BYTES + (wg == 2 ? HALF_BYTES : 0);
}

__device__ __forceinline__ void consume(const Consumer& c, const Ring& r, float (&acc)[32], uint32_t i, bool early) {
    const int next_turn = 4 + (c.wg + 1) % NUM_WG;
    if ((i | c.wg) != 0) asm volatile("bar.sync %0, 256;" ::"r"(4 + c.wg) : "memory");
    TRE(1 + c.wg * 2, i);
    const uint64_t desc = c.desc_base + (uint64_t)(r.s * (STAGE_BYTES >> 4));
    asm volatile("wgmma.fence.sync.aligned;" ::: "memory");
#pragma unroll
    for (int ks = 0; ks < 24; ks++) {
        const uint64_t d = desc + (uint64_t)((ks >> 2) * 64 + (ks & 3) * 2);
        wgmma_rs_n64(acc, &c.wreg[ks * 4], d, ks != 0);
        if (ks + 1 == EARLY_AT && early) asm volatile("bar.arrive %0, 256;" ::"r"(next_turn) : "memory");
    }
    asm volatile("wgmma.commit_group.sync.aligned;" ::: "memory");
    asm volatile("wgmma.wait_group.sync.aligned 0;" ::: "memory");
#pragma unroll
    for (int j = 0; j < 32; j++) asm volatile("" : "+f"(acc[j])::"memory");
    if (!early) asm volatile("bar.arrive %0, 256;" ::"r"(next_turn) : "memory");
    TRE(2 + c.wg * 2, i);
    if (c.lane < 2) mbar_arrive_cta(c.bars + BAR_EMPTY + 8 * r.s, c.lane);
    const uint32_t obar = c.bars + (r.s * 4 + c.wg) * 8;
    mbar_wait_w(obar + BAR_OFREE, r.parity ^ 1);
    const uint32_t dst = c.st_addr + r.s * HALF_BYTES;
#pragma unroll
    for (int j = 0; j < 4; j++) {
        const uint32_t r0 = pack_bias(acc[8 * j + 0], acc[8 * j + 1], c.bias_lo);
        const uint32_t r1 = pack_bias(acc[8 * j + 2], acc[8 * j + 3], c.bias_hi);
        const uint32_t r2 = pack_bias(acc[8 * j + 4], acc[8 * j + 5], c.bias_lo);
        const uint32_t r3 = pack_bias(acc[8 * j + 6], acc[8 * j + 7], c.bias_hi);
        asm volatile("stmatrix.sync.aligned.m8n8.x4.trans.shared.b16 [%0], {%1, %2, %3, %4};"
                     ::"r"(dst + j * 2048), "r"(r0), "r"(r1), "r"(r2), "r"(r3) : "memory");
    }
    asm volatile("fence.proxy.async.shared::cta;" ::: "memory");
    __syncwarp();
    mbar_arrive_1(obar + BAR_OFULL);
    TRE(8 + c.wg, i);
}

struct StoreQueue {
    uint32_t items, count;
};
__device__ __forceinline__ void release_oldest(StoreQueue& q, uint32_t bars) {
    if (q.count == 1) stores_read_wait<0>();
    else if (q.count == 2) stores_read_wait<1>();
    else if (q.count == 3) stores_read_wait<2>();
    else stores_read_wait<3>();
    mbar_arrive_1(bars + BAR_OFREE + (q.items & 15) * 8);
    q.items >>= 4;
    q.count--;
}

__global__ void __cluster_dims__(2, 1, 1) __launch_bounds__(THREADS, 1)
conv1x1_kernel(const uint8_t* __restrict__ x_raw,
               const uint8_t* __restrict__ w_raw,
               const uint16_t* __restrict__ bias,
               uint32_t num_tiles,
               uint32_t num_clusters,
               const __grid_constant__ Maps maps,
               const __grid_constant__ Tune tune) {
    if (threadIdx.x < 96) {
        const uint32_t line = blockIdx.x % (W_LINES / PRE_W) * PRE_W + threadIdx.x;
        if (threadIdx.x < PRE_W) asm volatile("prefetch.global.L2 [%0];" ::"l"(w_raw + line * 128) : "memory");
    } else if (threadIdx.x < 128) {
        prefetch_map_1(&maps.w);
        prefetch_map_1(&maps.x);
    }
    if (threadIdx.x < NUM_WG * 128) cluster_arrive();
    if (threadIdx.x >= 128 && threadIdx.x < 128 + PRE_X * 96) {
        const uint8_t* p = x_raw + (size_t)blockIdx.x * HALF_BYTES + (threadIdx.x - 128) * 128;
        if (PRE_D0 + PRE_DT != 0) {
            const uint32_t wait = PRE_D0 + ((threadIdx.x - 128) >> 5) * PRE_DT;
            const uint32_t c0 = clock();
            while (clock() - c0 < wait) {}
        }
        asm volatile("prefetch.global.L2 [%0];" ::"l"(p) : "memory");
    }
    extern __shared__ uint8_t smem_raw[];
    const uint32_t smem = (smem_u32(smem_raw) + 1023u) & ~1023u;
    const uint32_t bars = smem + SMEM_BAR;

    const int warp = uniform(threadIdx.x >> 5);
    const int lane = threadIdx.x & 31;
    const uint32_t rank         = blockIdx.x & 1;
    const uint32_t cluster      = blockIdx.x >> 1;

    if (warp < NUM_WG * 4) {
        const int wg = warp >> 2;
        const int wq = warp & 3;
        asm volatile("setmaxnreg.inc.sync.aligned.u32 160;");
        Consumer c;
        c.wg = wg;
        c.lane = lane;
        c.bars = bars;
        c.bias_lo = bias[slice_channel(rank, wg) + wq * 16 + (lane >> 2)] * 0x10001u;
        c.bias_hi = bias[slice_channel(rank, wg) + wq * 16 + (lane >> 2) + 8] * 0x10001u;

        cluster_wait();
        TRE(1 + wg, 63);
        mbar_wait_w(bars + BAR_W + 8 * wg, 0);
        TRE(4 + wg, 63);
        {
            const int r = lane & 7, m = lane >> 3;
            const uint32_t base = smem + w_stage(wg) + ((m >> 1) * 8 + r) * 128 + (((2 * wq + (m & 1)) ^ r) << 4);
#pragma unroll
            for (int ks = 0; ks < 24; ks++) {
                asm volatile("ldmatrix.sync.aligned.m8n8.x4.trans.shared.b16 {%0, %1, %2, %3}, [%4];"
                             : "=r"(c.wreg[ks * 4 + 0]), "=r"(c.wreg[ks * 4 + 1]), "=r"(c.wreg[ks * 4 + 2]), "=r"(c.wreg[ks * 4 + 3])
                             : "r"(base + ks * 2048) : "memory");
            }
        }
        uint32_t dep = 0;
#pragma unroll
        for (int ks = 0; ks < 24; ks++) dep ^= c.wreg[ks * 4];
        dep &= num_tiles >> 31;
        __syncwarp();
        if (lane < 6 && wg < 2) mbar_arrive_cta(bars + BAR_EMPTY + 8 * (wg + 1) + dep, lane & 1);
        TRE(1 + wg, 60);

        c.st_addr = smem + SMEM_OUT + wg * SLICE_BYTES + ((lane >> 4) * 8 + (lane & 7)) * 128 + (((2 * wq + ((lane >> 3) & 1)) ^ (lane & 7)) << 4);
        c.desc_base = (uint64_t)((smem & 0x3FFFF) >> 4) | ((uint64_t)1 << 16) | ((uint64_t)(6144 >> 4) << 32) | ((uint64_t)1 << 62);

        float acc[32];
        Ring r = {0, dep};
        for (uint32_t i = 0;; i++, r.advance()) {
            mbar_wait(bars + BAR_FULL + 8 * r.s, r.parity);
            const uint32_t id = lds32(bars + ID_AT + 4 * (i & (ID_SLOTS - 1)));
            if (id >= num_tiles) break;
            consume(c, r, acc, i, id + TP(EARLY_TILES) >= num_tiles || id + 1 <= TP(EARLY_HEAD));
        }
        if (wg == 0) {
            mbar_wait_w(bars + BAR_OFREE + r.s * 32, r.parity ^ 1);
            mbar_arrive_1(bars + BAR_OFULL + r.s * 32);
            asm volatile("bar.sync 4, 256;" ::: "memory");
        }
        TRE(1 + wg, 62);
    } else {
        asm volatile("setmaxnreg.dec.sync.aligned.u32 32;");
        if (warp == NUM_WG * 4) {
#pragma unroll
            for (int j = 0; j < NUM_WG; j++) mbar_init_1(bars + BAR_W + 8 * j, 1);
            publish_barriers();
            cluster_arrive();
            sts32(bars + ID_AT, cluster);
#pragma unroll
            for (int j = 0; j < NUM_WG; j++) {
                if (j == W_FIRST) {
                    cluster_wait();
                    TR(0, 0);
                    mbar_expect_tx_1(bars + BAR_FULL, STAGE_BYTES);
                    tma_load_x_1(smem + rank * HALF_BYTES, &maps.x, bars + BAR_FULL, cluster * 8 + rank * 4, EVICT_NORMAL);
                }
                mbar_expect_tx_1(bars + BAR_W + 8 * j, STAGE_BYTES);
                tma_load_w_1(smem + w_stage(j), &maps.w, bars + BAR_W + 8 * j, slice_channel(rank, j));
                if (j == 0) TR(2, 61);
            }
            const uint32_t first_dynamic = TP(N_STATIC) * num_clusters;
            const uint32_t wrap = num_tiles - first_dynamic + num_clusters - 1;
            uint32_t s = 0, fph = 1, eph = 0, s1 = 0, s2 = 0, id = 0;
#pragma unroll 1
            for (uint32_t i = 1;; i++) {
                s2 = s1;
                s1 = s;
                s = s == STAGES - 1 ? 0 : s + 1;
                const uint32_t slot = bars + ID_AT + 4 * (i & (ID_SLOTS - 1));
                const bool deep = id + TP(DEEP_AT) >= num_tiles;
                const bool eager = id + 1 <= TP(EAGER_TO);
                id = cluster + i * num_clusters;
                if (i >= TP(N_STATIC)) {
                    const uint32_t b = bars + BAR_ID + 8 * ((i - TP(N_STATIC)) & (ID_BARS - 1));
                    if (rank == 0) {
                        if (deep) mbar_wait_w(bars + BAR_EMPTY + 8 * s, (eph >> s) & 1);
                        else if (i > TP(N_STATIC) && !eager) mbar_wait_w(bars + BAR_FULL + 8 * s2, ((fph >> s2) & 1) ^ 1);
                        if (lane == 0) {
                            id = first_dynamic + atomicInc(&g_tile_counter, wrap);
                            st_async_peer(slot, id, b);
                        }
                    } else {
                        mbar_expect_tx_1(b, 4);
                        mbar_wait_w(b, ((i - TP(N_STATIC)) / ID_BARS) & 1);
                        id = lds32(slot);
                    }
                    id = uniform(id);
                }
                sts32(slot, id);
                sts32(bars + FRONT_AT, id);
                TR(7, i);
                mbar_wait_w(bars + BAR_EMPTY + 8 * s, (eph >> s) & 1);
                eph ^= 1u << s;
                fph ^= 1u << s;
                const uint32_t full = bars + BAR_FULL + 8 * s;
                if (id >= num_tiles) {
                    sts32(bars + ISSUED_AT, id);
                    mbar_arrive_1(full);
#pragma unroll 1
                    for (uint32_t u = 0; u < STAGES; u++)
                        if (u != s) mbar_wait_w(bars + BAR_EMPTY + 8 * u, (eph >> u) & 1);
                    break;
                }
                sts32(bars + ISSUED_AT, id);
                TR(0, i);
                TRV(15, i, id);
                mbar_expect_tx_1(full, STAGE_BYTES);
                tma_load_x_1(smem + s * STAGE_BYTES + rank * HALF_BYTES, &maps.x, full, id * 8 + rank * 4,
                             id + TP(EF_TAIL) >= num_tiles ? EVICT_FIRST : EVICT_NORMAL);
            }
        } else if (warp == NUM_WG * 4 + 1) {
#pragma unroll
            for (int s = 0; s < STAGES; s++) {
                mbar_init_1(bars + BAR_FULL + 8 * s, 1);
                mbar_init_1(bars + BAR_EMPTY + 8 * s, NUM_WG * 4 * 2);
            }
#pragma unroll
            for (int s = 0; s < ID_BARS; s++) mbar_init_1(bars + BAR_ID + 8 * s, 1);
            publish_barriers();
            cluster_arrive();
            TR(0, 61);
            cluster_wait();
            prefetch_map_1(&maps.out);
        } else if (warp == NUM_WG * 4 + 2) {
#pragma unroll
            for (int b = 0; b < 3; b++) {
#pragma unroll
                for (int w = 0; w < NUM_WG; w++) {
                    mbar_init_1(bars + BAR_OFREE + b * 32 + w * 8, 1);
                    mbar_init_1(bars + BAR_OFULL + b * 32 + w * 8, 4);
                }
            }
            publish_barriers();
            cluster_arrive();
            cluster_wait();
            const uint32_t lag_at = TP(LAG_AT) + cluster % TP(LAG_SPREAD);
            StoreQueue q = {0, 0};
            uint32_t ob = 0, phase = 0;
#pragma unroll 1
            for (uint32_t j = 0;; j++) {
                uint32_t lag = (j >= lag_at) + (j >= lag_at + TP(LAG_GAP));
#pragma unroll 1
                for (uint32_t spins = 0; lag != 0 && spins < SPIN_LIMIT; spins++) {
                    const uint32_t front = uniform(lds32(bars + FRONT_AT));
                    if (front + TP(LAG_T2) >= num_tiles) break;
                    if (front + TP(LAG_T1) >= num_tiles) lag = 1;
                    uint32_t b = ob + lag;
                    if (b >= 3) b -= 3;
                    const uint32_t gate = bars + BAR_OFULL + b * 32 + TP(LAG_WG) * 8;
                    if (q.count != 0) {
                        if (mbar_test_w(gate, (phase >> b) & 1)) break;
                        release_oldest(q, bars);
                    } else if (mbar_try_w(gate, (phase >> b) & 1, 100)) {
                        break;
                    }
                }
                const uint32_t parity = (phase >> ob) & 1;
                uint32_t id = 0;
#pragma unroll 1
                for (uint32_t w = 0; w < NUM_WG; w++) {
                    const uint32_t slice = ob * 4 + w;
#pragma unroll 1
                    while (q.count != 0 && !mbar_test_w(bars + BAR_OFULL + slice * 8, parity)) release_oldest(q, bars);
                    if (q.count == 0) mbar_wait_w(bars + BAR_OFULL + slice * 8, parity);
                    if (w == 0) {
                        id = uniform(lds32(bars + ID_AT + 4 * (j & (ID_SLOTS - 1))));
                        if (id >= num_tiles) break;
                    }
                    TR(11 + w, j);
                    tma_store_1(&maps.out, smem + SMEM_OUT + ob * HALF_BYTES + w * SLICE_BYTES, slice_channel(rank, w), id * TILE_PIX);
                    q.items |= slice << (4 * q.count);
                    if (++q.count == 4) release_oldest(q, bars);
                }
                if (id >= num_tiles) break;
                phase ^= 1u << ob;
                ob = ob == STAGES - 1 ? 0 : ob + 1;
            }
            stores_read_wait<0>();
            TR(4, 62);
        } else {
            uint32_t due = timer_ns() + TP(PM_T0) + (blockIdx.x & 3) * TP(PM_STAG);
            sts32(bars + ISSUED_AT, 0);
            cluster_arrive();
            const uint32_t step = num_clusters / 2;
#pragma unroll 1
            for (uint32_t piece = PRE_X; piece < TP(PM_E4); piece++) {
                const uint32_t t = cluster + piece / 2 * num_clusters;
                if (t >= num_tiles) break;
                uint32_t now;
#pragma unroll 1
                for (uint32_t spins = 0; spins < 16384; spins++) {
                    const uint32_t issued = uniform(lds32(bars + ISSUED_AT));
                    now = timer_ns();
                    const int lead = max((int)TP(LEAD_B), (int)TP(LEAD_A) - (max((int)issued - (int)TP(LEAD_F), 0) * (int)TP(LEAD_S) >> 4));
                    if ((int32_t)(now - due) >= 0 && cluster + piece * step <= issued + lead) break;
                    __nanosleep(20);
                }
                if ((int32_t)(now - TP(PM_SLACK) - due) > 0) due = now - TP(PM_SLACK);
                due += piece < TP(PM_E1) ? TP(PM_DT1) : piece < TP(PM_E2) ? TP(PM_DT2) : piece < TP(PM_E3) ? TP(PM_DT3) : TP(PM_DT4);
                const uint8_t* p = x_raw + (size_t)t * STAGE_BYTES + rank * HALF_BYTES + (piece % 2) * 12288 + lane * 128;
#pragma unroll
                for (int k = 0; k < 3; k++) asm volatile("prefetch.global.L2 [%0];" ::"l"(p + k * 4096) : "memory");
                if (piece % 2 == 0) TR(14, piece / 2);
            }
            cluster_wait();
        }
    }
}

typedef CUresult (*EncodeTiledFn)(CUtensorMap*, CUtensorMapDataType, cuuint32_t, void*, const cuuint64_t*,
                                  const cuuint64_t*, const cuuint32_t*, const cuuint32_t*, CUtensorMapInterleave,
                                  CUtensorMapSwizzle, CUtensorMapL2promotion, CUtensorMapFloatOOBfill);

}

extern "C" void kernel_launch(void* const* d_in, const int* in_sizes, int n_in, void* d_out, int out_size) {
    (void)n_in;
    (void)out_size;
    void* x = d_in[0];
    void* w = d_in[1];
    const uint16_t* b = (const uint16_t*)d_in[2];
    const int M = in_sizes[0] / C;
    const int num_tiles = M / TILE_PIX;

    static EncodeTiledFn encode = nullptr;
    static int sms = 0;
    if (!encode) {
        void* fn = nullptr;
        cudaDriverEntryPointQueryResult q;
        cudaGetDriverEntryPoint("cuTensorMapEncodeTiled", &fn, cudaEnableDefault, &q);
        encode = (EncodeTiledFn)fn;
        cudaDeviceGetAttribute(&sms, cudaDevAttrMultiProcessorCount, 0);
        cudaFuncSetAttribute(conv1x1_kernel, cudaFuncAttributeMaxDynamicSharedMemorySize, SMEM_TOTAL);
    }

    Maps maps;
    const cuuint32_t ones[4] = {1, 1, 1, 1};
    auto make = [&](CUtensorMap* map, int rank, void* base, const cuuint64_t* dims, const cuuint64_t* strides,
                    const cuuint32_t* box, CUtensorMapL2promotion promo) {
        encode(map, CU_TENSOR_MAP_DATA_TYPE_BFLOAT16, rank, base, dims, strides, box, ones, CU_TENSOR_MAP_INTERLEAVE_NONE,
               CU_TENSOR_MAP_SWIZZLE_128B, promo, CU_TENSOR_MAP_FLOAT_OOB_FILL_NONE);
    };
    {
        const cuuint64_t dims[4]    = {64, 8, 6, (cuuint64_t)(M / 8)};
        const cuuint64_t strides[3] = {C * 2, 128, 8 * C * 2};
        const cuuint32_t box[4]     = {64, 8, 6, TILE_PIX / 16};
        make(&maps.x, 4, x, dims, strides, box, CU_TENSOR_MAP_L2_PROMOTION_L2_128B);
    }
    {
        const cuuint64_t dims[3]    = {C, C / 2, 2};
        const cuuint64_t strides[2] = {C * 2, C * C};
        const cuuint32_t box[3]     = {64, C / 2, 2};
        make(&maps.w, 3, w, dims, strides, box, CU_TENSOR_MAP_L2_PROMOTION_L2_128B);
    }
    {
        const cuuint64_t dims[2]    = {C, (cuuint64_t)M};
        const cuuint64_t strides[1] = {C * 2};
        const cuuint32_t box[2]     = {64, TILE_PIX};
        make(&maps.out, 2, d_out, dims, strides, box, CU_TENSOR_MAP_L2_PROMOTION_NONE);
    }

    const Tune tune;
    int clusters = sms / 2;
    if (clusters > num_tiles / (int)TP(N_STATIC)) clusters = num_tiles / (int)TP(N_STATIC);
    conv1x1_kernel<<<clusters * 2, THREADS, SMEM_TOTAL>>>((const uint8_t*)x, (const uint8_t*)w, b, (uint32_t)num_tiles,
                                                          (uint32_t)clusters, maps, tune);
}
```

```cpp
#include <cuda_runtime.h>
#include <cuda_bf16.h>
#include <cuda.h>
#include <stdint.h>

#define EARLY_AT 18

#define W_FIRST 2
#define PRE_X 1
#define PRE_D0 200
#define PRE_DT 300
#define PRE_W 64

#define TUNABLES(F) \
    F(EARLY_TILES, 198)    \
    F(EARLY_HEAD, 660)       \
    F(N_STATIC, 20)        \
    F(PM_T0, 0)            \
    F(PM_DT1, 450)         \
    F(PM_E1, 13) \
    F(PM_DT2, 350) \
    F(PM_E2, 20) \
    F(PM_DT3, 940) \
    F(PM_E3, 51) \
    F(PM_DT4, 750) \
    F(PM_E4, 72) \
    F(PM_STAG, 150)        \
    F(LEAD_A, 280)        \
    F(LEAD_F, 500)         \
    F(LEAD_S, 3)           \
    F(LEAD_B, 134)        \
    F(PM_SLACK, 600)    \
    F(AHEAD_TO, 1100)      \
    F(EF_TAIL, 340)        \
    F(LAG_AT, 3)           \
    F(LAG_SPREAD, 3)       \
    F(LAG_GAP, 3)          \
    F(LAG_WG, 2)           \
    F(LAG_T1, 32)          \
    F(LAG_T2, 26)           \
    F(HOLD_AT, 27)         \
    F(HOLD_SPREAD, 1) \
    F(HOLD_T, 80)         \
    F(DEEP_AT, 120)          \
    F(X0, 0) \
    F(X1, 0) \
    F(X2, 0) \
    F(X3, 0)

struct Tune {
#define F(n, v) static constexpr uint32_t n = v;
    TUNABLES(F)
#undef F
};
#define TP(n) (Tune::n)

#define TRV(slot, idx, v)
#define TR(slot, idx)
#define TRE(slot, idx)

namespace {

constexpr int C            = 384;
constexpr int TILE_PIX     = 64;
constexpr int STAGES       = 3;
constexpr int STAGE_BYTES  = TILE_PIX * C * 2;
constexpr int HALF_BYTES   = STAGE_BYTES / 2;
constexpr int SLICE_BYTES  = TILE_PIX * 128;
constexpr int W_LINES      = C * C * 2 / 128;
constexpr int NUM_WG       = 3;
constexpr int THREADS      = (NUM_WG + 1) * 128;
constexpr int SMEM_OUT     = STAGES * STAGE_BYTES;
constexpr int SMEM_BAR     = SMEM_OUT + STAGES * HALF_BYTES;
constexpr int SMEM_TOTAL   = SMEM_BAR + 512 + 1024;
constexpr int ID_SLOTS     = 16;
constexpr int ID_BARS      = 4;
constexpr uint32_t SPIN_LIMIT = 1u << 24;
constexpr int BAR_W     = 0;
constexpr int BAR_FULL  = 32;
constexpr int BAR_EMPTY = BAR_FULL + 32;
constexpr int BAR_ID    = BAR_EMPTY + 32;
constexpr int BAR_OFREE = BAR_ID + 8 * ID_BARS;
constexpr int BAR_OFULL = BAR_OFREE + 8 * 12;
constexpr int ID_AT     = BAR_OFULL + 8 * 12;
constexpr int FRONT_AT  = ID_AT + 4 * ID_SLOTS;
constexpr int ISSUED_AT = FRONT_AT + 4;
constexpr uint64_t EVICT_NORMAL = 0x1000000000000000ull;
constexpr uint64_t EVICT_FIRST  = 0x12F0000000000000ull;

struct Maps {
    CUtensorMap w, x, out;
};

__device__ unsigned int g_tile_counter;

#define ELECT "{\n.reg .pred e;\nelect.sync _|e, 0xffffffff;\n@e "

__device__ __forceinline__ uint32_t smem_u32(const void* p) {
    return (uint32_t)__cvta_generic_to_shared(p);
}
__device__ __forceinline__ void mbar_init_1(uint32_t bar, uint32_t count) {
    asm volatile(ELECT "mbarrier.init.shared::cta.b64 [%0], %1;\n}" ::"r"(bar), "r"(count) : "memory");
}
__device__ __forceinline__ void mbar_expect_tx_1(uint32_t bar, uint32_t bytes) {
    asm volatile(ELECT "mbarrier.arrive.expect_tx.shared::cta.b64 _, [%0], %1;\n}" ::"r"(bar), "r"(bytes) : "memory");
}
__device__ __forceinline__ void mbar_arrive_1(uint32_t bar) {
    asm volatile(ELECT "mbarrier.arrive.shared::cta.b64 _, [%0];\n}" ::"r"(bar) : "memory");
}
__device__ __forceinline__ void mbar_wait(uint32_t bar, uint32_t parity) {
    uint32_t done;
    uint32_t spins = 0;
    do {
        asm volatile(
            "{\n.reg .pred p;\n"
            "mbarrier.try_wait.parity.shared::cta.b64 p, [%1], %2;\n"
            "selp.u32 %0, 1, 0, p;\n}"
            : "=r"(done) : "r"(bar), "r"(parity) : "memory");
    } while (!done && ++spins < SPIN_LIMIT);
}
__device__ __forceinline__ void mbar_wait_w(uint32_t bar, uint32_t parity) {
    mbar_wait(bar, parity);
    __syncwarp();
}
__device__ __forceinline__ bool mbar_test_w(uint32_t bar, uint32_t parity) {
    uint32_t done;
    asm volatile(
        "{\n.reg .pred p;\n"
        "mbarrier.test_wait.parity.shared::cta.b64 p, [%1], %2;\n"
        "selp.u32 %0, 1, 0, p;\n}"
        : "=r"(done) : "r"(bar), "r"(parity) : "memory");
    return __all_sync(0xffffffffu, done);
}
__device__ __forceinline__ bool mbar_try_w(uint32_t bar, uint32_t parity, uint32_t ns) {
    uint32_t done;
    asm volatile(
        "{\n.reg .pred p;\n"
        "mbarrier.try_wait.parity.shared::cta.b64 p, [%1], %2, %3;\n"
        "selp.u32 %0, 1, 0, p;\n}"
        : "=r"(done) : "r"(bar), "r"(parity), "r"(ns) : "memory");
    return __all_sync(0xffffffffu, done);
}
__device__ __forceinline__ void mbar_arrive_cta(uint32_t bar, uint32_t cta) {
    asm volatile(
        "{\n.reg .b32 ra;\n"
        "mapa.shared::cluster.u32 ra, %0, %1;\n"
        "mbarrier.arrive.shared::cluster.b64 _, [ra];\n}"
        ::"r"(bar), "r"(cta) : "memory");
}
__device__ __forceinline__ void st_async_peer(uint32_t addr, uint32_t val, uint32_t bar) {
    asm volatile(
        "{\n.reg .b32 ra, rb;\n"
        "mapa.shared::cluster.u32 ra, %0, 1;\n"
        "mapa.shared::cluster.u32 rb, %2, 1;\n"
        "st.async.weak.shared::cluster.mbarrier::complete_tx::bytes.b32 [ra], %1, [rb];\n}"
        ::"r"(addr), "r"(val), "r"(bar) : "memory");
}
__device__ __forceinline__ uint32_t lds32(uint32_t addr) {
    uint32_t v;
    asm volatile("ld.shared.b32 %0, [%1];" : "=r"(v) : "r"(addr) : "memory");
    return v;
}
__device__ __forceinline__ uint32_t uniform(uint32_t v) {
    return __shfl_sync(0xffffffffu, v, 0);
}
__device__ __forceinline__ void sts32(uint32_t addr, uint32_t v) {
    asm volatile("st.shared.b32 [%0], %1;" ::"r"(addr), "r"(v) : "memory");
}
__device__ __forceinline__ void tma_load_w_1(uint32_t dst, const CUtensorMap* map, uint32_t bar, int n) {
    asm volatile(
        ELECT "cp.async.bulk.tensor.3d.shared::cluster.global.mbarrier::complete_tx::bytes [%0], [%1, {%3, %4, %4}], [%2];\n}"
        ::"r"(dst), "l"(map), "r"(bar), "r"(n), "r"(0) : "memory");
}
__device__ __forceinline__ void tma_load_x_1(uint32_t dst, const CUtensorMap* map, uint32_t bar, int group, uint64_t policy) {
    asm volatile(
        ELECT "cp.async.bulk.tensor.4d.shared::cluster.global.mbarrier::complete_tx::bytes.multicast::cluster.L2::cache_hint"
        " [%0], [%1, {%3, %3, %3, %4}], [%2], %5, %6;\n}"
        ::"r"(dst), "l"(map), "r"(bar), "r"(0), "r"(group), "h"((uint16_t)3), "l"(policy) : "memory");
}
__device__ __forceinline__ void tma_store_1(const CUtensorMap* map, uint32_t src, int ch, int pix) {
    asm volatile(
        ELECT "cp.async.bulk.tensor.2d.global.shared::cta.bulk_group [%0, {%2, %3}], [%1];\n}\n"
        "cp.async.bulk.commit_group;"
        ::"l"(map), "r"(src), "r"(ch), "r"(pix) : "memory");
}
template <int N>
__device__ __forceinline__ void stores_read_wait() {
    asm volatile("cp.async.bulk.wait_group.read %0;" ::"n"(N) : "memory");
}
__device__ __forceinline__ void prefetch_map_1(const CUtensorMap* map) {
    asm volatile(ELECT "prefetch.tensormap [%0];\n}" ::"l"(map) : "memory");
}
__device__ __forceinline__ uint32_t timer_ns() {
    uint32_t t;
    asm volatile("mov.u32 %0, %%globaltimer_lo;" : "=r"(t)::"memory");
    return t;
}
__device__ __forceinline__ void cluster_arrive() {
    asm volatile("barrier.cluster.arrive.relaxed.aligned;" ::: "memory");
}
__device__ __forceinline__ void cluster_wait() {
    asm volatile("barrier.cluster.wait.aligned;" ::: "memory");
}
__device__ __forceinline__ void publish_barriers() {
    asm volatile("fence.mbarrier_init.release.cluster;" ::: "memory");
    asm volatile("fence.proxy.async.shared::cta;" ::: "memory");
}

__device__ __forceinline__ void wgmma_rs_n64(float (&d)[32], const uint32_t* a, uint64_t desc, int scale_d) {
    asm volatile(
        "{\n.reg .pred p;\n"
        "setp.ne.b32 p, %37, 0;\n"
        "wgmma.mma_async.sync.aligned.m64n64k16.f32.bf16.bf16 "
        "{%0, %1, %2, %3, %4, %5, %6, %7, %8, %9, %10, %11, %12, %13, %14, %15, "
        "%16, %17, %18, %19, %20, %21, %22, %23, %24, %25, %26, %27, %28, %29, %30, %31}, "
        "{%32, %33, %34, %35}, %36, p, 1, 1, 0;\n}"
        : "+f"(d[0]), "+f"(d[1]), "+f"(d[2]), "+f"(d[3]), "+f"(d[4]), "+f"(d[5]), "+f"(d[6]), "+f"(d[7]),
          "+f"(d[8]), "+f"(d[9]), "+f"(d[10]), "+f"(d[11]), "+f"(d[12]), "+f"(d[13]), "+f"(d[14]), "+f"(d[15]),
          "+f"(d[16]), "+f"(d[17]), "+f"(d[18]), "+f"(d[19]), "+f"(d[20]), "+f"(d[21]), "+f"(d[22]), "+f"(d[23]),
          "+f"(d[24]), "+f"(d[25]), "+f"(d[26]), "+f"(d[27]), "+f"(d[28]), "+f"(d[29]), "+f"(d[30]), "+f"(d[31])
        : "r"(a[0]), "r"(a[1]), "r"(a[2]), "r"(a[3]), "l"(desc), "r"(scale_d));
}

__device__ __forceinline__ uint32_t pack_bias(float lo, float hi, uint32_t bias2) {
    uint32_t r;
    asm("{\n.reg .b32 t;\n"
        "cvt.rn.bf16x2.f32 t, %2, %1;\n"
        "add.rn.bf16x2 %0, t, %3;\n}"
        : "=r"(r) : "f"(lo), "f"(hi), "r"(bias2));
    return r;
}

__device__ __forceinline__ int slice_channel(uint32_t rank, int wg) {
    return (wg * 2 + rank) * 64;
}

struct Consumer {
    uint32_t wreg[96];
    uint32_t bias_lo, bias_hi, st_addr, bars;
    uint64_t desc_base;
    int wg, lane;
};
struct Ring {
    uint32_t s, parity;
    __device__ __forceinline__ void advance() {
        if (++s == STAGES) {
            s = 0;
            parity ^= 1;
        }
    }
};
__device__ __forceinline__ uint32_t w_stage(int wg) {
    return (wg + 1) * STAGE_BYTES + (wg == 2 ? HALF_BYTES : 0);
}

__device__ __forceinline__ void multiply(const Consumer& c, const Ring& r, float (&acc)[32], uint32_t i, bool early) {
    const int next_turn = 4 + (c.wg + 1) % NUM_WG;
    if ((i | c.wg) != 0) asm volatile("bar.sync %0, 256;" ::"r"(4 + c.wg) : "memory");
    TRE(1 + c.wg * 2, i);
    const uint64_t desc = c.desc_base + (uint64_t)(r.s * (STAGE_BYTES >> 4));
    asm volatile("wgmma.fence.sync.aligned;" ::: "memory");
#pragma unroll
    for (int ks = 0; ks < 24; ks++) {
        const uint64_t d = desc + (uint64_t)((ks >> 2) * 64 + (ks & 3) * 2);
        wgmma_rs_n64(acc, &c.wreg[ks * 4], d, ks != 0);
        if (ks + 1 == EARLY_AT && early) asm volatile("bar.arrive %0, 256;" ::"r"(next_turn) : "memory");
    }
    asm volatile("wgmma.commit_group.sync.aligned;" ::: "memory");
    asm volatile("wgmma.wait_group.sync.aligned 0;" ::: "memory");
#pragma unroll
    for (int j = 0; j < 32; j++) asm volatile("" : "+f"(acc[j])::"memory");
    if (!early) asm volatile("bar.arrive %0, 256;" ::"r"(next_turn) : "memory");
    TRE(2 + c.wg * 2, i);
    if (c.lane < 2) mbar_arrive_cta(c.bars + BAR_EMPTY + 8 * r.s, c.lane);
}
__device__ __forceinline__ void write_out(const Consumer& c, const Ring& r, const uint32_t (&v)[16]) {
    const uint32_t obar = c.bars + (r.s * 4 + c.wg) * 8;
    mbar_wait_w(obar + BAR_OFREE, r.parity ^ 1);
    const uint32_t dst = c.st_addr + r.s * HALF_BYTES;
#pragma unroll
    for (int j = 0; j < 4; j++) {
        asm volatile("stmatrix.sync.aligned.m8n8.x4.trans.shared.b16 [%0], {%1, %2, %3, %4};"
                     ::"r"(dst + j * 2048), "r"(v[4 * j]), "r"(v[4 * j + 1]), "r"(v[4 * j + 2]), "r"(v[4 * j + 3]) : "memory");
    }
    asm volatile("fence.proxy.async.shared::cta;" ::: "memory");
    __syncwarp();
    mbar_arrive_1(obar + BAR_OFULL);
}

struct StoreQueue {
    uint32_t items, count;
};
__device__ __forceinline__ void release_oldest(StoreQueue& q, uint32_t bars) {
    if (q.count == 1) stores_read_wait<0>();
    else if (q.count == 2) stores_read_wait<1>();
    else if (q.count == 3) stores_read_wait<2>();
    else stores_read_wait<3>();
    mbar_arrive_1(bars + BAR_OFREE + (q.items & 15) * 8);
    q.items >>= 4;
    q.count--;
}

__global__ void __cluster_dims__(2, 1, 1) __launch_bounds__(THREADS, 1)
conv1x1_kernel(const uint8_t* __restrict__ x_raw,
               const uint8_t* __restrict__ w_raw,
               const uint16_t* __restrict__ bias,
               uint32_t num_tiles,
               uint32_t num_clusters,
               const __grid_constant__ Maps maps,
               const __grid_constant__ Tune tune) {
    if (threadIdx.x < 96) {
        const uint32_t line = blockIdx.x % (W_LINES / PRE_W) * PRE_W + threadIdx.x;
        if (threadIdx.x < PRE_W) asm volatile("prefetch.global.L2 [%0];" ::"l"(w_raw + line * 128) : "memory");
    } else if (threadIdx.x < 128) {
        prefetch_map_1(&maps.w);
        prefetch_map_1(&maps.x);
    }
    if (threadIdx.x < NUM_WG * 128) cluster_arrive();
    if (threadIdx.x >= 128 && threadIdx.x < 128 + PRE_X * 96) {
        const uint8_t* p = x_raw + (size_t)blockIdx.x * HALF_BYTES + (threadIdx.x - 128) * 128;
        if (PRE_D0 + PRE_DT != 0) {
            const uint32_t wait = PRE_D0 + ((threadIdx.x - 128) >> 5) * PRE_DT;
            const uint32_t c0 = clock();
            while (clock() - c0 < wait) {}
        }
        asm volatile("prefetch.global.L2 [%0];" ::"l"(p) : "memory");
    }
    extern __shared__ uint8_t smem_raw[];
    const uint32_t smem = (smem_u32(smem_raw) + 1023u) & ~1023u;
    const uint32_t bars = smem + SMEM_BAR;

    const int warp = uniform(threadIdx.x >> 5);
    const int lane = threadIdx.x & 31;
    const uint32_t rank         = blockIdx.x & 1;
    const uint32_t cluster      = blockIdx.x >> 1;

    if (warp < NUM_WG * 4) {
        const int wg = warp >> 2;
        const int wq = warp & 3;
        asm volatile("setmaxnreg.inc.sync.aligned.u32 160;");
        Consumer c;
        c.wg = wg;
        c.lane = lane;
        c.bars = bars;
        c.bias_lo = bias[slice_channel(rank, wg) + wq * 16 + (lane >> 2)] * 0x10001u;
        c.bias_hi = bias[slice_channel(rank, wg) + wq * 16 + (lane >> 2) + 8] * 0x10001u;

        cluster_wait();
        TRE(1 + wg, 63);
        mbar_wait_w(bars + BAR_W + 8 * wg, 0);
        TRE(4 + wg, 63);
        {
            const int r = lane & 7, m = lane >> 3;
            const uint32_t base = smem + w_stage(wg) + ((m >> 1) * 8 + r) * 128 + (((2 * wq + (m & 1)) ^ r) << 4);
#pragma unroll
            for (int ks = 0; ks < 24; ks++) {
                asm volatile("ldmatrix.sync.aligned.m8n8.x4.trans.shared.b16 {%0, %1, %2, %3}, [%4];"
                             : "=r"(c.wreg[ks * 4 + 0]), "=r"(c.wreg[ks * 4 + 1]), "=r"(c.wreg[ks * 4 + 2]), "=r"(c.wreg[ks * 4 + 3])
                             : "r"(base + ks * 2048) : "memory");
            }
        }
        uint32_t dep = 0;
#pragma unroll
        for (int ks = 0; ks < 24; ks++) dep ^= c.wreg[ks * 4];
        dep &= num_tiles >> 31;
        __syncwarp();
        if (lane < 6 && wg < 2) mbar_arrive_cta(bars + BAR_EMPTY + 8 * (wg + 1) + dep, lane & 1);
        TRE(1 + wg, 60);

        c.st_addr = smem + SMEM_OUT + wg * SLICE_BYTES + ((lane >> 4) * 8 + (lane & 7)) * 128 + (((2 * wq + ((lane >> 3) & 1)) ^ (lane & 7)) << 4);
        c.desc_base = (uint64_t)((smem & 0x3FFFF) >> 4) | ((uint64_t)1 << 16) | ((uint64_t)(6144 >> 4) << 32) | ((uint64_t)1 << 62);

        float acc[32];
        uint32_t packed[16];
        const uint32_t hold_at = TP(HOLD_AT) + cluster % TP(HOLD_SPREAD);
        Ring r = {0, dep}, o = r;
        bool held = false;
        for (uint32_t i = 0;; i++, r.advance()) {
            mbar_wait(bars + BAR_FULL + 8 * r.s, r.parity);
            const uint32_t id = lds32(bars + ID_AT + 4 * (i & (ID_SLOTS - 1)));
            if (id >= num_tiles) break;
            multiply(c, r, acc, i, id + TP(EARLY_TILES) >= num_tiles || id + 1 <= TP(EARLY_HEAD));
            if (held) write_out(c, o, packed);
#pragma unroll
            for (int j = 0; j < 16; j++) packed[j] = pack_bias(acc[2 * j], acc[2 * j + 1], j & 1 ? c.bias_hi : c.bias_lo);
            o = r;
            held = i >= hold_at && id + TP(HOLD_T) < num_tiles;
            if (!held) write_out(c, o, packed);
            TRE(8 + wg, i);
        }
        if (held) write_out(c, o, packed);
        if (wg == 0) {
            mbar_wait_w(bars + BAR_OFREE + r.s * 32, r.parity ^ 1);
            mbar_arrive_1(bars + BAR_OFULL + r.s * 32);
            asm volatile("bar.sync 4, 256;" ::: "memory");
        }
        TRE(1 + wg, 62);
    } else {
        asm volatile("setmaxnreg.dec.sync.aligned.u32 32;");
        if (warp == NUM_WG * 4) {
#pragma unroll
            for (int j = 0; j < NUM_WG; j++) mbar_init_1(bars + BAR_W + 8 * j, 1);
            publish_barriers();
            cluster_arrive();
            sts32(bars + ID_AT, cluster);
#pragma unroll
            for (int j = 0; j < NUM_WG; j++) {
                if (j == W_FIRST) {
                    cluster_wait();
                    TR(0, 0);
                    mbar_expect_tx_1(bars + BAR_FULL, STAGE_BYTES);
                    tma_load_x_1(smem + rank * HALF_BYTES, &maps.x, bars + BAR_FULL, cluster * 8 + rank * 4, EVICT_NORMAL);
                }
                mbar_expect_tx_1(bars + BAR_W + 8 * j, STAGE_BYTES);
                tma_load_w_1(smem + w_stage(j), &maps.w, bars + BAR_W + 8 * j, slice_channel(rank, j));
                if (j == 0) TR(2, 61);
            }
            const uint32_t first_dynamic = TP(N_STATIC) * num_clusters;
            const uint32_t wrap = num_tiles - first_dynamic + num_clusters - 1;
            uint32_t s = 0, eph = 0, next = 0, id = 0;
            bool drawn = false;
#pragma unroll 1
            for (uint32_t i = 1;; i++) {
                s = s == STAGES - 1 ? 0 : s + 1;
                const uint32_t slot = bars + ID_AT + 4 * (i & (ID_SLOTS - 1));
                const bool late = id + TP(DEEP_AT) >= num_tiles;
                id = cluster + i * num_clusters;
                if (i >= TP(N_STATIC)) {
                    const uint32_t b = bars + BAR_ID + 8 * ((i - TP(N_STATIC)) & (ID_BARS - 1));
                    if (rank == 0) {
                        if (!drawn) {
                            if (late) mbar_wait_w(bars + BAR_EMPTY + 8 * s, (eph >> s) & 1);
                            if (lane == 0) next = atomicInc(&g_tile_counter, wrap);
                        }
                        id = first_dynamic + next;
                        if (lane == 0) st_async_peer(slot, id, b);
                    } else {
                        mbar_expect_tx_1(b, 4);
                        mbar_wait_w(b, ((i - TP(N_STATIC)) / ID_BARS) & 1);
                        id = lds32(slot);
                    }
                    id = uniform(id);
                }
                drawn = rank == 0 && i + 1 >= TP(N_STATIC) && id + TP(AHEAD_TO) < num_tiles;
                if (drawn && lane == 0) next = atomicInc(&g_tile_counter, wrap);
                sts32(slot, id);
                sts32(bars + FRONT_AT, id);
                TR(7, i);
                mbar_wait_w(bars + BAR_EMPTY + 8 * s, (eph >> s) & 1);
                eph ^= 1u << s;
                const uint32_t full = bars + BAR_FULL + 8 * s;
                if (id >= num_tiles) {
                    sts32(bars + ISSUED_AT, id);
                    mbar_arrive_1(full);
#pragma unroll 1
                    for (uint32_t u = 0; u < STAGES; u++)
                        if (u != s) mbar_wait_w(bars + BAR_EMPTY + 8 * u, (eph >> u) & 1);
                    break;
                }
                sts32(bars + ISSUED_AT, id);
                TR(0, i);
                TRV(15, i, id);
                mbar_expect_tx_1(full, STAGE_BYTES);
                tma_load_x_1(smem + s * STAGE_BYTES + rank * HALF_BYTES, &maps.x, full, id * 8 + rank * 4,
                             id + TP(EF_TAIL) >= num_tiles ? EVICT_FIRST : EVICT_NORMAL);
            }
        } else if (warp == NUM_WG * 4 + 1) {
#pragma unroll
            for (int s = 0; s < STAGES; s++) {
                mbar_init_1(bars + BAR_FULL + 8 * s, 1);
                mbar_init_1(bars + BAR_EMPTY + 8 * s, NUM_WG * 4 * 2);
            }
#pragma unroll
            for (int s = 0; s < ID_BARS; s++) mbar_init_1(bars + BAR_ID + 8 * s, 1);
            publish_barriers();
            cluster_arrive();
            TR(0, 61);
            cluster_wait();
            prefetch_map_1(&maps.out);
        } else if (warp == NUM_WG * 4 + 2) {
#pragma unroll
            for (int b = 0; b < 3; b++) {
#pragma unroll
                for (int w = 0; w < NUM_WG; w++) {
                    mbar_init_1(bars + BAR_OFREE + b * 32 + w * 8, 1);
                    mbar_init_1(bars + BAR_OFULL + b * 32 + w * 8, 4);
                }
            }
            publish_barriers();
            cluster_arrive();
            cluster_wait();
            const uint32_t lag_at = TP(LAG_AT) + cluster % TP(LAG_SPREAD);
            StoreQueue q = {0, 0};
            uint32_t ob = 0, phase = 0;
#pragma unroll 1
            for (uint32_t j = 0;; j++) {
                uint32_t lag = (j >= lag_at) + (j >= lag_at + TP(LAG_GAP));
#pragma unroll 1
                for (uint32_t spins = 0; lag != 0 && spins < SPIN_LIMIT; spins++) {
                    const uint32_t front = uniform(lds32(bars + FRONT_AT));
                    if (front + TP(LAG_T2) >= num_tiles) break;
                    if (front + TP(LAG_T1) >= num_tiles) lag = 1;
                    uint32_t b = ob + lag;
                    if (b >= 3) b -= 3;
                    const uint32_t gate = bars + BAR_OFULL + b * 32 + TP(LAG_WG) * 8;
                    if (q.count != 0) {
                        if (mbar_test_w(gate, (phase >> b) & 1)) break;
                        release_oldest(q, bars);
                    } else if (mbar_try_w(gate, (phase >> b) & 1, 100)) {
                        break;
                    }
                }
                const uint32_t parity = (phase >> ob) & 1;
                uint32_t id = 0;
#pragma unroll 1
                for (uint32_t w = 0; w < NUM_WG; w++) {
                    const uint32_t slice = ob * 4 + w;
#pragma unroll 1
                    while (q.count != 0 && !mbar_test_w(bars + BAR_OFULL + slice * 8, parity)) release_oldest(q, bars);
                    if (q.count == 0) mbar_wait_w(bars + BAR_OFULL + slice * 8, parity);
                    if (w == 0) {
                        id = uniform(lds32(bars + ID_AT + 4 * (j & (ID_SLOTS - 1))));
                        if (id >= num_tiles) break;
                    }
                    TR(11 + w, j);
                    tma_store_1(&maps.out, smem + SMEM_OUT + ob * HALF_BYTES + w * SLICE_BYTES, slice_channel(rank, w), id * TILE_PIX);
                    q.items |= slice << (4 * q.count);
                    if (++q.count == 4) release_oldest(q, bars);
                }
                if (id >= num_tiles) break;
                phase ^= 1u << ob;
                ob = ob == STAGES - 1 ? 0 : ob + 1;
            }
            stores_read_wait<0>();
            TR(4, 62);
        } else {
            uint32_t due = timer_ns() + TP(PM_T0) + (blockIdx.x & 3) * TP(PM_STAG);
            sts32(bars + ISSUED_AT, 0);
            cluster_arrive();
            const uint32_t step = num_clusters / 2;
#pragma unroll 1
            for (uint32_t piece = PRE_X; piece < TP(PM_E4); piece++) {
                const uint32_t t = cluster + piece / 2 * num_clusters;
                if (t >= num_tiles) break;
                uint32_t now;
#pragma unroll 1
                for (uint32_t spins = 0; spins < 16384; spins++) {
                    const uint32_t issued = uniform(lds32(bars + ISSUED_AT));
                    now = timer_ns();
                    const int lead = max((int)TP(LEAD_B), (int)TP(LEAD_A) - (max((int)issued - (int)TP(LEAD_F), 0) * (int)TP(LEAD_S) >> 4));
                    if ((int32_t)(now - due) >= 0 && cluster + piece * step <= issued + lead) break;
                    __nanosleep(20);
                }
                if ((int32_t)(now - TP(PM_SLACK) - due) > 0) due = now - TP(PM_SLACK);
                due += piece < TP(PM_E1) ? TP(PM_DT1) : piece < TP(PM_E2) ? TP(PM_DT2) : piece < TP(PM_E3) ? TP(PM_DT3) : TP(PM_DT4);
                const uint8_t* p = x_raw + (size_t)t * STAGE_BYTES + rank * HALF_BYTES + (piece % 2) * 12288 + lane * 128;
#pragma unroll
                for (int k = 0; k < 3; k++) asm volatile("prefetch.global.L2 [%0];" ::"l"(p + k * 4096) : "memory");
                if (piece % 2 == 0) TR(14, piece / 2);
            }
            cluster_wait();
        }
    }
}

typedef CUresult (*EncodeTiledFn)(CUtensorMap*, CUtensorMapDataType, cuuint32_t, void*, const cuuint64_t*,
                                  const cuuint64_t*, const cuuint32_t*, const cuuint32_t*, CUtensorMapInterleave,
                                  CUtensorMapSwizzle, CUtensorMapL2promotion, CUtensorMapFloatOOBfill);

}

extern "C" void kernel_launch(void* const* d_in, const int* in_sizes, int n_in, void* d_out, int out_size) {
    (void)n_in;
    (void)out_size;
    void* x = d_in[0];
    void* w = d_in[1];
    const uint16_t* b = (const uint16_t*)d_in[2];
    const int M = in_sizes[0] / C;
    const int num_tiles = M / TILE_PIX;

    static EncodeTiledFn encode = nullptr;
    static int sms = 0;
    if (!encode) {
        void* fn = nullptr;
        cudaDriverEntryPointQueryResult q;
        cudaGetDriverEntryPoint("cuTensorMapEncodeTiled", &fn, cudaEnableDefault, &q);
        encode = (EncodeTiledFn)fn;
        cudaDeviceGetAttribute(&sms, cudaDevAttrMultiProcessorCount, 0);
        cudaFuncSetAttribute(conv1x1_kernel, cudaFuncAttributeMaxDynamicSharedMemorySize, SMEM_TOTAL);
    }

    Maps maps;
    const cuuint32_t ones[4] = {1, 1, 1, 1};
    auto make = [&](CUtensorMap* map, int rank, void* base, const cuuint64_t* dims, const cuuint64_t* strides,
                    const cuuint32_t* box, CUtensorMapL2promotion promo) {
        encode(map, CU_TENSOR_MAP_DATA_TYPE_BFLOAT16, rank, base, dims, strides, box, ones, CU_TENSOR_MAP_INTERLEAVE_NONE,
               CU_TENSOR_MAP_SWIZZLE_128B, promo, CU_TENSOR_MAP_FLOAT_OOB_FILL_NONE);
    };
    {
        const cuuint64_t dims[4]    = {64, 8, 6, (cuuint64_t)(M / 8)};
        const cuuint64_t strides[3] = {C * 2, 128, 8 * C * 2};
        const cuuint32_t box[4]     = {64, 8, 6, TILE_PIX / 16};
        make(&maps.x, 4, x, dims, strides, box, CU_TENSOR_MAP_L2_PROMOTION_L2_128B);
    }
    {
        const cuuint64_t dims[3]    = {C, C / 2, 2};
        const cuuint64_t strides[2] = {C * 2, C * C};
        const cuuint32_t box[3]     = {64, C / 2, 2};
        make(&maps.w, 3, w, dims, strides, box, CU_TENSOR_MAP_L2_PROMOTION_L2_128B);
    }
    {
        const cuuint64_t dims[2]    = {C, (cuuint64_t)M};
        const cuuint64_t strides[1] = {C * 2};
        const cuuint32_t box[2]     = {64, TILE_PIX};
        make(&maps.out, 2, d_out, dims, strides, box, CU_TENSOR_MAP_L2_PROMOTION_NONE);
    }

    const Tune tune;
    int clusters = sms / 2;
    if (clusters > num_tiles / (int)TP(N_STATIC)) clusters = num_tiles / (int)TP(N_STATIC);
    conv1x1_kernel<<<clusters * 2, THREADS, SMEM_TOTAL>>>((const uint8_t*)x, (const uint8_t*)w, b, (uint32_t)num_tiles,
                                                          (uint32_t)clusters, maps, tune);
}
```

```cpp
#include <cuda_runtime.h>
#include <cuda_bf16.h>
#include <cuda.h>
#include <stdint.h>

#define EARLY_AT 18

#define W_FIRST 2
#define PRE_X 1
#define PRE_D0 200
#define PRE_DT 300
#define PRE_W 64

#define TUNABLES(F) \
    F(EARLY_TILES, 396)    \
    F(EARLY_HEAD, 792)       \
    F(N_STATIC, 20)        \
    F(PM_T0, 0)            \
    F(PM_DT1, 435)         \
    F(PM_E1, 14) \
    F(PM_DT2, 350) \
    F(PM_E2, 20) \
    F(PM_DT3, 820) \
    F(PM_E3, 61) \
    F(PM_DT4, 650) \
    F(PM_E4, 72) \
    F(PM_STAG, 150)        \
    F(LEAD_A, 280)        \
    F(LEAD_F, 500)         \
    F(LEAD_S, 3)           \
    F(LEAD_B, 151)        \
    F(PM_SLACK, 300)    \
    F(AHEAD_TO, 1034)      \
    F(EF_TAIL, 380)        \
    F(LAG_AT, 3)           \
    F(LAG_SPREAD, 2)       \
    F(LAG_GAP, 3)          \
    F(LAG_WG, 2)           \
    F(LAG_T1, 62)          \
    F(LAG_T2, 34)           \
    F(WAIT_NS, 900)          \
    F(WAIT_AT, 10)         \
    F(WAIT_T, 120)         \
    F(HOLD_AT, 23)         \
    F(HOLD_SPREAD, 1) \
    F(HOLD_T, 100)         \
    F(DEEP_AT, 120)          \
    F(X0, 0) \
    F(X1, 0) \
    F(X2, 0) \
    F(X3, 0)

struct Tune {
#define F(n, v) static constexpr uint32_t n = v;
    TUNABLES(F)
#undef F
};
#define TP(n) (Tune::n)

#define TRV(slot, idx, v)
#define TR(slot, idx)
#define TRE(slot, idx)

namespace {

constexpr int C            = 384;
constexpr int TILE_PIX     = 64;
constexpr int STAGES       = 3;
constexpr int STAGE_BYTES  = TILE_PIX * C * 2;
constexpr int HALF_BYTES   = STAGE_BYTES / 2;
constexpr int SLICE_BYTES  = TILE_PIX * 128;
constexpr int W_LINES      = C * C * 2 / 128;
constexpr int NUM_WG       = 3;
constexpr int THREADS      = (NUM_WG + 1) * 128;
constexpr int SMEM_OUT     = STAGES * STAGE_BYTES;
constexpr int SMEM_BAR     = SMEM_OUT + STAGES * HALF_BYTES;
constexpr int SMEM_TOTAL   = SMEM_BAR + 512 + 1024;
constexpr int ID_SLOTS     = 16;
constexpr int ID_BARS      = 4;
constexpr uint32_t SPIN_LIMIT = 1u << 24;
constexpr int BAR_W     = 0;
constexpr int BAR_FULL  = 32;
constexpr int BAR_EMPTY = BAR_FULL + 32;
constexpr int BAR_ID    = BAR_EMPTY + 32;
constexpr int BAR_OFREE = BAR_ID + 8 * ID_BARS;
constexpr int BAR_OFULL = BAR_OFREE + 8 * 12;
constexpr int ID_AT     = BAR_OFULL + 8 * 12;
constexpr int FRONT_AT  = ID_AT + 4 * ID_SLOTS;
constexpr int ISSUED_AT = FRONT_AT + 4;
constexpr uint64_t EVICT_NORMAL = 0x1000000000000000ull;
constexpr uint64_t EVICT_FIRST  = 0x12F0000000000000ull;

struct Maps {
    CUtensorMap w, x, out;
};

__device__ unsigned int g_tile_counter;

#define ELECT "{\n.reg .pred e;\nelect.sync _|e, 0xffffffff;\n@e "

__device__ __forceinline__ uint32_t smem_u32(const void* p) {
    return (uint32_t)__cvta_generic_to_shared(p);
}
__device__ __forceinline__ void mbar_init_1(uint32_t bar, uint32_t count) {
    asm volatile(ELECT "mbarrier.init.shared::cta.b64 [%0], %1;\n}" ::"r"(bar), "r"(count) : "memory");
}
__device__ __forceinline__ void mbar_expect_tx_1(uint32_t bar, uint32_t bytes) {
    asm volatile(ELECT "mbarrier.arrive.expect_tx.shared::cta.b64 _, [%0], %1;\n}" ::"r"(bar), "r"(bytes) : "memory");
}
__device__ __forceinline__ void mbar_arrive_1(uint32_t bar) {
    asm volatile(ELECT "mbarrier.arrive.shared::cta.b64 _, [%0];\n}" ::"r"(bar) : "memory");
}
__device__ __forceinline__ void mbar_wait(uint32_t bar, uint32_t parity) {
    uint32_t done;
    uint32_t spins = 0;
    do {
        asm volatile(
            "{\n.reg .pred p;\n"
            "mbarrier.try_wait.parity.shared::cta.b64 p, [%1], %2;\n"
            "selp.u32 %0, 1, 0, p;\n}"
            : "=r"(done) : "r"(bar), "r"(parity) : "memory");
    } while (!done && ++spins < SPIN_LIMIT);
}
__device__ __forceinline__ void mbar_wait_w(uint32_t bar, uint32_t parity) {
    mbar_wait(bar, parity);
    __syncwarp();
}
__device__ __forceinline__ bool mbar_test_w(uint32_t bar, uint32_t parity) {
    uint32_t done;
    asm volatile(
        "{\n.reg .pred p;\n"
        "mbarrier.test_wait.parity.shared::cta.b64 p, [%1], %2;\n"
        "selp.u32 %0, 1, 0, p;\n}"
        : "=r"(done) : "r"(bar), "r"(parity) : "memory");
    return __all_sync(0xffffffffu, done);
}
__device__ __forceinline__ bool mbar_try_w(uint32_t bar, uint32_t parity, uint32_t ns) {
    uint32_t done;
    asm volatile(
        "{\n.reg .pred p;\n"
        "mbarrier.try_wait.parity.shared::cta.b64 p, [%1], %2, %3;\n"
        "selp.u32 %0, 1, 0, p;\n}"
        : "=r"(done) : "r"(bar), "r"(parity), "r"(ns) : "memory");
    return __all_sync(0xffffffffu, done);
}
__device__ __forceinline__ void mbar_arrive_cta(uint32_t bar, uint32_t cta) {
    asm volatile(
        "{\n.reg .b32 ra;\n"
        "mapa.shared::cluster.u32 ra, %0, %1;\n"
        "mbarrier.arrive.shared::cluster.b64 _, [ra];\n}"
        ::"r"(bar), "r"(cta) : "memory");
}
__device__ __forceinline__ void st_async_peer(uint32_t addr, uint32_t val, uint32_t bar) {
    asm volatile(
        "{\n.reg .b32 ra, rb;\n"
        "mapa.shared::cluster.u32 ra, %0, 1;\n"
        "mapa.shared::cluster.u32 rb, %2, 1;\n"
        "st.async.weak.shared::cluster.mbarrier::complete_tx::bytes.b32 [ra], %1, [rb];\n}"
        ::"r"(addr), "r"(val), "r"(bar) : "memory");
}
__device__ __forceinline__ uint32_t lds32(uint32_t addr) {
    uint32_t v;
    asm volatile("ld.shared.b32 %0, [%1];" : "=r"(v) : "r"(addr) : "memory");
    return v;
}
__device__ __forceinline__ uint32_t uniform(uint32_t v) {
    return __shfl_sync(0xffffffffu, v, 0);
}
__device__ __forceinline__ void sts32(uint32_t addr, uint32_t v) {
    asm volatile("st.shared.b32 [%0], %1;" ::"r"(addr), "r"(v) : "memory");
}
__device__ __forceinline__ void tma_load_w_1(uint32_t dst, const CUtensorMap* map, uint32_t bar, int n) {
    asm volatile(
        ELECT "cp.async.bulk.tensor.3d.shared::cluster.global.mbarrier::complete_tx::bytes [%0], [%1, {%3, %4, %4}], [%2];\n}"
        ::"r"(dst), "l"(map), "r"(bar), "r"(n), "r"(0) : "memory");
}
__device__ __forceinline__ void tma_load_x_1(uint32_t dst, const CUtensorMap* map, uint32_t bar, int group, uint64_t policy) {
    asm volatile(
        ELECT "cp.async.bulk.tensor.4d.shared::cluster.global.mbarrier::complete_tx::bytes.multicast::cluster.L2::cache_hint"
        " [%0], [%1, {%3, %3, %3, %4}], [%2], %5, %6;\n}"
        ::"r"(dst), "l"(map), "r"(bar), "r"(0), "r"(group), "h"((uint16_t)3), "l"(policy) : "memory");
}
__device__ __forceinline__ void tma_store_1(const CUtensorMap* map, uint32_t src, int ch, int pix) {
    asm volatile(
        ELECT "cp.async.bulk.tensor.2d.global.shared::cta.bulk_group [%0, {%2, %3}], [%1];\n}\n"
        "cp.async.bulk.commit_group;"
        ::"l"(map), "r"(src), "r"(ch), "r"(pix) : "memory");
}
template <int N>
__device__ __forceinline__ void stores_read_wait() {
    asm volatile("cp.async.bulk.wait_group.read %0;" ::"n"(N) : "memory");
}
__device__ __forceinline__ void prefetch_map_1(const CUtensorMap* map) {
    asm volatile(ELECT "prefetch.tensormap [%0];\n}" ::"l"(map) : "memory");
}
__device__ __forceinline__ uint32_t timer_ns() {
    uint32_t t;
    asm volatile("mov.u32 %0, %%globaltimer_lo;" : "=r"(t)::"memory");
    return t;
}
__device__ __forceinline__ void cluster_arrive() {
    asm volatile("barrier.cluster.arrive.relaxed.aligned;" ::: "memory");
}
__device__ __forceinline__ void cluster_wait() {
    asm volatile("barrier.cluster.wait.aligned;" ::: "memory");
}
__device__ __forceinline__ void publish_barriers() {
    asm volatile("fence.mbarrier_init.release.cluster;" ::: "memory");
    asm volatile("fence.proxy.async.shared::cta;" ::: "memory");
}

__device__ __forceinline__ void wgmma_rs_n64(float (&d)[32], const uint32_t* a, uint64_t desc, int scale_d) {
    asm volatile(
        "{\n.reg .pred p;\n"
        "setp.ne.b32 p, %37, 0;\n"
        "wgmma.mma_async.sync.aligned.m64n64k16.f32.bf16.bf16 "
        "{%0, %1, %2, %3, %4, %5, %6, %7, %8, %9, %10, %11, %12, %13, %14, %15, "
        "%16, %17, %18, %19, %20, %21, %22, %23, %24, %25, %26, %27, %28, %29, %30, %31}, "
        "{%32, %33, %34, %35}, %36, p, 1, 1, 0;\n}"
        : "+f"(d[0]), "+f"(d[1]), "+f"(d[2]), "+f"(d[3]), "+f"(d[4]), "+f"(d[5]), "+f"(d[6]), "+f"(d[7]),
          "+f"(d[8]), "+f"(d[9]), "+f"(d[10]), "+f"(d[11]), "+f"(d[12]), "+f"(d[13]), "+f"(d[14]), "+f"(d[15]),
          "+f"(d[16]), "+f"(d[17]), "+f"(d[18]), "+f"(d[19]), "+f"(d[20]), "+f"(d[21]), "+f"(d[22]), "+f"(d[23]),
          "+f"(d[24]), "+f"(d[25]), "+f"(d[26]), "+f"(d[27]), "+f"(d[28]), "+f"(d[29]), "+f"(d[30]), "+f"(d[31])
        : "r"(a[0]), "r"(a[1]), "r"(a[2]), "r"(a[3]), "l"(desc), "r"(scale_d));
}

__device__ __forceinline__ uint32_t pack_bias(float lo, float hi, uint32_t bias2) {
    uint32_t r;
    asm("{\n.reg .b32 t;\n"
        "cvt.rn.bf16x2.f32 t, %2, %1;\n"
        "add.rn.bf16x2 %0, t, %3;\n}"
        : "=r"(r) : "f"(lo), "f"(hi), "r"(bias2));
    return r;
}

__device__ __forceinline__ int slice_channel(uint32_t rank, int wg) {
    return (wg * 2 + rank) * 64;
}

struct Consumer {
    uint32_t wreg[96];
    uint32_t bias_lo, bias_hi, st_addr, bars;
    uint64_t desc_base;
    int wg, lane;
};
struct Ring {
    uint32_t s, parity;
    __device__ __forceinline__ void advance() {
        if (++s == STAGES) {
            s = 0;
            parity ^= 1;
        }
    }
};
__device__ __forceinline__ uint32_t w_stage(int wg) {
    return (wg + 1) * STAGE_BYTES + (wg == 2 ? HALF_BYTES : 0);
}

__device__ __forceinline__ void multiply(const Consumer& c, const Ring& r, float (&acc)[32], uint32_t i, bool early) {
    const int next_turn = 4 + (c.wg + 1) % NUM_WG;
    if ((i | c.wg) != 0) asm volatile("bar.sync %0, 256;" ::"r"(4 + c.wg) : "memory");
    TRE(1 + c.wg * 2, i);
    const uint64_t desc = c.desc_base + (uint64_t)(r.s * (STAGE_BYTES >> 4));
    asm volatile("wgmma.fence.sync.aligned;" ::: "memory");
#pragma unroll
    for (int ks = 0; ks < 24; ks++) {
        const uint64_t d = desc + (uint64_t)((ks >> 2) * 64 + (ks & 3) * 2);
        wgmma_rs_n64(acc, &c.wreg[ks * 4], d, ks != 0);
        if (ks + 1 == EARLY_AT && early) asm volatile("bar.arrive %0, 256;" ::"r"(next_turn) : "memory");
    }
    asm volatile("wgmma.commit_group.sync.aligned;" ::: "memory");
    asm volatile("wgmma.wait_group.sync.aligned 0;" ::: "memory");
#pragma unroll
    for (int j = 0; j < 32; j++) asm volatile("" : "+f"(acc[j])::"memory");
    if (!early) asm volatile("bar.arrive %0, 256;" ::"r"(next_turn) : "memory");
    TRE(2 + c.wg * 2, i);
    if (c.lane < 2) mbar_arrive_cta(c.bars + BAR_EMPTY + 8 * r.s, c.lane);
}
__device__ __forceinline__ void write_out(const Consumer& c, const Ring& r, const uint32_t (&v)[16]) {
    const uint32_t obar = c.bars + (r.s * 4 + c.wg) * 8;
    mbar_wait_w(obar + BAR_OFREE, r.parity ^ 1);
    const uint32_t dst = c.st_addr + r.s * HALF_BYTES;
#pragma unroll
    for (int j = 0; j < 4; j++) {
        asm volatile("stmatrix.sync.aligned.m8n8.x4.trans.shared.b16 [%0], {%1, %2, %3, %4};"
                     ::"r"(dst + j * 2048), "r"(v[4 * j]), "r"(v[4 * j + 1]), "r"(v[4 * j + 2]), "r"(v[4 * j + 3]) : "memory");
    }
    asm volatile("fence.proxy.async.shared::cta;" ::: "memory");
    __syncwarp();
    mbar_arrive_1(obar + BAR_OFULL);
}

template <int N>
__device__ __forceinline__ void hand_back(uint32_t& open) {
    if (open != 0) {
        stores_read_wait<N>();
        mbar_arrive_1(open);
        open = 0;
    }
}

__global__ void __cluster_dims__(2, 1, 1) __launch_bounds__(THREADS, 1)
conv1x1_kernel(const uint8_t* __restrict__ x_raw,
               const uint8_t* __restrict__ w_raw,
               const uint16_t* __restrict__ bias,
               uint32_t num_tiles,
               uint32_t num_clusters,
               const __grid_constant__ Maps maps,
               const __grid_constant__ Tune tune) {
    if (threadIdx.x < 96) {
        const uint32_t line = blockIdx.x % (W_LINES / PRE_W) * PRE_W + threadIdx.x;
        if (threadIdx.x < PRE_W) asm volatile("prefetch.global.L2 [%0];" ::"l"(w_raw + line * 128) : "memory");
    } else if (threadIdx.x < 128) {
        prefetch_map_1(&maps.w);
        prefetch_map_1(&maps.x);
    }
    if (threadIdx.x < NUM_WG * 128) cluster_arrive();
    if (threadIdx.x >= 128 && threadIdx.x < 128 + PRE_X * 96) {
        const uint8_t* p = x_raw + (size_t)blockIdx.x * HALF_BYTES + (threadIdx.x - 128) * 128;
        if (PRE_D0 + PRE_DT != 0) {
            const uint32_t wait = PRE_D0 + ((threadIdx.x - 128) >> 5) * PRE_DT;
            const uint32_t c0 = clock();
            while (clock() - c0 < wait) {}
        }
        asm volatile("prefetch.global.L2 [%0];" ::"l"(p) : "memory");
    }
    extern __shared__ uint8_t smem_raw[];
    const uint32_t smem = (smem_u32(smem_raw) + 1023u) & ~1023u;
    const uint32_t bars = smem + SMEM_BAR;

    const int warp = uniform(threadIdx.x >> 5);
    const int lane = threadIdx.x & 31;
    const uint32_t rank         = blockIdx.x & 1;
    const uint32_t cluster      = blockIdx.x >> 1;

    if (warp < NUM_WG * 4) {
        const int wg = warp >> 2;
        const int wq = warp & 3;
        asm volatile("setmaxnreg.inc.sync.aligned.u32 160;");
        Consumer c;
        c.wg = wg;
        c.lane = lane;
        c.bars = bars;
        c.bias_lo = bias[slice_channel(rank, wg) + wq * 16 + (lane >> 2)] * 0x10001u;
        c.bias_hi = bias[slice_channel(rank, wg) + wq * 16 + (lane >> 2) + 8] * 0x10001u;

        cluster_wait();
        TRE(1 + wg, 63);
        mbar_wait_w(bars + BAR_W + 8 * wg, 0);
        TRE(4 + wg, 63);
        {
            const int r = lane & 7, m = lane >> 3;
            const uint32_t base = smem + w_stage(wg) + ((m >> 1) * 8 + r) * 128 + (((2 * wq + (m & 1)) ^ r) << 4);
#pragma unroll
            for (int ks = 0; ks < 24; ks++) {
                asm volatile("ldmatrix.sync.aligned.m8n8.x4.trans.shared.b16 {%0, %1, %2, %3}, [%4];"
                             : "=r"(c.wreg[ks * 4 + 0]), "=r"(c.wreg[ks * 4 + 1]), "=r"(c.wreg[ks * 4 + 2]), "=r"(c.wreg[ks * 4 + 3])
                             : "r"(base + ks * 2048) : "memory");
            }
        }
        uint32_t dep = 0;
#pragma unroll
        for (int ks = 0; ks < 24; ks++) dep ^= c.wreg[ks * 4];
        dep &= num_tiles >> 31;
        __syncwarp();
        if (lane < 6 && wg < 2) mbar_arrive_cta(bars + BAR_EMPTY + 8 * (wg + 1) + dep, lane & 1);
        TRE(1 + wg, 60);

        c.st_addr = smem + SMEM_OUT + wg * SLICE_BYTES + ((lane >> 4) * 8 + (lane & 7)) * 128 + (((2 * wq + ((lane >> 3) & 1)) ^ (lane & 7)) << 4);
        c.desc_base = (uint64_t)((smem & 0x3FFFF) >> 4) | ((uint64_t)1 << 16) | ((uint64_t)(6144 >> 4) << 32) | ((uint64_t)1 << 62);

        float acc[32];
        uint32_t packed[16];
        const uint32_t hold_at = TP(HOLD_AT) + cluster % TP(HOLD_SPREAD);
        Ring r = {0, dep}, o = r;
        bool held = false;
        for (uint32_t i = 0;; i++, r.advance()) {
            mbar_wait(bars + BAR_FULL + 8 * r.s, r.parity);
            const uint32_t id = lds32(bars + ID_AT + 4 * (i & (ID_SLOTS - 1)));
            if (id >= num_tiles) break;
            multiply(c, r, acc, i, id + TP(EARLY_TILES) >= num_tiles || id + 1 <= TP(EARLY_HEAD));
            if (held) write_out(c, o, packed);
#pragma unroll
            for (int j = 0; j < 16; j++) packed[j] = pack_bias(acc[2 * j], acc[2 * j + 1], j & 1 ? c.bias_hi : c.bias_lo);
            o = r;
            held = i >= hold_at && id + TP(HOLD_T) < num_tiles;
            if (!held) write_out(c, o, packed);
            TRE(8 + wg, i);
        }
        if (held) write_out(c, o, packed);
        if (wg == 0) {
            mbar_wait_w(bars + BAR_OFREE + r.s * 32, r.parity ^ 1);
            mbar_arrive_1(bars + BAR_OFULL + r.s * 32);
            asm volatile("bar.sync 4, 256;" ::: "memory");
        }
        TRE(1 + wg, 62);
    } else {
        asm volatile("setmaxnreg.dec.sync.aligned.u32 32;");
        if (warp == NUM_WG * 4) {
#pragma unroll
            for (int j = 0; j < NUM_WG; j++) mbar_init_1(bars + BAR_W + 8 * j, 1);
            publish_barriers();
            cluster_arrive();
            sts32(bars + ID_AT, cluster);
#pragma unroll
            for (int j = 0; j < NUM_WG; j++) {
                if (j == W_FIRST) {
                    cluster_wait();
                    TR(0, 0);
                    mbar_expect_tx_1(bars + BAR_FULL, STAGE_BYTES);
                    tma_load_x_1(smem + rank * HALF_BYTES, &maps.x, bars + BAR_FULL, cluster * 8 + rank * 4, EVICT_NORMAL);
                }
                mbar_expect_tx_1(bars + BAR_W + 8 * j, STAGE_BYTES);
                tma_load_w_1(smem + w_stage(j), &maps.w, bars + BAR_W + 8 * j, slice_channel(rank, j));
                if (j == 0) TR(2, 61);
            }
            const uint32_t first_dynamic = TP(N_STATIC) * num_clusters;
            const uint32_t wrap = num_tiles - first_dynamic + num_clusters - 1;
            uint32_t s = 0, eph = 0, next = 0, id = 0;
            bool drawn = false;
#pragma unroll 1
            for (uint32_t i = 1;; i++) {
                s = s == STAGES - 1 ? 0 : s + 1;
                const uint32_t slot = bars + ID_AT + 4 * (i & (ID_SLOTS - 1));
                const bool late = id + TP(DEEP_AT) >= num_tiles;
                id = cluster + i * num_clusters;
                if (i >= TP(N_STATIC)) {
                    const uint32_t b = bars + BAR_ID + 8 * ((i - TP(N_STATIC)) & (ID_BARS - 1));
                    if (rank == 0) {
                        if (!drawn) {
                            if (late) mbar_wait_w(bars + BAR_EMPTY + 8 * s, (eph >> s) & 1);
                            if (lane == 0) next = atomicInc(&g_tile_counter, wrap);
                        }
                        id = first_dynamic + next;
                        if (lane == 0) st_async_peer(slot, id, b);
                    } else {
                        mbar_expect_tx_1(b, 4);
                        mbar_wait_w(b, ((i - TP(N_STATIC)) / ID_BARS) & 1);
                        id = lds32(slot);
                    }
                    id = uniform(id);
                }
                drawn = rank == 0 && i + 1 >= TP(N_STATIC) && id + TP(AHEAD_TO) < num_tiles;
                if (drawn && lane == 0) next = atomicInc(&g_tile_counter, wrap);
                sts32(slot, id);
                sts32(bars + FRONT_AT, id);
                TR(7, i);
                mbar_wait_w(bars + BAR_EMPTY + 8 * s, (eph >> s) & 1);
                eph ^= 1u << s;
                const uint32_t full = bars + BAR_FULL + 8 * s;
                if (id >= num_tiles) {
                    sts32(bars + ISSUED_AT, id);
                    mbar_arrive_1(full);
#pragma unroll 1
                    for (uint32_t u = 0; u < STAGES; u++)
                        if (u != s) mbar_wait_w(bars + BAR_EMPTY + 8 * u, (eph >> u) & 1);
                    break;
                }
                sts32(bars + ISSUED_AT, id);
                TR(0, i);
                TRV(15, i, id);
                mbar_expect_tx_1(full, STAGE_BYTES);
                tma_load_x_1(smem + s * STAGE_BYTES + rank * HALF_BYTES, &maps.x, full, id * 8 + rank * 4,
                             id + TP(EF_TAIL) >= num_tiles ? EVICT_FIRST : EVICT_NORMAL);
            }
        } else if (warp == NUM_WG * 4 + 1) {
#pragma unroll
            for (int s = 0; s < STAGES; s++) {
                mbar_init_1(bars + BAR_FULL + 8 * s, 1);
                mbar_init_1(bars + BAR_EMPTY + 8 * s, NUM_WG * 4 * 2);
            }
#pragma unroll
            for (int s = 0; s < ID_BARS; s++) mbar_init_1(bars + BAR_ID + 8 * s, 1);
            publish_barriers();
            cluster_arrive();
            TR(0, 61);
            cluster_wait();
            prefetch_map_1(&maps.out);
        } else if (warp == NUM_WG * 4 + 2) {
#pragma unroll
            for (int b = 0; b < 3; b++) {
#pragma unroll
                for (int w = 0; w < NUM_WG; w++) {
                    mbar_init_1(bars + BAR_OFREE + b * 32 + w * 8, 1);
                    mbar_init_1(bars + BAR_OFULL + b * 32 + w * 8, 4);
                }
            }
            publish_barriers();
            cluster_arrive();
            cluster_wait();
            const uint32_t lag_at = TP(LAG_AT) + cluster % TP(LAG_SPREAD);
            uint32_t ob = 0, phase = 0, open = 0;
#pragma unroll 1
            for (uint32_t j = 0;; j++) {
                const uint32_t parity = (phase >> ob) & 1;
                const uint32_t obar = bars + ob * 32;
                if (!mbar_test_w(obar + BAR_OFULL, parity)) {
                    hand_back<0>(open);
                    mbar_wait_w(obar + BAR_OFULL, parity);
                }
                const uint32_t id = uniform(lds32(bars + ID_AT + 4 * (j & (ID_SLOTS - 1))));
                if (id >= num_tiles) break;
                const uint32_t src = smem + SMEM_OUT + ob * HALF_BYTES;
                uint32_t lag = (j >= lag_at) + (j >= lag_at + TP(LAG_GAP));
                bool whole = mbar_test_w(obar + BAR_OFULL + 8, parity) && mbar_test_w(obar + BAR_OFULL + 16, parity);
#pragma unroll 1
                for (uint32_t spins = 0; lag != 0 && spins < SPIN_LIMIT; spins++) {
                    const uint32_t front = uniform(lds32(bars + FRONT_AT));
                    if (front + TP(LAG_T2) >= num_tiles) break;
                    if (front + TP(LAG_T1) >= num_tiles) lag = 1;
                    uint32_t b = ob + lag;
                    if (b >= 3) b -= 3;
                    const uint32_t gate = bars + BAR_OFULL + b * 32 + TP(LAG_WG) * 8;
                    if (open != 0) {
                        if (mbar_test_w(gate, (phase >> b) & 1)) break;
                        hand_back<0>(open);
                    }
                    if (mbar_try_w(gate, (phase >> b) & 1, 100)) break;
                }
                if (TP(WAIT_NS) != 0 && j >= TP(WAIT_AT)) {
                    const uint32_t t0 = timer_ns();
#pragma unroll 1
                    while (timer_ns() - t0 < TP(WAIT_NS) && uniform(lds32(bars + FRONT_AT)) + TP(WAIT_T) < num_tiles) hand_back<0>(open);
                }
                if (whole) {
                    TR(11, j);
#pragma unroll
                    for (int w = 0; w < NUM_WG; w++) tma_store_1(&maps.out, src + w * SLICE_BYTES, slice_channel(rank, w), id * TILE_PIX);
                    TR(12, j);
                    TR(13, j);
                    hand_back<3>(open);
                    stores_read_wait<2>();
                    mbar_arrive_1(obar + BAR_OFREE);
                    stores_read_wait<1>();
                    mbar_arrive_1(obar + BAR_OFREE + 8);
                    open = obar + BAR_OFREE + 16;
                } else {
#pragma unroll 1
                    for (uint32_t w = 0; w < NUM_WG; w++) {
                        if (!mbar_test_w(obar + BAR_OFULL + w * 8, parity)) {
                            hand_back<0>(open);
                            mbar_wait_w(obar + BAR_OFULL + w * 8, parity);
                        }
                        TR(11 + w, j);
                        tma_store_1(&maps.out, src + w * SLICE_BYTES, slice_channel(rank, w), id * TILE_PIX);
                        hand_back<1>(open);
                        open = obar + BAR_OFREE + w * 8;
                    }
                }
                phase ^= 1u << ob;
                ob = ob == STAGES - 1 ? 0 : ob + 1;
            }
            stores_read_wait<0>();
            TR(4, 62);
        } else {
            uint32_t due = timer_ns() + TP(PM_T0) + (blockIdx.x & 3) * TP(PM_STAG);
            sts32(bars + ISSUED_AT, 0);
            cluster_arrive();
            const uint32_t step = num_clusters / 2;
#pragma unroll 1
            for (uint32_t piece = PRE_X; piece < TP(PM_E4); piece++) {
                const uint32_t t = cluster + piece / 2 * num_clusters;
                if (t >= num_tiles) break;
                uint32_t now;
#pragma unroll 1
                for (uint32_t spins = 0; spins < 16384; spins++) {
                    const uint32_t issued = uniform(lds32(bars + ISSUED_AT));
                    now = timer_ns();
                    const int lead = max((int)TP(LEAD_B), (int)TP(LEAD_A) - (max((int)issued - (int)TP(LEAD_F), 0) * (int)TP(LEAD_S) >> 4));
                    if ((int32_t)(now - due) >= 0 && cluster + piece * step <= issued + lead) break;
                    __nanosleep(20);
                }
                if ((int32_t)(now - TP(PM_SLACK) - due) > 0) due = now - TP(PM_SLACK);
                due += piece < TP(PM_E1) ? TP(PM_DT1) : piece < TP(PM_E2) ? TP(PM_DT2) : piece < TP(PM_E3) ? TP(PM_DT3) : TP(PM_DT4);
                const uint8_t* p = x_raw + (size_t)t * STAGE_BYTES + rank * HALF_BYTES + (piece % 2) * 12288 + lane * 128;
#pragma unroll
                for (int k = 0; k < 3; k++) asm volatile("prefetch.global.L2 [%0];" ::"l"(p + k * 4096) : "memory");
                if (piece % 2 == 0) TR(14, piece / 2);
            }
            cluster_wait();
        }
    }
}

typedef CUresult (*EncodeTiledFn)(CUtensorMap*, CUtensorMapDataType, cuuint32_t, void*, const cuuint64_t*,
                                  const cuuint64_t*, const cuuint32_t*, const cuuint32_t*, CUtensorMapInterleave,
                                  CUtensorMapSwizzle, CUtensorMapL2promotion, CUtensorMapFloatOOBfill);

}

extern "C" void kernel_launch(void* const* d_in, const int* in_sizes, int n_in, void* d_out, int out_size) {
    (void)n_in;
    (void)out_size;
    void* x = d_in[0];
    void* w = d_in[1];
    const uint16_t* b = (const uint16_t*)d_in[2];
    const int M = in_sizes[0] / C;
    const int num_tiles = M / TILE_PIX;

    static EncodeTiledFn encode = nullptr;
    static int sms = 0;
    if (!encode) {
        void* fn = nullptr;
        cudaDriverEntryPointQueryResult q;
        cudaGetDriverEntryPoint("cuTensorMapEncodeTiled", &fn, cudaEnableDefault, &q);
        encode = (EncodeTiledFn)fn;
        cudaDeviceGetAttribute(&sms, cudaDevAttrMultiProcessorCount, 0);
        cudaFuncSetAttribute(conv1x1_kernel, cudaFuncAttributeMaxDynamicSharedMemorySize, SMEM_TOTAL);
    }

    Maps maps;
    const cuuint32_t ones[4] = {1, 1, 1, 1};
    auto make = [&](CUtensorMap* map, int rank, void* base, const cuuint64_t* dims, const cuuint64_t* strides,
                    const cuuint32_t* box, CUtensorMapL2promotion promo) {
        encode(map, CU_TENSOR_MAP_DATA_TYPE_BFLOAT16, rank, base, dims, strides, box, ones, CU_TENSOR_MAP_INTERLEAVE_NONE,
               CU_TENSOR_MAP_SWIZZLE_128B, promo, CU_TENSOR_MAP_FLOAT_OOB_FILL_NONE);
    };
    {
        const cuuint64_t dims[4]    = {64, 8, 6, (cuuint64_t)(M / 8)};
        const cuuint64_t strides[3] = {C * 2, 128, 8 * C * 2};
        const cuuint32_t box[4]     = {64, 8, 6, TILE_PIX / 16};
        make(&maps.x, 4, x, dims, strides, box, CU_TENSOR_MAP_L2_PROMOTION_L2_128B);
    }
    {
        const cuuint64_t dims[3]    = {C, C / 2, 2};
        const cuuint64_t strides[2] = {C * 2, C * C};
        const cuuint32_t box[3]     = {64, C / 2, 2};
        make(&maps.w, 3, w, dims, strides, box, CU_TENSOR_MAP_L2_PROMOTION_L2_128B);
    }
    {
        const cuuint64_t dims[2]    = {C, (cuuint64_t)M};
        const cuuint64_t strides[1] = {C * 2};
        const cuuint32_t box[2]     = {64, TILE_PIX};
        make(&maps.out, 2, d_out, dims, strides, box, CU_TENSOR_MAP_L2_PROMOTION_NONE);
    }

    const Tune tune;
    int clusters = sms / 2;
    if (clusters > num_tiles / (int)TP(N_STATIC)) clusters = num_tiles / (int)TP(N_STATIC);
    conv1x1_kernel<<<clusters * 2, THREADS, SMEM_TOTAL>>>((const uint8_t*)x, (const uint8_t*)w, b, (uint32_t)num_tiles,
                                                          (uint32_t)clusters, maps, tune);
}
```

```cpp
#include <cuda_runtime.h>
#include <cuda_bf16.h>
#include <cuda.h>
#include <stdint.h>

#define EARLY_AT 18

#define W_FIRST 2
#define PRE_X 1
#define PRE_D0 200
#define PRE_DT 300
#define PRE_W 64

#define TUNABLES(F) \
    F(EARLY_TILES, 330)    \
    F(EARLY_HEAD, 1056)       \
    F(N_STATIC, 20)        \
    F(PM_T0, 0)            \
    F(PM_DT1, 435)         \
    F(PM_E1, 14) \
    F(PM_DT2, 300) \
    F(PM_E2, 20) \
    F(PM_DT3, 780) \
    F(PM_E3, 61) \
    F(PM_DT4, 650) \
    F(PM_E4, 72) \
    F(PM_STAG, 150)        \
    F(LEAD_A, 280)        \
    F(LEAD_F, 500)         \
    F(LEAD_S, 3)           \
    F(LEAD_B, 140)        \
    F(PM_SLACK, 150)    \
    F(AHEAD_TO, 1034)      \
    F(EF_TAIL, 380)        \
    F(ST_AT, 2)            \
    F(ST_STAG, 30)          \
    F(ST_P1, 2000)         \
    F(ST_E1, 10) \
    F(ST_P2, 1970) \
    F(ST_E2, 18) \
    F(ST_P3, 2000) \
    F(ST_SLACK, 100)       \
    F(ST_T1, 165)          \
    F(ST_PT, 1500)         \
    F(ST_T2, 50)           \
    F(HOLD_T, 100)         \
    F(DEEP_AT, 120)          \
    F(X0, 0) \
    F(X1, 0) \
    F(X2, 0) \
    F(X3, 0)

struct Tune {
#define F(n, v) static constexpr uint32_t n = v;
    TUNABLES(F)
#undef F
};
#define TP(n) (Tune::n)

#define TRV(slot, idx, v)
#define TR(slot, idx)
#define TRE(slot, idx)

namespace {

constexpr int C            = 384;
constexpr int TILE_PIX     = 64;
constexpr int STAGES       = 3;
constexpr int STAGE_BYTES  = TILE_PIX * C * 2;
constexpr int HALF_BYTES   = STAGE_BYTES / 2;
constexpr int SLICE_BYTES  = TILE_PIX * 128;
constexpr int W_LINES      = C * C * 2 / 128;
constexpr int NUM_WG       = 3;
constexpr int THREADS      = (NUM_WG + 1) * 128;
constexpr int SMEM_OUT     = STAGES * STAGE_BYTES;
constexpr int SMEM_BAR     = SMEM_OUT + STAGES * HALF_BYTES;
constexpr int SMEM_TOTAL   = SMEM_BAR + 512 + 1024;
constexpr int ID_SLOTS     = 16;
constexpr int ID_BARS      = 4;
constexpr uint32_t SPIN_LIMIT = 1u << 24;
constexpr int BAR_W     = 0;
constexpr int BAR_FULL  = 32;
constexpr int BAR_EMPTY = BAR_FULL + 32;
constexpr int BAR_ID    = BAR_EMPTY + 32;
constexpr int BAR_OFREE = BAR_ID + 8 * ID_BARS;
constexpr int BAR_OFULL = BAR_OFREE + 8 * 12;
constexpr int ID_AT     = BAR_OFULL + 8 * 12;
constexpr int FRONT_AT  = ID_AT + 4 * ID_SLOTS;
constexpr int ISSUED_AT = FRONT_AT + 4;
constexpr uint64_t EVICT_NORMAL = 0x1000000000000000ull;
constexpr uint64_t EVICT_FIRST  = 0x12F0000000000000ull;

struct Maps {
    CUtensorMap w, x, out;
};

__device__ unsigned int g_tile_counter;

#define ELECT "{\n.reg .pred e;\nelect.sync _|e, 0xffffffff;\n@e "

__device__ __forceinline__ uint32_t smem_u32(const void* p) {
    return (uint32_t)__cvta_generic_to_shared(p);
}
__device__ __forceinline__ void mbar_init_1(uint32_t bar, uint32_t count) {
    asm volatile(ELECT "mbarrier.init.shared::cta.b64 [%0], %1;\n}" ::"r"(bar), "r"(count) : "memory");
}
__device__ __forceinline__ void mbar_expect_tx_1(uint32_t bar, uint32_t bytes) {
    asm volatile(ELECT "mbarrier.arrive.expect_tx.shared::cta.b64 _, [%0], %1;\n}" ::"r"(bar), "r"(bytes) : "memory");
}
__device__ __forceinline__ void mbar_arrive_1(uint32_t bar) {
    asm volatile(ELECT "mbarrier.arrive.shared::cta.b64 _, [%0];\n}" ::"r"(bar) : "memory");
}
__device__ __forceinline__ void mbar_wait(uint32_t bar, uint32_t parity) {
    uint32_t done;
    uint32_t spins = 0;
    do {
        asm volatile(
            "{\n.reg .pred p;\n"
            "mbarrier.try_wait.parity.shared::cta.b64 p, [%1], %2;\n"
            "selp.u32 %0, 1, 0, p;\n}"
            : "=r"(done) : "r"(bar), "r"(parity) : "memory");
    } while (!done && ++spins < SPIN_LIMIT);
}
__device__ __forceinline__ void mbar_wait_w(uint32_t bar, uint32_t parity) {
    mbar_wait(bar, parity);
    __syncwarp();
}
__device__ __forceinline__ bool mbar_test_w(uint32_t bar, uint32_t parity) {
    uint32_t done;
    asm volatile(
        "{\n.reg .pred p;\n"
        "mbarrier.test_wait.parity.shared::cta.b64 p, [%1], %2;\n"
        "selp.u32 %0, 1, 0, p;\n}"
        : "=r"(done) : "r"(bar), "r"(parity) : "memory");
    return __all_sync(0xffffffffu, done);
}
__device__ __forceinline__ bool mbar_try_w(uint32_t bar, uint32_t parity, uint32_t ns) {
    uint32_t done;
    asm volatile(
        "{\n.reg .pred p;\n"
        "mbarrier.try_wait.parity.shared::cta.b64 p, [%1], %2, %3;\n"
        "selp.u32 %0, 1, 0, p;\n}"
        : "=r"(done) : "r"(bar), "r"(parity), "r"(ns) : "memory");
    return __all_sync(0xffffffffu, done);
}
__device__ __forceinline__ void mbar_arrive_cta(uint32_t bar, uint32_t cta) {
    asm volatile(
        "{\n.reg .b32 ra;\n"
        "mapa.shared::cluster.u32 ra, %0, %1;\n"
        "mbarrier.arrive.shared::cluster.b64 _, [ra];\n}"
        ::"r"(bar), "r"(cta) : "memory");
}
__device__ __forceinline__ void st_async_peer(uint32_t addr, uint32_t val, uint32_t bar) {
    asm volatile(
        "{\n.reg .b32 ra, rb;\n"
        "mapa.shared::cluster.u32 ra, %0, 1;\n"
        "mapa.shared::cluster.u32 rb, %2, 1;\n"
        "st.async.weak.shared::cluster.mbarrier::complete_tx::bytes.b32 [ra], %1, [rb];\n}"
        ::"r"(addr), "r"(val), "r"(bar) : "memory");
}
__device__ __forceinline__ uint32_t lds32(uint32_t addr) {
    uint32_t v;
    asm volatile("ld.shared.b32 %0, [%1];" : "=r"(v) : "r"(addr) : "memory");
    return v;
}
__device__ __forceinline__ uint32_t uniform(uint32_t v) {
    return __shfl_sync(0xffffffffu, v, 0);
}
__device__ __forceinline__ void sts32(uint32_t addr, uint32_t v) {
    asm volatile("st.shared.b32 [%0], %1;" ::"r"(addr), "r"(v) : "memory");
}
__device__ __forceinline__ void tma_load_w_1(uint32_t dst, const CUtensorMap* map, uint32_t bar, int n) {
    asm volatile(
        ELECT "cp.async.bulk.tensor.3d.shared::cluster.global.mbarrier::complete_tx::bytes [%0], [%1, {%3, %4, %4}], [%2];\n}"
        ::"r"(dst), "l"(map), "r"(bar), "r"(n), "r"(0) : "memory");
}
__device__ __forceinline__ void tma_load_x_1(uint32_t dst, const CUtensorMap* map, uint32_t bar, int group, uint64_t policy) {
    asm volatile(
        ELECT "cp.async.bulk.tensor.4d.shared::cluster.global.mbarrier::complete_tx::bytes.multicast::cluster.L2::cache_hint"
        " [%0], [%1, {%3, %3, %3, %4}], [%2], %5, %6;\n}"
        ::"r"(dst), "l"(map), "r"(bar), "r"(0), "r"(group), "h"((uint16_t)3), "l"(policy) : "memory");
}
__device__ __forceinline__ void tma_store_1(const CUtensorMap* map, uint32_t src, int ch, int pix) {
    asm volatile(
        ELECT "cp.async.bulk.tensor.2d.global.shared::cta.bulk_group [%0, {%2, %3}], [%1];\n}\n"
        "cp.async.bulk.commit_group;"
        ::"l"(map), "r"(src), "r"(ch), "r"(pix) : "memory");
}
template <int N>
__device__ __forceinline__ void stores_read_wait() {
    asm volatile("cp.async.bulk.wait_group.read %0;" ::"n"(N) : "memory");
}
__device__ __forceinline__ void prefetch_map_1(const CUtensorMap* map) {
    asm volatile(ELECT "prefetch.tensormap [%0];\n}" ::"l"(map) : "memory");
}
__device__ __forceinline__ uint32_t timer_ns() {
    uint32_t t;
    asm volatile("mov.u32 %0, %%globaltimer_lo;" : "=r"(t)::"memory");
    return t;
}
__device__ __forceinline__ void cluster_arrive() {
    asm volatile("barrier.cluster.arrive.relaxed.aligned;" ::: "memory");
}
__device__ __forceinline__ void cluster_wait() {
    asm volatile("barrier.cluster.wait.aligned;" ::: "memory");
}
__device__ __forceinline__ void publish_barriers() {
    asm volatile("fence.mbarrier_init.release.cluster;" ::: "memory");
    asm volatile("fence.proxy.async.shared::cta;" ::: "memory");
}

__device__ __forceinline__ void wgmma_rs_n64(float (&d)[32], const uint32_t* a, uint64_t desc, int scale_d) {
    asm volatile(
        "{\n.reg .pred p;\n"
        "setp.ne.b32 p, %37, 0;\n"
        "wgmma.mma_async.sync.aligned.m64n64k16.f32.bf16.bf16 "
        "{%0, %1, %2, %3, %4, %5, %6, %7, %8, %9, %10, %11, %12, %13, %14, %15, "
        "%16, %17, %18, %19, %20, %21, %22, %23, %24, %25, %26, %27, %28, %29, %30, %31}, "
        "{%32, %33, %34, %35}, %36, p, 1, 1, 0;\n}"
        : "+f"(d[0]), "+f"(d[1]), "+f"(d[2]), "+f"(d[3]), "+f"(d[4]), "+f"(d[5]), "+f"(d[6]), "+f"(d[7]),
          "+f"(d[8]), "+f"(d[9]), "+f"(d[10]), "+f"(d[11]), "+f"(d[12]), "+f"(d[13]), "+f"(d[14]), "+f"(d[15]),
          "+f"(d[16]), "+f"(d[17]), "+f"(d[18]), "+f"(d[19]), "+f"(d[20]), "+f"(d[21]), "+f"(d[22]), "+f"(d[23]),
          "+f"(d[24]), "+f"(d[25]), "+f"(d[26]), "+f"(d[27]), "+f"(d[28]), "+f"(d[29]), "+f"(d[30]), "+f"(d[31])
        : "r"(a[0]), "r"(a[1]), "r"(a[2]), "r"(a[3]), "l"(desc), "r"(scale_d));
}

__device__ __forceinline__ uint32_t pack_bias(float lo, float hi, uint32_t bias2) {
    uint32_t r;
    asm("{\n.reg .b32 t;\n"
        "cvt.rn.bf16x2.f32 t, %2, %1;\n"
        "add.rn.bf16x2 %0, t, %3;\n}"
        : "=r"(r) : "f"(lo), "f"(hi), "r"(bias2));
    return r;
}

__device__ __forceinline__ int slice_channel(uint32_t rank, int wg) {
    return (wg * 2 + rank) * 64;
}

struct Consumer {
    uint32_t wreg[96];
    uint32_t bias_lo, bias_hi, st_addr, bars;
    uint64_t desc_base;
    int wg, lane;
};
struct Ring {
    uint32_t s, parity;
    __device__ __forceinline__ void advance() {
        if (++s == STAGES) {
            s = 0;
            parity ^= 1;
        }
    }
};
__device__ __forceinline__ uint32_t w_stage(int wg) {
    return (wg + 1) * STAGE_BYTES + (wg == 2 ? HALF_BYTES : 0);
}

__device__ __forceinline__ void multiply(const Consumer& c, const Ring& r, float (&acc)[32], uint32_t i, bool early) {
    const int next_turn = 4 + (c.wg + 1) % NUM_WG;
    if ((i | c.wg) != 0) asm volatile("bar.sync %0, 256;" ::"r"(4 + c.wg) : "memory");
    TRE(1 + c.wg * 2, i);
    const uint64_t desc = c.desc_base + (uint64_t)(r.s * (STAGE_BYTES >> 4));
    asm volatile("wgmma.fence.sync.aligned;" ::: "memory");
#pragma unroll
    for (int ks = 0; ks < 24; ks++) {
        const uint64_t d = desc + (uint64_t)((ks >> 2) * 64 + (ks & 3) * 2);
        wgmma_rs_n64(acc, &c.wreg[ks * 4], d, ks != 0);
        if (ks + 1 == EARLY_AT && early) asm volatile("bar.arrive %0, 256;" ::"r"(next_turn) : "memory");
    }
    asm volatile("wgmma.commit_group.sync.aligned;" ::: "memory");
    asm volatile("wgmma.wait_group.sync.aligned 0;" ::: "memory");
#pragma unroll
    for (int j = 0; j < 32; j++) asm volatile("" : "+f"(acc[j])::"memory");
    if (!early) asm volatile("bar.arrive %0, 256;" ::"r"(next_turn) : "memory");
    TRE(2 + c.wg * 2, i);
    if (c.lane < 2) mbar_arrive_cta(c.bars + BAR_EMPTY + 8 * r.s, c.lane);
}
__device__ __forceinline__ void write_out(const Consumer& c, const Ring& r, const uint32_t (&v)[16]) {
    const uint32_t obar = c.bars + (r.s * 4 + c.wg) * 8;
    mbar_wait_w(obar + BAR_OFREE, r.parity ^ 1);
    const uint32_t dst = c.st_addr + r.s * HALF_BYTES;
#pragma unroll
    for (int j = 0; j < 4; j++) {
        asm volatile("stmatrix.sync.aligned.m8n8.x4.trans.shared.b16 [%0], {%1, %2, %3, %4};"
                     ::"r"(dst + j * 2048), "r"(v[4 * j]), "r"(v[4 * j + 1]), "r"(v[4 * j + 2]), "r"(v[4 * j + 3]) : "memory");
    }
    asm volatile("fence.proxy.async.shared::cta;" ::: "memory");
    __syncwarp();
    mbar_arrive_1(obar + BAR_OFULL);
}

template <int N>
__device__ __forceinline__ void hand_back(uint32_t& open) {
    if (open != 0) {
        stores_read_wait<N>();
        mbar_arrive_1(open);
        open = 0;
    }
}

__global__ void __cluster_dims__(2, 1, 1) __launch_bounds__(THREADS, 1)
conv1x1_kernel(const uint8_t* __restrict__ x_raw,
               const uint8_t* __restrict__ w_raw,
               const uint16_t* __restrict__ bias,
               uint32_t num_tiles,
               uint32_t num_clusters,
               const __grid_constant__ Maps maps,
               const __grid_constant__ Tune tune) {
    if (threadIdx.x < 96) {
        const uint32_t line = blockIdx.x % (W_LINES / PRE_W) * PRE_W + threadIdx.x;
        if (threadIdx.x < PRE_W) asm volatile("prefetch.global.L2 [%0];" ::"l"(w_raw + line * 128) : "memory");
    } else if (threadIdx.x < 128) {
        prefetch_map_1(&maps.w);
        prefetch_map_1(&maps.x);
    }
    if (threadIdx.x < NUM_WG * 128) cluster_arrive();
    if (threadIdx.x >= 128 && threadIdx.x < 128 + PRE_X * 96) {
        const uint8_t* p = x_raw + (size_t)blockIdx.x * HALF_BYTES + (threadIdx.x - 128) * 128;
        if (PRE_D0 + PRE_DT != 0) {
            const uint32_t wait = PRE_D0 + ((threadIdx.x - 128) >> 5) * PRE_DT;
            const uint32_t c0 = clock();
            while (clock() - c0 < wait) {}
        }
        asm volatile("prefetch.global.L2 [%0];" ::"l"(p) : "memory");
    }
    extern __shared__ uint8_t smem_raw[];
    const uint32_t smem = (smem_u32(smem_raw) + 1023u) & ~1023u;
    const uint32_t bars = smem + SMEM_BAR;

    const int warp = uniform(threadIdx.x >> 5);
    const int lane = threadIdx.x & 31;
    const uint32_t rank         = blockIdx.x & 1;
    const uint32_t cluster      = blockIdx.x >> 1;

    if (warp < NUM_WG * 4) {
        const int wg = warp >> 2;
        const int wq = warp & 3;
        asm volatile("setmaxnreg.inc.sync.aligned.u32 160;");
        Consumer c;
        c.wg = wg;
        c.lane = lane;
        c.bars = bars;
        c.bias_lo = bias[slice_channel(rank, wg) + wq * 16 + (lane >> 2)] * 0x10001u;
        c.bias_hi = bias[slice_channel(rank, wg) + wq * 16 + (lane >> 2) + 8] * 0x10001u;

        cluster_wait();
        TRE(1 + wg, 63);
        mbar_wait_w(bars + BAR_W + 8 * wg, 0);
        TRE(4 + wg, 63);
        {
            const int r = lane & 7, m = lane >> 3;
            const uint32_t base = smem + w_stage(wg) + ((m >> 1) * 8 + r) * 128 + (((2 * wq + (m & 1)) ^ r) << 4);
#pragma unroll
            for (int ks = 0; ks < 24; ks++) {
                asm volatile("ldmatrix.sync.aligned.m8n8.x4.trans.shared.b16 {%0, %1, %2, %3}, [%4];"
                             : "=r"(c.wreg[ks * 4 + 0]), "=r"(c.wreg[ks * 4 + 1]), "=r"(c.wreg[ks * 4 + 2]), "=r"(c.wreg[ks * 4 + 3])
                             : "r"(base + ks * 2048) : "memory");
            }
        }
        uint32_t dep = 0;
#pragma unroll
        for (int ks = 0; ks < 24; ks++) dep ^= c.wreg[ks * 4];
        dep &= num_tiles >> 31;
        __syncwarp();
        if (lane < 6 && wg < 2) mbar_arrive_cta(bars + BAR_EMPTY + 8 * (wg + 1) + dep, lane & 1);
        TRE(1 + wg, 60);

        c.st_addr = smem + SMEM_OUT + wg * SLICE_BYTES + ((lane >> 4) * 8 + (lane & 7)) * 128 + (((2 * wq + ((lane >> 3) & 1)) ^ (lane & 7)) << 4);
        c.desc_base = (uint64_t)((smem & 0x3FFFF) >> 4) | ((uint64_t)1 << 16) | ((uint64_t)(6144 >> 4) << 32) | ((uint64_t)1 << 62);

        float acc[32];
        uint32_t packed[16];
        Ring r = {0, dep}, o = r;
        bool held = false;
        for (uint32_t i = 0;; i++, r.advance()) {
            mbar_wait(bars + BAR_FULL + 8 * r.s, r.parity);
            const uint32_t id = lds32(bars + ID_AT + 4 * (i & (ID_SLOTS - 1)));
            if (id >= num_tiles) break;
            multiply(c, r, acc, i, id + TP(EARLY_TILES) >= num_tiles || id + 1 <= TP(EARLY_HEAD));
            if (held) write_out(c, o, packed);
#pragma unroll
            for (int j = 0; j < 16; j++) packed[j] = pack_bias(acc[2 * j], acc[2 * j + 1], j & 1 ? c.bias_hi : c.bias_lo);
            o = r;
            held = id + TP(HOLD_T) < num_tiles && !mbar_test_w(bars + BAR_OFREE + (r.s * 4 + wg) * 8, r.parity ^ 1);
            if (!held) write_out(c, o, packed);
            TRE(8 + wg, i);
        }
        if (held) write_out(c, o, packed);
        if (wg == 0) {
            mbar_wait_w(bars + BAR_OFREE + r.s * 32, r.parity ^ 1);
            mbar_arrive_1(bars + BAR_OFULL + r.s * 32);
            asm volatile("bar.sync 4, 256;" ::: "memory");
        }
        TRE(1 + wg, 62);
    } else {
        asm volatile("setmaxnreg.dec.sync.aligned.u32 32;");
        if (warp == NUM_WG * 4) {
#pragma unroll
            for (int j = 0; j < NUM_WG; j++) mbar_init_1(bars + BAR_W + 8 * j, 1);
            publish_barriers();
            cluster_arrive();
            sts32(bars + ID_AT, cluster);
#pragma unroll
            for (int j = 0; j < NUM_WG; j++) {
                if (j == W_FIRST) {
                    cluster_wait();
                    TR(0, 0);
                    mbar_expect_tx_1(bars + BAR_FULL, STAGE_BYTES);
                    tma_load_x_1(smem + rank * HALF_BYTES, &maps.x, bars + BAR_FULL, cluster * 8 + rank * 4, EVICT_NORMAL);
                }
                mbar_expect_tx_1(bars + BAR_W + 8 * j, STAGE_BYTES);
                tma_load_w_1(smem + w_stage(j), &maps.w, bars + BAR_W + 8 * j, slice_channel(rank, j));
                if (j == 0) TR(2, 61);
            }
            const uint32_t first_dynamic = TP(N_STATIC) * num_clusters;
            const uint32_t wrap = num_tiles - first_dynamic + num_clusters - 1;
            uint32_t s = 0, eph = 0, next = 0, id = 0;
            bool drawn = false;
#pragma unroll 1
            for (uint32_t i = 1;; i++) {
                s = s == STAGES - 1 ? 0 : s + 1;
                const uint32_t slot = bars + ID_AT + 4 * (i & (ID_SLOTS - 1));
                const bool late = id + TP(DEEP_AT) >= num_tiles;
                id = cluster + i * num_clusters;
                if (i >= TP(N_STATIC)) {
                    const uint32_t b = bars + BAR_ID + 8 * ((i - TP(N_STATIC)) & (ID_BARS - 1));
                    if (rank == 0) {
                        if (!drawn) {
                            if (late) mbar_wait_w(bars + BAR_EMPTY + 8 * s, (eph >> s) & 1);
                            if (lane == 0) next = atomicInc(&g_tile_counter, wrap);
                        }
                        id = first_dynamic + next;
                        if (lane == 0) st_async_peer(slot, id, b);
                    } else {
                        mbar_expect_tx_1(b, 4);
                        mbar_wait_w(b, ((i - TP(N_STATIC)) / ID_BARS) & 1);
                        id = lds32(slot);
                    }
                    id = uniform(id);
                }
                drawn = rank == 0 && i + 1 >= TP(N_STATIC) && id + TP(AHEAD_TO) < num_tiles;
                if (drawn && lane == 0) next = atomicInc(&g_tile_counter, wrap);
                sts32(slot, id);
                sts32(bars + FRONT_AT, id);
                TR(7, i);
                mbar_wait_w(bars + BAR_EMPTY + 8 * s, (eph >> s) & 1);
                eph ^= 1u << s;
                const uint32_t full = bars + BAR_FULL + 8 * s;
                if (id >= num_tiles) {
                    sts32(bars + ISSUED_AT, id);
                    mbar_arrive_1(full);
#pragma unroll 1
                    for (uint32_t u = 0; u < STAGES; u++)
                        if (u != s) mbar_wait_w(bars + BAR_EMPTY + 8 * u, (eph >> u) & 1);
                    break;
                }
                sts32(bars + ISSUED_AT, id);
                TR(0, i);
                TRV(15, i, id);
                mbar_expect_tx_1(full, STAGE_BYTES);
                tma_load_x_1(smem + s * STAGE_BYTES + rank * HALF_BYTES, &maps.x, full, id * 8 + rank * 4,
                             id + TP(EF_TAIL) >= num_tiles ? EVICT_FIRST : EVICT_NORMAL);
            }
        } else if (warp == NUM_WG * 4 + 1) {
#pragma unroll
            for (int s = 0; s < STAGES; s++) {
                mbar_init_1(bars + BAR_FULL + 8 * s, 1);
                mbar_init_1(bars + BAR_EMPTY + 8 * s, NUM_WG * 4 * 2);
            }
#pragma unroll
            for (int s = 0; s < ID_BARS; s++) mbar_init_1(bars + BAR_ID + 8 * s, 1);
            publish_barriers();
            cluster_arrive();
            TR(0, 61);
            cluster_wait();
            prefetch_map_1(&maps.out);
        } else if (warp == NUM_WG * 4 + 2) {
#pragma unroll
            for (int b = 0; b < 3; b++) {
#pragma unroll
                for (int w = 0; w < NUM_WG; w++) {
                    mbar_init_1(bars + BAR_OFREE + b * 32 + w * 8, 1);
                    mbar_init_1(bars + BAR_OFULL + b * 32 + w * 8, 4);
                }
            }
            publish_barriers();
            cluster_arrive();
            cluster_wait();
            uint32_t ob = 0, phase = 0, open = 0, due = 0;
#pragma unroll 1
            for (uint32_t j = 0;; j++) {
                const uint32_t parity = (phase >> ob) & 1;
                const uint32_t obar = bars + ob * 32;
                if (!mbar_test_w(obar + BAR_OFULL, parity)) {
                    hand_back<0>(open);
                    mbar_wait_w(obar + BAR_OFULL, parity);
                }
                const uint32_t id = uniform(lds32(bars + ID_AT + 4 * (j & (ID_SLOTS - 1))));
                if (id >= num_tiles) break;
                const uint32_t src = smem + SMEM_OUT + ob * HALF_BYTES;
                const uint32_t period = j <= TP(ST_E1) ? TP(ST_P1) : j <= TP(ST_E2) ? TP(ST_P2) : TP(ST_P3);
                uint32_t now = timer_ns();
                if (j >= TP(ST_AT)) {
                    if (j == TP(ST_AT)) due += cluster * TP(ST_STAG);
#pragma unroll 1
                    for (uint32_t spins = 0; spins < SPIN_LIMIT; spins++) {
                        const uint32_t front = uniform(lds32(bars + FRONT_AT));
                        const uint32_t gap = front + TP(ST_T2) >= num_tiles ? 0 : front + TP(ST_T1) >= num_tiles ? TP(ST_PT) : period;
                        if ((int32_t)(now - due - gap) >= 0) {
                            due += gap;
                            break;
                        }
                        hand_back<0>(open);
                        now = timer_ns();
                    }
                }
                if (j < TP(ST_AT) || (int32_t)(now - TP(ST_SLACK) - due) > 0) due = now - TP(ST_SLACK);
                const bool whole = mbar_test_w(obar + BAR_OFULL + 8, parity) && mbar_test_w(obar + BAR_OFULL + 16, parity);
                if (whole) {
                    TR(11, j);
#pragma unroll
                    for (int w = 0; w < NUM_WG; w++) tma_store_1(&maps.out, src + w * SLICE_BYTES, slice_channel(rank, w), id * TILE_PIX);
                    TR(12, j);
                    TR(13, j);
                    hand_back<3>(open);
                    stores_read_wait<2>();
                    mbar_arrive_1(obar + BAR_OFREE);
                    stores_read_wait<1>();
                    mbar_arrive_1(obar + BAR_OFREE + 8);
                    open = obar + BAR_OFREE + 16;
                } else {
#pragma unroll 1
                    for (uint32_t w = 0; w < NUM_WG; w++) {
                        if (!mbar_test_w(obar + BAR_OFULL + w * 8, parity)) {
                            hand_back<0>(open);
                            mbar_wait_w(obar + BAR_OFULL + w * 8, parity);
                        }
                        TR(11 + w, j);
                        tma_store_1(&maps.out, src + w * SLICE_BYTES, slice_channel(rank, w), id * TILE_PIX);
                        hand_back<1>(open);
                        open = obar + BAR_OFREE + w * 8;
                    }
                }
                phase ^= 1u << ob;
                ob = ob == STAGES - 1 ? 0 : ob + 1;
            }
            stores_read_wait<0>();
            TR(4, 62);
        } else {
            uint32_t due = timer_ns() + TP(PM_T0) + (blockIdx.x & 3) * TP(PM_STAG);
            sts32(bars + ISSUED_AT, 0);
            cluster_arrive();
            const uint32_t step = num_clusters / 2;
#pragma unroll 1
            for (uint32_t piece = PRE_X; piece < TP(PM_E4); piece++) {
                const uint32_t t = cluster + piece / 2 * num_clusters;
                if (t >= num_tiles) break;
                uint32_t now;
#pragma unroll 1
                for (uint32_t spins = 0; spins < 16384; spins++) {
                    const uint32_t issued = uniform(lds32(bars + ISSUED_AT));
                    now = timer_ns();
                    const int lead = max((int)TP(LEAD_B), (int)TP(LEAD_A) - (max((int)issued - (int)TP(LEAD_F), 0) * (int)TP(LEAD_S) >> 4));
                    if ((int32_t)(now - due) >= 0 && cluster + piece * step <= issued + lead) break;
                    __nanosleep(20);
                }
                if ((int32_t)(now - TP(PM_SLACK) - due) > 0) due = now - TP(PM_SLACK);
                due += piece < TP(PM_E1) ? TP(PM_DT1) : piece < TP(PM_E2) ? TP(PM_DT2) : piece < TP(PM_E3) ? TP(PM_DT3) : TP(PM_DT4);
                const uint8_t* p = x_raw + (size_t)t * STAGE_BYTES + rank * HALF_BYTES + (piece % 2) * 12288 + lane * 128;
#pragma unroll
                for (int k = 0; k < 3; k++) asm volatile("prefetch.global.L2 [%0];" ::"l"(p + k * 4096) : "memory");
                if (piece % 2 == 0) TR(14, piece / 2);
            }
            cluster_wait();
        }
    }
}

typedef CUresult (*EncodeTiledFn)(CUtensorMap*, CUtensorMapDataType, cuuint32_t, void*, const cuuint64_t*,
                                  const cuuint64_t*, const cuuint32_t*, const cuuint32_t*, CUtensorMapInterleave,
                                  CUtensorMapSwizzle, CUtensorMapL2promotion, CUtensorMapFloatOOBfill);

}

extern "C" void kernel_launch(void* const* d_in, const int* in_sizes, int n_in, void* d_out, int out_size) {
    (void)n_in;
    (void)out_size;
    void* x = d_in[0];
    void* w = d_in[1];
    const uint16_t* b = (const uint16_t*)d_in[2];
    const int M = in_sizes[0] / C;
    const int num_tiles = M / TILE_PIX;

    static EncodeTiledFn encode = nullptr;
    static int sms = 0;
    if (!encode) {
        void* fn = nullptr;
        cudaDriverEntryPointQueryResult q;
        cudaGetDriverEntryPoint("cuTensorMapEncodeTiled", &fn, cudaEnableDefault, &q);
        encode = (EncodeTiledFn)fn;
        cudaDeviceGetAttribute(&sms, cudaDevAttrMultiProcessorCount, 0);
        cudaFuncSetAttribute(conv1x1_kernel, cudaFuncAttributeMaxDynamicSharedMemorySize, SMEM_TOTAL);
    }

    Maps maps;
    const cuuint32_t ones[4] = {1, 1, 1, 1};
    auto make = [&](CUtensorMap* map, int rank, void* base, const cuuint64_t* dims, const cuuint64_t* strides,
                    const cuuint32_t* box, CUtensorMapL2promotion promo) {
        encode(map, CU_TENSOR_MAP_DATA_TYPE_BFLOAT16, rank, base, dims, strides, box, ones, CU_TENSOR_MAP_INTERLEAVE_NONE,
               CU_TENSOR_MAP_SWIZZLE_128B, promo, CU_TENSOR_MAP_FLOAT_OOB_FILL_NONE);
    };
    {
        const cuuint64_t dims[4]    = {64, 8, 6, (cuuint64_t)(M / 8)};
        const cuuint64_t strides[3] = {C * 2, 128, 8 * C * 2};
        const cuuint32_t box[4]     = {64, 8, 6, TILE_PIX / 16};
        make(&maps.x, 4, x, dims, strides, box, CU_TENSOR_MAP_L2_PROMOTION_L2_128B);
    }
    {
        const cuuint64_t dims[3]    = {C, C / 2, 2};
        const cuuint64_t strides[2] = {C * 2, C * C};
        const cuuint32_t box[3]     = {64, C / 2, 2};
        make(&maps.w, 3, w, dims, strides, box, CU_TENSOR_MAP_L2_PROMOTION_L2_128B);
    }
    {
        const cuuint64_t dims[2]    = {C, (cuuint64_t)M};
        const cuuint64_t strides[1] = {C * 2};
        const cuuint32_t box[2]     = {64, TILE_PIX};
        make(&maps.out, 2, d_out, dims, strides, box, CU_TENSOR_MAP_L2_PROMOTION_NONE);
    }

    const Tune tune;
    int clusters = sms / 2;
    if (clusters > num_tiles / (int)TP(N_STATIC)) clusters = num_tiles / (int)TP(N_STATIC);
    conv1x1_kernel<<<clusters * 2, THREADS, SMEM_TOTAL>>>((const uint8_t*)x, (const uint8_t*)w, b, (uint32_t)num_tiles,
                                                          (uint32_t)clusters, maps, tune);
}
```

```cpp
#include <cuda_runtime.h>
#include <cuda_bf16.h>
#include <cuda.h>
#include <stdint.h>

#define EARLY_AT 18

#define W_FIRST 2
#define PRE_X 1
#define PRE_D0 200
#define PRE_DT 300
#define PRE_W 64

#define TUNABLES(F) \
    F(EARLY_TILES, 330)    \
    F(EARLY_HEAD, 1056)       \
    F(N_STATIC, 20)        \
    F(PM_T0, 0)            \
    F(PM_DT1, 435)         \
    F(PM_E1, 14) \
    F(PM_DT2, 300) \
    F(PM_E2, 20) \
    F(PM_DT3, 780) \
    F(PM_E3, 61) \
    F(PM_DT4, 650) \
    F(PM_E4, 72) \
    F(PM_STAG, 150)        \
    F(LEAD_A, 280)        \
    F(LEAD_F, 500)         \
    F(LEAD_S, 3)           \
    F(LEAD_B, 151)        \
    F(PM_SLACK, 150)    \
    F(AHEAD_TO, 1034)      \
    F(EF_TAIL, 380)        \
    F(ST_AT, 2)            \
    F(ST_STAG, 30)          \
    F(ST_P1, 2000)         \
    F(ST_E1, 10) \
    F(ST_P2, 2010) \
    F(ST_E2, 18) \
    F(ST_P3, 2020) \
    F(ST_SLACK, 300)       \
    F(ST_T1, 165)          \
    F(ST_PT, 1500)         \
    F(ST_T2, 50)           \
    F(ST_PU, 0)            \
    F(RING2_AT, 999)       \
    F(OUT5_AT, 999)        \
    F(HOLD_T, 100)         \
    F(DEEP_AT, 120)          \
    F(X0, 0) \
    F(X1, 0) \
    F(X2, 0) \
    F(X3, 0)

struct Tune {
#define F(n, v) static constexpr uint32_t n = v;
    TUNABLES(F)
#undef F
};
#define TP(n) (Tune::n)

#define TRV(slot, idx, v)
#define TR(slot, idx)
#define TRE(slot, idx)

namespace {

constexpr int C            = 384;
constexpr int TILE_PIX     = 64;
constexpr int STAGES       = 3;
constexpr int STAGE_BYTES  = TILE_PIX * C * 2;
constexpr int HALF_BYTES   = STAGE_BYTES / 2;
constexpr int SLICE_BYTES  = TILE_PIX * 128;
constexpr int W_LINES      = C * C * 2 / 128;
constexpr int NUM_WG       = 3;
constexpr int THREADS      = (NUM_WG + 1) * 128;
constexpr int BUFFERS      = 5;
constexpr int SMEM_OUT     = 2 * STAGE_BYTES;
constexpr int SMEM_BAR     = SMEM_OUT + BUFFERS * HALF_BYTES;
constexpr int SMEM_TOTAL   = SMEM_BAR + 1024 + 1024;
constexpr int ID_SLOTS     = 16;
constexpr int ID_BARS      = 4;
constexpr uint32_t SPIN_LIMIT = 1u << 24;
constexpr int BAR_W     = 0;
constexpr int BAR_FULL  = 32;
constexpr int BAR_EMPTY = BAR_FULL + 32;
constexpr int BAR_ID    = BAR_EMPTY + 32;
constexpr int BAR_OFREE = BAR_ID + 8 * ID_BARS;
constexpr int BAR_OFULL = BAR_OFREE + 32 * BUFFERS;
constexpr int ID_AT     = BAR_OFULL + 32 * BUFFERS;
constexpr int FRONT_AT  = ID_AT + 4 * ID_SLOTS;
constexpr int ISSUED_AT = FRONT_AT + 4;
constexpr uint64_t EVICT_NORMAL = 0x1000000000000000ull;
constexpr uint64_t EVICT_FIRST  = 0x12F0000000000000ull;

struct Maps {
    CUtensorMap w, x, out;
};

__device__ unsigned int g_tile_counter;

#define ELECT "{\n.reg .pred e;\nelect.sync _|e, 0xffffffff;\n@e "

__device__ __forceinline__ uint32_t smem_u32(const void* p) {
    return (uint32_t)__cvta_generic_to_shared(p);
}
__device__ __forceinline__ void mbar_init_1(uint32_t bar, uint32_t count) {
    asm volatile(ELECT "mbarrier.init.shared::cta.b64 [%0], %1;\n}" ::"r"(bar), "r"(count) : "memory");
}
__device__ __forceinline__ void mbar_expect_tx_1(uint32_t bar, uint32_t bytes) {
    asm volatile(ELECT "mbarrier.arrive.expect_tx.shared::cta.b64 _, [%0], %1;\n}" ::"r"(bar), "r"(bytes) : "memory");
}
__device__ __forceinline__ void mbar_arrive_1(uint32_t bar) {
    asm volatile(ELECT "mbarrier.arrive.shared::cta.b64 _, [%0];\n}" ::"r"(bar) : "memory");
}
__device__ __forceinline__ void mbar_wait(uint32_t bar, uint32_t parity) {
    uint32_t done;
    uint32_t spins = 0;
    do {
        asm volatile(
            "{\n.reg .pred p;\n"
            "mbarrier.try_wait.parity.shared::cta.b64 p, [%1], %2;\n"
            "selp.u32 %0, 1, 0, p;\n}"
            : "=r"(done) : "r"(bar), "r"(parity) : "memory");
    } while (!done && ++spins < SPIN_LIMIT);
}
__device__ __forceinline__ void mbar_wait_w(uint32_t bar, uint32_t parity) {
    mbar_wait(bar, parity);
    __syncwarp();
}
__device__ __forceinline__ bool mbar_test_w(uint32_t bar, uint32_t parity) {
    uint32_t done;
    asm volatile(
        "{\n.reg .pred p;\n"
        "mbarrier.test_wait.parity.shared::cta.b64 p, [%1], %2;\n"
        "selp.u32 %0, 1, 0, p;\n}"
        : "=r"(done) : "r"(bar), "r"(parity) : "memory");
    return __all_sync(0xffffffffu, done);
}
__device__ __forceinline__ bool mbar_try_w(uint32_t bar, uint32_t parity, uint32_t ns) {
    uint32_t done;
    asm volatile(
        "{\n.reg .pred p;\n"
        "mbarrier.try_wait.parity.shared::cta.b64 p, [%1], %2, %3;\n"
        "selp.u32 %0, 1, 0, p;\n}"
        : "=r"(done) : "r"(bar), "r"(parity), "r"(ns) : "memory");
    return __all_sync(0xffffffffu, done);
}
__device__ __forceinline__ void mbar_arrive_cta(uint32_t bar, uint32_t cta) {
    asm volatile(
        "{\n.reg .b32 ra;\n"
        "mapa.shared::cluster.u32 ra, %0, %1;\n"
        "mbarrier.arrive.shared::cluster.b64 _, [ra];\n}"
        ::"r"(bar), "r"(cta) : "memory");
}
__device__ __forceinline__ void st_async_peer(uint32_t addr, uint32_t val, uint32_t bar) {
    asm volatile(
        "{\n.reg .b32 ra, rb;\n"
        "mapa.shared::cluster.u32 ra, %0, 1;\n"
        "mapa.shared::cluster.u32 rb, %2, 1;\n"
        "st.async.weak.shared::cluster.mbarrier::complete_tx::bytes.b32 [ra], %1, [rb];\n}"
        ::"r"(addr), "r"(val), "r"(bar) : "memory");
}
__device__ __forceinline__ uint32_t lds32(uint32_t addr) {
    uint32_t v;
    asm volatile("ld.shared.b32 %0, [%1];" : "=r"(v) : "r"(addr) : "memory");
    return v;
}
__device__ __forceinline__ uint32_t uniform(uint32_t v) {
    return __shfl_sync(0xffffffffu, v, 0);
}
__device__ __forceinline__ void sts32(uint32_t addr, uint32_t v) {
    asm volatile("st.shared.b32 [%0], %1;" ::"r"(addr), "r"(v) : "memory");
}
__device__ __forceinline__ void tma_load_w_1(uint32_t dst, const CUtensorMap* map, uint32_t bar, int n) {
    asm volatile(
        ELECT "cp.async.bulk.tensor.3d.shared::cluster.global.mbarrier::complete_tx::bytes [%0], [%1, {%3, %4, %4}], [%2];\n}"
        ::"r"(dst), "l"(map), "r"(bar), "r"(n), "r"(0) : "memory");
}
__device__ __forceinline__ void tma_load_x_1(uint32_t dst, const CUtensorMap* map, uint32_t bar, int group, uint64_t policy) {
    asm volatile(
        ELECT "cp.async.bulk.tensor.4d.shared::cluster.global.mbarrier::complete_tx::bytes.multicast::cluster.L2::cache_hint"
        " [%0], [%1, {%3, %3, %3, %4}], [%2], %5, %6;\n}"
        ::"r"(dst), "l"(map), "r"(bar), "r"(0), "r"(group), "h"((uint16_t)3), "l"(policy) : "memory");
}
__device__ __forceinline__ void tma_store_1(const CUtensorMap* map, uint32_t src, int ch, int pix) {
    asm volatile(
        ELECT "cp.async.bulk.tensor.2d.global.shared::cta.bulk_group [%0, {%2, %3}], [%1];\n}\n"
        "cp.async.bulk.commit_group;"
        ::"l"(map), "r"(src), "r"(ch), "r"(pix) : "memory");
}
template <int N>
__device__ __forceinline__ void stores_read_wait() {
    asm volatile("cp.async.bulk.wait_group.read %0;" ::"n"(N) : "memory");
}
__device__ __forceinline__ void prefetch_map_1(const CUtensorMap* map) {
    asm volatile(ELECT "prefetch.tensormap [%0];\n}" ::"l"(map) : "memory");
}
__device__ __forceinline__ uint32_t timer_ns() {
    uint32_t t;
    asm volatile("mov.u32 %0, %%globaltimer_lo;" : "=r"(t)::"memory");
    return t;
}
__device__ __forceinline__ void cluster_arrive() {
    asm volatile("barrier.cluster.arrive.relaxed.aligned;" ::: "memory");
}
__device__ __forceinline__ void cluster_wait() {
    asm volatile("barrier.cluster.wait.aligned;" ::: "memory");
}
__device__ __forceinline__ void publish_barriers() {
    asm volatile("fence.mbarrier_init.release.cluster;" ::: "memory");
    asm volatile("fence.proxy.async.shared::cta;" ::: "memory");
}

__device__ __forceinline__ void wgmma_rs_n64(float (&d)[32], const uint32_t* a, uint64_t desc, int scale_d) {
    asm volatile(
        "{\n.reg .pred p;\n"
        "setp.ne.b32 p, %37, 0;\n"
        "wgmma.mma_async.sync.aligned.m64n64k16.f32.bf16.bf16 "
        "{%0, %1, %2, %3, %4, %5, %6, %7, %8, %9, %10, %11, %12, %13, %14, %15, "
        "%16, %17, %18, %19, %20, %21, %22, %23, %24, %25, %26, %27, %28, %29, %30, %31}, "
        "{%32, %33, %34, %35}, %36, p, 1, 1, 0;\n}"
        : "+f"(d[0]), "+f"(d[1]), "+f"(d[2]), "+f"(d[3]), "+f"(d[4]), "+f"(d[5]), "+f"(d[6]), "+f"(d[7]),
          "+f"(d[8]), "+f"(d[9]), "+f"(d[10]), "+f"(d[11]), "+f"(d[12]), "+f"(d[13]), "+f"(d[14]), "+f"(d[15]),
          "+f"(d[16]), "+f"(d[17]), "+f"(d[18]), "+f"(d[19]), "+f"(d[20]), "+f"(d[21]), "+f"(d[22]), "+f"(d[23]),
          "+f"(d[24]), "+f"(d[25]), "+f"(d[26]), "+f"(d[27]), "+f"(d[28]), "+f"(d[29]), "+f"(d[30]), "+f"(d[31])
        : "r"(a[0]), "r"(a[1]), "r"(a[2]), "r"(a[3]), "l"(desc), "r"(scale_d));
}

__device__ __forceinline__ uint32_t pack_bias(float lo, float hi, uint32_t bias2) {
    uint32_t r;
    asm("{\n.reg .b32 t;\n"
        "cvt.rn.bf16x2.f32 t, %2, %1;\n"
        "add.rn.bf16x2 %0, t, %3;\n}"
        : "=r"(r) : "f"(lo), "f"(hi), "r"(bias2));
    return r;
}

__device__ __forceinline__ int slice_channel(uint32_t rank, int wg) {
    return (wg * 2 + rank) * 64;
}

struct Consumer {
    uint32_t wreg[96];
    uint32_t bias_lo, bias_hi, st_addr, bars;
    uint64_t desc_base;
    int wg, lane;
};
struct Ring {
    uint32_t s, phase;
    __device__ __forceinline__ uint32_t parity() const { return (phase >> s) & 1; }
    __device__ __forceinline__ void next_slot(const Tune& tune, uint32_t next_i) {
        phase ^= 1u << s;
        s = s == 2 || (s == 1 && next_i >= TP(RING2_AT)) ? 0 : s + 1;
    }
    __device__ __forceinline__ void next_buffer(const Tune& tune, uint32_t next_i) {
        phase ^= 1u << s;
        s = s != BUFFERS - 1 ? s + 1 : next_i >= TP(OUT5_AT) ? 0 : 2;
    }
};
__device__ __forceinline__ uint32_t w_stage(int wg) {
    return (wg + 1) * STAGE_BYTES + (wg == 2 ? HALF_BYTES : 0);
}

__device__ __forceinline__ void multiply(const Consumer& c, const Ring& r, float (&acc)[32], uint32_t i, bool early) {
    const int next_turn = 4 + (c.wg + 1) % NUM_WG;
    if ((i | c.wg) != 0) asm volatile("bar.sync %0, 256;" ::"r"(4 + c.wg) : "memory");
    TRE(1 + c.wg * 2, i);
    const uint64_t desc = c.desc_base + (uint64_t)(r.s * (STAGE_BYTES >> 4));
    asm volatile("wgmma.fence.sync.aligned;" ::: "memory");
#pragma unroll
    for (int ks = 0; ks < 24; ks++) {
        const uint64_t d = desc + (uint64_t)((ks >> 2) * 64 + (ks & 3) * 2);
        wgmma_rs_n64(acc, &c.wreg[ks * 4], d, ks != 0);
        if (ks + 1 == EARLY_AT && early) asm volatile("bar.arrive %0, 256;" ::"r"(next_turn) : "memory");
    }
    asm volatile("wgmma.commit_group.sync.aligned;" ::: "memory");
    asm volatile("wgmma.wait_group.sync.aligned 0;" ::: "memory");
#pragma unroll
    for (int j = 0; j < 32; j++) asm volatile("" : "+f"(acc[j])::"memory");
    if (!early) asm volatile("bar.arrive %0, 256;" ::"r"(next_turn) : "memory");
    TRE(2 + c.wg * 2, i);
    if (c.lane < 2) mbar_arrive_cta(c.bars + BAR_EMPTY + 8 * r.s, c.lane);
}
__device__ __forceinline__ void write_out(const Consumer& c, const Ring& r, const uint32_t (&v)[16]) {
    const uint32_t obar = c.bars + (r.s * 4 + c.wg) * 8;
    mbar_wait_w(obar + BAR_OFREE, r.parity() ^ 1);
    const uint32_t dst = c.st_addr + r.s * HALF_BYTES;
#pragma unroll
    for (int j = 0; j < 4; j++) {
        asm volatile("stmatrix.sync.aligned.m8n8.x4.trans.shared.b16 [%0], {%1, %2, %3, %4};"
                     ::"r"(dst + j * 2048), "r"(v[4 * j]), "r"(v[4 * j + 1]), "r"(v[4 * j + 2]), "r"(v[4 * j + 3]) : "memory");
    }
    asm volatile("fence.proxy.async.shared::cta;" ::: "memory");
    __syncwarp();
    mbar_arrive_1(obar + BAR_OFULL);
}

template <int N>
__device__ __forceinline__ void hand_back(uint32_t& open) {
    if (open != 0) {
        stores_read_wait<N>();
        mbar_arrive_1(open);
        open = 0;
    }
}

__global__ void __cluster_dims__(2, 1, 1) __launch_bounds__(THREADS, 1)
conv1x1_kernel(const uint8_t* __restrict__ x_raw,
               const uint8_t* __restrict__ w_raw,
               const uint16_t* __restrict__ bias,
               uint32_t num_tiles,
               uint32_t num_clusters,
               const __grid_constant__ Maps maps,
               const __grid_constant__ Tune tune) {
    if (threadIdx.x < 96) {
        const uint32_t line = blockIdx.x % (W_LINES / PRE_W) * PRE_W + threadIdx.x;
        if (threadIdx.x < PRE_W) asm volatile("prefetch.global.L2 [%0];" ::"l"(w_raw + line * 128) : "memory");
    } else if (threadIdx.x < 128) {
        prefetch_map_1(&maps.w);
        prefetch_map_1(&maps.x);
    }
    if (threadIdx.x < NUM_WG * 128) cluster_arrive();
    if (threadIdx.x >= 128 && threadIdx.x < 128 + PRE_X * 96) {
        const uint8_t* p = x_raw + (size_t)blockIdx.x * HALF_BYTES + (threadIdx.x - 128) * 128;
        if (PRE_D0 + PRE_DT != 0) {
            const uint32_t wait = PRE_D0 + ((threadIdx.x - 128) >> 5) * PRE_DT;
            const uint32_t c0 = clock();
            while (clock() - c0 < wait) {}
        }
        asm volatile("prefetch.global.L2 [%0];" ::"l"(p) : "memory");
    }
    extern __shared__ uint8_t smem_raw[];
    const uint32_t smem = (smem_u32(smem_raw) + 1023u) & ~1023u;
    const uint32_t bars = smem + SMEM_BAR;

    const int warp = uniform(threadIdx.x >> 5);
    const int lane = threadIdx.x & 31;
    const uint32_t rank         = blockIdx.x & 1;
    const uint32_t cluster      = blockIdx.x >> 1;

    if (warp < NUM_WG * 4) {
        const int wg = warp >> 2;
        const int wq = warp & 3;
        asm volatile("setmaxnreg.inc.sync.aligned.u32 160;");
        Consumer c;
        c.wg = wg;
        c.lane = lane;
        c.bars = bars;
        c.bias_lo = bias[slice_channel(rank, wg) + wq * 16 + (lane >> 2)] * 0x10001u;
        c.bias_hi = bias[slice_channel(rank, wg) + wq * 16 + (lane >> 2) + 8] * 0x10001u;

        cluster_wait();
        TRE(1 + wg, 63);
        mbar_wait_w(bars + BAR_W + 8 * wg, 0);
        TRE(4 + wg, 63);
        {
            const int r = lane & 7, m = lane >> 3;
            const uint32_t base = smem + w_stage(wg) + ((m >> 1) * 8 + r) * 128 + (((2 * wq + (m & 1)) ^ r) << 4);
#pragma unroll
            for (int ks = 0; ks < 24; ks++) {
                asm volatile("ldmatrix.sync.aligned.m8n8.x4.trans.shared.b16 {%0, %1, %2, %3}, [%4];"
                             : "=r"(c.wreg[ks * 4 + 0]), "=r"(c.wreg[ks * 4 + 1]), "=r"(c.wreg[ks * 4 + 2]), "=r"(c.wreg[ks * 4 + 3])
                             : "r"(base + ks * 2048) : "memory");
            }
        }
        uint32_t dep = 0;
#pragma unroll
        for (int ks = 0; ks < 24; ks++) dep ^= c.wreg[ks * 4];
        dep &= num_tiles >> 31;
        __syncwarp();
        if (lane < 6 && wg < 2) mbar_arrive_cta(bars + BAR_EMPTY + 8 * (wg + 1) + dep, lane & 1);
        TRE(1 + wg, 60);

        c.st_addr = smem + SMEM_OUT + wg * SLICE_BYTES + ((lane >> 4) * 8 + (lane & 7)) * 128 + (((2 * wq + ((lane >> 3) & 1)) ^ (lane & 7)) << 4);
        c.desc_base = (uint64_t)((smem & 0x3FFFF) >> 4) | ((uint64_t)1 << 16) | ((uint64_t)(6144 >> 4) << 32) | ((uint64_t)1 << 62);

        float acc[32];
        uint32_t packed[16];
        Ring r = {0, uniform(dep)}, o = {2, 0};
        bool held = false;
        uint32_t i = 0;
        for (;; r.next_slot(tune, ++i)) {
            mbar_wait(bars + BAR_FULL + 8 * r.s, r.parity());
            const uint32_t id = lds32(bars + ID_AT + 4 * (i & (ID_SLOTS - 1)));
            if (id >= num_tiles) break;
            multiply(c, r, acc, i, id + TP(EARLY_TILES) >= num_tiles || id + 1 <= TP(EARLY_HEAD));
            if (held) {
                write_out(c, o, packed);
                o.next_buffer(tune, i);
            }
#pragma unroll
            for (int j = 0; j < 16; j++) packed[j] = pack_bias(acc[2 * j], acc[2 * j + 1], j & 1 ? c.bias_hi : c.bias_lo);
            held = id + TP(HOLD_T) < num_tiles && !mbar_test_w(bars + BAR_OFREE + (o.s * 4 + wg) * 8, o.parity() ^ 1);
            if (!held) {
                write_out(c, o, packed);
                o.next_buffer(tune, i + 1);
            }
            TRE(8 + wg, i);
        }
        if (held) {
            write_out(c, o, packed);
            o.next_buffer(tune, i);
        }
        if (wg == 0) {
            mbar_wait_w(bars + BAR_OFREE + o.s * 32, o.parity() ^ 1);
            mbar_arrive_1(bars + BAR_OFULL + o.s * 32);
            asm volatile("bar.sync 4, 256;" ::: "memory");
        }
        TRE(1 + wg, 62);
    } else {
        asm volatile("setmaxnreg.dec.sync.aligned.u32 32;");
        if (warp == NUM_WG * 4) {
#pragma unroll
            for (int j = 0; j < NUM_WG; j++) mbar_init_1(bars + BAR_W + 8 * j, 1);
            publish_barriers();
            cluster_arrive();
            sts32(bars + ID_AT, cluster);
#pragma unroll
            for (int j = 0; j < NUM_WG; j++) {
                if (j == W_FIRST) {
                    cluster_wait();
                    TR(0, 0);
                    mbar_expect_tx_1(bars + BAR_FULL, STAGE_BYTES);
                    tma_load_x_1(smem + rank * HALF_BYTES, &maps.x, bars + BAR_FULL, cluster * 8 + rank * 4, EVICT_NORMAL);
                }
                mbar_expect_tx_1(bars + BAR_W + 8 * j, STAGE_BYTES);
                tma_load_w_1(smem + w_stage(j), &maps.w, bars + BAR_W + 8 * j, slice_channel(rank, j));
                if (j == 0) TR(2, 61);
            }
            const uint32_t first_dynamic = TP(N_STATIC) * num_clusters;
            const uint32_t wrap = num_tiles - first_dynamic + num_clusters - 1;
            uint32_t s = 0, eph = 0, next = 0, id = 0;
            bool drawn = false;
#pragma unroll 1
            for (uint32_t i = 1;; i++) {
                s = s == 2 || (s == 1 && i >= TP(RING2_AT)) ? 0 : s + 1;
                const uint32_t slot = bars + ID_AT + 4 * (i & (ID_SLOTS - 1));
                const bool late = id + TP(DEEP_AT) >= num_tiles;
                id = cluster + i * num_clusters;
                if (i >= TP(N_STATIC)) {
                    const uint32_t b = bars + BAR_ID + 8 * ((i - TP(N_STATIC)) & (ID_BARS - 1));
                    if (rank == 0) {
                        if (!drawn) {
                            if (late) mbar_wait_w(bars + BAR_EMPTY + 8 * s, (eph >> s) & 1);
                            if (lane == 0) next = atomicInc(&g_tile_counter, wrap);
                        }
                        id = first_dynamic + next;
                        if (lane == 0) st_async_peer(slot, id, b);
                    } else {
                        mbar_expect_tx_1(b, 4);
                        mbar_wait_w(b, ((i - TP(N_STATIC)) / ID_BARS) & 1);
                        id = lds32(slot);
                    }
                    id = uniform(id);
                }
                drawn = rank == 0 && i + 1 >= TP(N_STATIC) && id + TP(AHEAD_TO) < num_tiles;
                if (drawn && lane == 0) next = atomicInc(&g_tile_counter, wrap);
                sts32(slot, id);
                sts32(bars + FRONT_AT, id);
                TR(7, i);
                mbar_wait_w(bars + BAR_EMPTY + 8 * s, (eph >> s) & 1);
                eph ^= 1u << s;
                const uint32_t full = bars + BAR_FULL + 8 * s;
                if (id >= num_tiles) {
                    sts32(bars + ISSUED_AT, id);
                    mbar_arrive_1(full);
#pragma unroll 1
                    for (uint32_t u = 0; u < STAGES; u++)
                        if (u != s) mbar_wait_w(bars + BAR_EMPTY + 8 * u, (eph >> u) & 1);
                    break;
                }
                sts32(bars + ISSUED_AT, id);
                TR(0, i);
                TRV(15, i, id);
                mbar_expect_tx_1(full, STAGE_BYTES);
                tma_load_x_1(smem + s * STAGE_BYTES + rank * HALF_BYTES, &maps.x, full, id * 8 + rank * 4,
                             id + TP(EF_TAIL) >= num_tiles ? EVICT_FIRST : EVICT_NORMAL);
            }
        } else if (warp == NUM_WG * 4 + 1) {
#pragma unroll
            for (int s = 0; s < STAGES; s++) {
                mbar_init_1(bars + BAR_FULL + 8 * s, 1);
                mbar_init_1(bars + BAR_EMPTY + 8 * s, NUM_WG * 4 * 2);
            }
#pragma unroll
            for (int s = 0; s < ID_BARS; s++) mbar_init_1(bars + BAR_ID + 8 * s, 1);
            publish_barriers();
            cluster_arrive();
            TR(0, 61);
            cluster_wait();
            prefetch_map_1(&maps.out);
        } else if (warp == NUM_WG * 4 + 2) {
#pragma unroll
            for (int b = 0; b < BUFFERS; b++) {
#pragma unroll
                for (int w = 0; w < NUM_WG; w++) {
                    mbar_init_1(bars + BAR_OFREE + b * 32 + w * 8, 1);
                    mbar_init_1(bars + BAR_OFULL + b * 32 + w * 8, 4);
                }
            }
            publish_barriers();
            cluster_arrive();
            cluster_wait();
            uint32_t open = 0, due = 0;
            Ring o = {2, 0};
#pragma unroll 1
            for (uint32_t j = 0;; o.next_buffer(tune, ++j)) {
                const uint32_t parity = o.parity();
                const uint32_t obar = bars + o.s * 32;
                if (!mbar_test_w(obar + BAR_OFULL, parity)) {
                    hand_back<0>(open);
                    mbar_wait_w(obar + BAR_OFULL, parity);
                }
                const uint32_t id = uniform(lds32(bars + ID_AT + 4 * (j & (ID_SLOTS - 1))));
                if (id >= num_tiles) break;
                const uint32_t src = smem + SMEM_OUT + o.s * HALF_BYTES;
                const uint32_t period = j <= TP(ST_E1) ? TP(ST_P1) : j <= TP(ST_E2) ? TP(ST_P2) : TP(ST_P3);
                uint32_t now = timer_ns();
                if (j >= TP(ST_AT)) {
                    if (j == TP(ST_AT)) due += cluster * TP(ST_STAG);
#pragma unroll 1
                    for (uint32_t spins = 0; spins < SPIN_LIMIT; spins++) {
                        const uint32_t front = uniform(lds32(bars + FRONT_AT));
                        const uint32_t gap = front + TP(ST_T2) >= num_tiles ? TP(ST_PU) : front + TP(ST_T1) >= num_tiles ? TP(ST_PT) : period;
                        if ((int32_t)(now - due - gap) >= 0) {
                            due += gap;
                            break;
                        }
                        hand_back<0>(open);
                        now = timer_ns();
                    }
                }
                if (j < TP(ST_AT) || (int32_t)(now - TP(ST_SLACK) - due) > 0) due = now - TP(ST_SLACK);
                const bool whole = mbar_test_w(obar + BAR_OFULL + 8, parity) && mbar_test_w(obar + BAR_OFULL + 16, parity);
                if (whole) {
                    TR(11, j);
#pragma unroll
                    for (int w = 0; w < NUM_WG; w++) tma_store_1(&maps.out, src + w * SLICE_BYTES, slice_channel(rank, w), id * TILE_PIX);
                    TR(12, j);
                    TR(13, j);
                    hand_back<3>(open);
                    stores_read_wait<2>();
                    mbar_arrive_1(obar + BAR_OFREE);
                    stores_read_wait<1>();
                    mbar_arrive_1(obar + BAR_OFREE + 8);
                    open = obar + BAR_OFREE + 16;
                } else {
#pragma unroll 1
                    for (uint32_t w = 0; w < NUM_WG; w++) {
                        if (!mbar_test_w(obar + BAR_OFULL + w * 8, parity)) {
                            hand_back<0>(open);
                            mbar_wait_w(obar + BAR_OFULL + w * 8, parity);
                        }
                        TR(11 + w, j);
                        tma_store_1(&maps.out, src + w * SLICE_BYTES, slice_channel(rank, w), id * TILE_PIX);
                        hand_back<1>(open);
                        open = obar + BAR_OFREE + w * 8;
                    }
                }
            }
            stores_read_wait<0>();
            TR(4, 62);
        } else {
            uint32_t due = timer_ns() + TP(PM_T0) + (blockIdx.x & 3) * TP(PM_STAG);
            sts32(bars + ISSUED_AT, 0);
            cluster_arrive();
            const uint32_t step = num_clusters / 2;
#pragma unroll 1
            for (uint32_t piece = PRE_X; piece < TP(PM_E4); piece++) {
                const uint32_t t = cluster + piece / 2 * num_clusters;
                if (t >= num_tiles) break;
                uint32_t now;
#pragma unroll 1
                for (uint32_t spins = 0; spins < 16384; spins++) {
                    const uint32_t issued = uniform(lds32(bars + ISSUED_AT));
                    now = timer_ns();
                    const int lead = max((int)TP(LEAD_B), (int)TP(LEAD_A) - (max((int)issued - (int)TP(LEAD_F), 0) * (int)TP(LEAD_S) >> 4));
                    if ((int32_t)(now - due) >= 0 && cluster + piece * step <= issued + lead) break;
                    __nanosleep(20);
                }
                if ((int32_t)(now - TP(PM_SLACK) - due) > 0) due = now - TP(PM_SLACK);
                due += piece < TP(PM_E1) ? TP(PM_DT1) : piece < TP(PM_E2) ? TP(PM_DT2) : piece < TP(PM_E3) ? TP(PM_DT3) : TP(PM_DT4);
                const uint8_t* p = x_raw + (size_t)t * STAGE_BYTES + rank * HALF_BYTES + (piece % 2) * 12288 + lane * 128;
#pragma unroll
                for (int k = 0; k < 3; k++) asm volatile("prefetch.global.L2 [%0];" ::"l"(p + k * 4096) : "memory");
                if (piece % 2 == 0) TR(14, piece / 2);
            }
            cluster_wait();
        }
    }
}

typedef CUresult (*EncodeTiledFn)(CUtensorMap*, CUtensorMapDataType, cuuint32_t, void*, const cuuint64_t*,
                                  const cuuint64_t*, const cuuint32_t*, const cuuint32_t*, CUtensorMapInterleave,
                                  CUtensorMapSwizzle, CUtensorMapL2promotion, CUtensorMapFloatOOBfill);

}

extern "C" void kernel_launch(void* const* d_in, const int* in_sizes, int n_in, void* d_out, int out_size) {
    (void)n_in;
    (void)out_size;
    void* x = d_in[0];
    void* w = d_in[1];
    const uint16_t* b = (const uint16_t*)d_in[2];
    const int M = in_sizes[0] / C;
    const int num_tiles = M / TILE_PIX;

    static EncodeTiledFn encode = nullptr;
    static int sms = 0;
    if (!encode) {
        void* fn = nullptr;
        cudaDriverEntryPointQueryResult q;
        cudaGetDriverEntryPoint("cuTensorMapEncodeTiled", &fn, cudaEnableDefault, &q);
        encode = (EncodeTiledFn)fn;
        cudaDeviceGetAttribute(&sms, cudaDevAttrMultiProcessorCount, 0);
        cudaFuncSetAttribute(conv1x1_kernel, cudaFuncAttributeMaxDynamicSharedMemorySize, SMEM_TOTAL);
    }

    Maps maps;
    const cuuint32_t ones[4] = {1, 1, 1, 1};
    auto make = [&](CUtensorMap* map, int rank, void* base, const cuuint64_t* dims, const cuuint64_t* strides,
                    const cuuint32_t* box, CUtensorMapL2promotion promo) {
        encode(map, CU_TENSOR_MAP_DATA_TYPE_BFLOAT16, rank, base, dims, strides, box, ones, CU_TENSOR_MAP_INTERLEAVE_NONE,
               CU_TENSOR_MAP_SWIZZLE_128B, promo, CU_TENSOR_MAP_FLOAT_OOB_FILL_NONE);
    };
    {
        const cuuint64_t dims[4]    = {64, 8, 6, (cuuint64_t)(M / 8)};
        const cuuint64_t strides[3] = {C * 2, 128, 8 * C * 2};
        const cuuint32_t box[4]     = {64, 8, 6, TILE_PIX / 16};
        make(&maps.x, 4, x, dims, strides, box, CU_TENSOR_MAP_L2_PROMOTION_L2_128B);
    }
    {
        const cuuint64_t dims[3]    = {C, C / 2, 2};
        const cuuint64_t strides[2] = {C * 2, C * C};
        const cuuint32_t box[3]     = {64, C / 2, 2};
        make(&maps.w, 3, w, dims, strides, box, CU_TENSOR_MAP_L2_PROMOTION_L2_128B);
    }
    {
        const cuuint64_t dims[2]    = {C, (cuuint64_t)M};
        const cuuint64_t strides[1] = {C * 2};
        const cuuint32_t box[2]     = {64, TILE_PIX};
        make(&maps.out, 2, d_out, dims, strides, box, CU_TENSOR_MAP_L2_PROMOTION_NONE);
    }

    const Tune tune;
    int clusters = sms / 2;
    if (TP(N_STATIC) < 36 && clusters > num_tiles / (int)TP(N_STATIC)) clusters = num_tiles / (int)TP(N_STATIC);
    conv1x1_kernel<<<clusters * 2, THREADS, SMEM_TOTAL>>>((const uint8_t*)x, (const uint8_t*)w, b, (uint32_t)num_tiles,
                                                          (uint32_t)clusters, maps, tune);
}
```

```cpp
#include <cuda_runtime.h>
#include <cuda_bf16.h>
#include <cuda.h>
#include <stdint.h>

#define EARLY_AT 18

#define W_FIRST 2
#define PRE_X 1
#define PRE_D0 200
#define PRE_DT 300
#define PRE_W 64

#define TUNABLES(F) \
    F(EARLY_TILES, 330)    \
    F(EARLY_HEAD, 1056)       \
    F(N_STATIC, 20)        \
    F(PM_T0, 0)            \
    F(PM_DT1, 420)         \
    F(PM_E1, 17) \
    F(PM_DT2, 300) \
    F(PM_E2, 20) \
    F(PM_DT3, 780) \
    F(PM_E3, 63) \
    F(PM_DT4, 650) \
    F(PM_E4, 72) \
    F(PM_STAG, 210)        \
    F(LEAD_A, 269)        \
    F(LEAD_F, 500)         \
    F(LEAD_S, 3)           \
    F(LEAD_B, 151)        \
    F(PM_SLACK, 150)    \
    F(AHEAD_TO, 1034)      \
    F(EF_TAIL, 500)        \
    F(ST_AT, 2)            \
    F(ST_STAG, 30)          \
    F(ST_P1, 2000)         \
    F(ST_E1, 10) \
    F(ST_P2, 2010) \
    F(ST_E2, 18) \
    F(ST_P3, 2020) \
    F(ST_SLACK, 300)       \
    F(SW_J, 12)            \
    F(SW_D, 7250)          \
    F(ST_PT, 1500)         \
    F(SW_D1, 3000)         \
    F(ST_PU, 520)          \
    F(LD_D, 0)             \
    F(LD_P, 0)             \
    F(RING2_AT, 999)       \
    F(OUT5_AT, 999)        \
    F(HOLD_T, 100)         \
    F(DEEP_AT, 120)          \
    F(X0, 0) \
    F(X1, 0) \
    F(X2, 0) \
    F(X3, 0)

struct Tune {
#define F(n, v) static constexpr uint32_t n = v;
    TUNABLES(F)
#undef F
};
#define TP(n) (Tune::n)

#define TRV(slot, idx, v)
#define TR(slot, idx)
#define TRE(slot, idx)

namespace {

constexpr int C            = 384;
constexpr int TILE_PIX     = 64;
constexpr int STAGES       = 3;
constexpr int STAGE_BYTES  = TILE_PIX * C * 2;
constexpr int HALF_BYTES   = STAGE_BYTES / 2;
constexpr int SLICE_BYTES  = TILE_PIX * 128;
constexpr int W_LINES      = C * C * 2 / 128;
constexpr int NUM_WG       = 3;
constexpr int THREADS      = (NUM_WG + 1) * 128;
constexpr int BUFFERS      = 5;
constexpr int SMEM_OUT     = 2 * STAGE_BYTES;
constexpr int SMEM_BAR     = SMEM_OUT + BUFFERS * HALF_BYTES;
constexpr int SMEM_TOTAL   = SMEM_BAR + 1024 + 1024;
constexpr int ID_SLOTS     = 16;
constexpr int ID_BARS      = 4;
constexpr uint32_t SPIN_LIMIT = 1u << 24;
constexpr int BAR_W     = 0;
constexpr int BAR_FULL  = 32;
constexpr int BAR_EMPTY = BAR_FULL + 32;
constexpr int BAR_ID    = BAR_EMPTY + 32;
constexpr int BAR_OFREE = BAR_ID + 8 * ID_BARS;
constexpr int BAR_OFULL = BAR_OFREE + 32 * BUFFERS;
constexpr int ID_AT     = BAR_OFULL + 32 * BUFFERS;
constexpr int FRONT_AT  = ID_AT + 4 * ID_SLOTS;
constexpr int ISSUED_AT = FRONT_AT + 4;
constexpr int SWITCH_AT = ISSUED_AT + 4;
constexpr uint64_t EVICT_NORMAL = 0x1000000000000000ull;
constexpr uint64_t EVICT_FIRST  = 0x12F0000000000000ull;

struct Maps {
    CUtensorMap w, x, out;
};

__device__ unsigned int g_tile_counter;

#define ELECT "{\n.reg .pred e;\nelect.sync _|e, 0xffffffff;\n@e "

__device__ __forceinline__ uint32_t smem_u32(const void* p) {
    return (uint32_t)__cvta_generic_to_shared(p);
}
__device__ __forceinline__ void mbar_init_1(uint32_t bar, uint32_t count) {
    asm volatile(ELECT "mbarrier.init.shared::cta.b64 [%0], %1;\n}" ::"r"(bar), "r"(count) : "memory");
}
__device__ __forceinline__ void mbar_expect_tx_1(uint32_t bar, uint32_t bytes) {
    asm volatile(ELECT "mbarrier.arrive.expect_tx.shared::cta.b64 _, [%0], %1;\n}" ::"r"(bar), "r"(bytes) : "memory");
}
__device__ __forceinline__ void mbar_arrive_1(uint32_t bar) {
    asm volatile(ELECT "mbarrier.arrive.shared::cta.b64 _, [%0];\n}" ::"r"(bar) : "memory");
}
__device__ __forceinline__ void mbar_wait(uint32_t bar, uint32_t parity) {
    uint32_t done;
    uint32_t spins = 0;
    do {
        asm volatile(
            "{\n.reg .pred p;\n"
            "mbarrier.try_wait.parity.shared::cta.b64 p, [%1], %2;\n"
            "selp.u32 %0, 1, 0, p;\n}"
            : "=r"(done) : "r"(bar), "r"(parity) : "memory");
    } while (!done && ++spins < SPIN_LIMIT);
}
__device__ __forceinline__ void mbar_wait_w(uint32_t bar, uint32_t parity) {
    mbar_wait(bar, parity);
    __syncwarp();
}
__device__ __forceinline__ bool mbar_test_w(uint32_t bar, uint32_t parity) {
    uint32_t done;
    asm volatile(
        "{\n.reg .pred p;\n"
        "mbarrier.test_wait.parity.shared::cta.b64 p, [%1], %2;\n"
        "selp.u32 %0, 1, 0, p;\n}"
        : "=r"(done) : "r"(bar), "r"(parity) : "memory");
    return __all_sync(0xffffffffu, done);
}
__device__ __forceinline__ bool mbar_try_w(uint32_t bar, uint32_t parity, uint32_t ns) {
    uint32_t done;
    asm volatile(
        "{\n.reg .pred p;\n"
        "mbarrier.try_wait.parity.shared::cta.b64 p, [%1], %2, %3;\n"
        "selp.u32 %0, 1, 0, p;\n}"
        : "=r"(done) : "r"(bar), "r"(parity), "r"(ns) : "memory");
    return __all_sync(0xffffffffu, done);
}
__device__ __forceinline__ void mbar_arrive_cta(uint32_t bar, uint32_t cta) {
    asm volatile(
        "{\n.reg .b32 ra;\n"
        "mapa.shared::cluster.u32 ra, %0, %1;\n"
        "mbarrier.arrive.shared::cluster.b64 _, [ra];\n}"
        ::"r"(bar), "r"(cta) : "memory");
}
__device__ __forceinline__ void st_async_peer(uint32_t addr, uint32_t val, uint32_t bar) {
    asm volatile(
        "{\n.reg .b32 ra, rb;\n"
        "mapa.shared::cluster.u32 ra, %0, 1;\n"
        "mapa.shared::cluster.u32 rb, %2, 1;\n"
        "st.async.weak.shared::cluster.mbarrier::complete_tx::bytes.b32 [ra], %1, [rb];\n}"
        ::"r"(addr), "r"(val), "r"(bar) : "memory");
}
__device__ __forceinline__ uint32_t lds32(uint32_t addr) {
    uint32_t v;
    asm volatile("ld.shared.b32 %0, [%1];" : "=r"(v) : "r"(addr) : "memory");
    return v;
}
__device__ __forceinline__ uint32_t uniform(uint32_t v) {
    return __shfl_sync(0xffffffffu, v, 0);
}
__device__ __forceinline__ void sts32(uint32_t addr, uint32_t v) {
    asm volatile("st.shared.b32 [%0], %1;" ::"r"(addr), "r"(v) : "memory");
}
__device__ __forceinline__ void tma_load_w_1(uint32_t dst, const CUtensorMap* map, uint32_t bar, int n) {
    asm volatile(
        ELECT "cp.async.bulk.tensor.3d.shared::cluster.global.mbarrier::complete_tx::bytes [%0], [%1, {%3, %4, %4}], [%2];\n}"
        ::"r"(dst), "l"(map), "r"(bar), "r"(n), "r"(0) : "memory");
}
__device__ __forceinline__ void tma_load_x_1(uint32_t dst, const CUtensorMap* map, uint32_t bar, int group, uint64_t policy) {
    asm volatile(
        ELECT "cp.async.bulk.tensor.4d.shared::cluster.global.mbarrier::complete_tx::bytes.multicast::cluster.L2::cache_hint"
        " [%0], [%1, {%3, %3, %3, %4}], [%2], %5, %6;\n}"
        ::"r"(dst), "l"(map), "r"(bar), "r"(0), "r"(group), "h"((uint16_t)3), "l"(policy) : "memory");
}
__device__ __forceinline__ void tma_store_1(const CUtensorMap* map, uint32_t src, int ch, int pix) {
    asm volatile(
        ELECT "cp.async.bulk.tensor.2d.global.shared::cta.bulk_group [%0, {%2, %3}], [%1];\n}\n"
        "cp.async.bulk.commit_group;"
        ::"l"(map), "r"(src), "r"(ch), "r"(pix) : "memory");
}
template <int N>
__device__ __forceinline__ void stores_read_wait() {
    asm volatile("cp.async.bulk.wait_group.read %0;" ::"n"(N) : "memory");
}
__device__ __forceinline__ void prefetch_map_1(const CUtensorMap* map) {
    asm volatile(ELECT "prefetch.tensormap [%0];\n}" ::"l"(map) : "memory");
}
__device__ __forceinline__ uint32_t timer_ns() {
    uint32_t t;
    asm volatile("mov.u32 %0, %%globaltimer_lo;" : "=r"(t)::"memory");
    return t;
}
__device__ __forceinline__ void cluster_arrive() {
    asm volatile("barrier.cluster.arrive.relaxed.aligned;" ::: "memory");
}
__device__ __forceinline__ void cluster_wait() {
    asm volatile("barrier.cluster.wait.aligned;" ::: "memory");
}
__device__ __forceinline__ void publish_barriers() {
    asm volatile("fence.mbarrier_init.release.cluster;" ::: "memory");
    asm volatile("fence.proxy.async.shared::cta;" ::: "memory");
}

__device__ __forceinline__ void wgmma_rs_n64(float (&d)[32], const uint32_t* a, uint64_t desc, int scale_d) {
    asm volatile(
        "{\n.reg .pred p;\n"
        "setp.ne.b32 p, %37, 0;\n"
        "wgmma.mma_async.sync.aligned.m64n64k16.f32.bf16.bf16 "
        "{%0, %1, %2, %3, %4, %5, %6, %7, %8, %9, %10, %11, %12, %13, %14, %15, "
        "%16, %17, %18, %19, %20, %21, %22, %23, %24, %25, %26, %27, %28, %29, %30, %31}, "
        "{%32, %33, %34, %35}, %36, p, 1, 1, 0;\n}"
        : "+f"(d[0]), "+f"(d[1]), "+f"(d[2]), "+f"(d[3]), "+f"(d[4]), "+f"(d[5]), "+f"(d[6]), "+f"(d[7]),
          "+f"(d[8]), "+f"(d[9]), "+f"(d[10]), "+f"(d[11]), "+f"(d[12]), "+f"(d[13]), "+f"(d[14]), "+f"(d[15]),
          "+f"(d[16]), "+f"(d[17]), "+f"(d[18]), "+f"(d[19]), "+f"(d[20]), "+f"(d[21]), "+f"(d[22]), "+f"(d[23]),
          "+f"(d[24]), "+f"(d[25]), "+f"(d[26]), "+f"(d[27]), "+f"(d[28]), "+f"(d[29]), "+f"(d[30]), "+f"(d[31])
        : "r"(a[0]), "r"(a[1]), "r"(a[2]), "r"(a[3]), "l"(desc), "r"(scale_d));
}

__device__ __forceinline__ uint32_t pack_bias(float lo, float hi, uint32_t bias2) {
    uint32_t r;
    asm("{\n.reg .b32 t;\n"
        "cvt.rn.bf16x2.f32 t, %2, %1;\n"
        "add.rn.bf16x2 %0, t, %3;\n}"
        : "=r"(r) : "f"(lo), "f"(hi), "r"(bias2));
    return r;
}

__device__ __forceinline__ int slice_channel(uint32_t rank, int wg) {
    return (wg * 2 + rank) * 64;
}

struct Consumer {
    uint32_t wreg[96];
    uint32_t bias_lo, bias_hi, st_addr, bars;
    uint64_t desc_base;
    int wg, lane;
};
struct Ring {
    uint32_t s, phase;
    __device__ __forceinline__ uint32_t parity() const { return (phase >> s) & 1; }
    __device__ __forceinline__ void next_slot(const Tune& tune, uint32_t next_i) {
        phase ^= 1u << s;
        s = s == 2 || (s == 1 && next_i >= TP(RING2_AT)) ? 0 : s + 1;
    }
    __device__ __forceinline__ void next_buffer(const Tune& tune, uint32_t next_i) {
        phase ^= 1u << s;
        s = s != BUFFERS - 1 ? s + 1 : next_i >= TP(OUT5_AT) ? 0 : 2;
    }
};
__device__ __forceinline__ uint32_t w_stage(int wg) {
    return (wg + 1) * STAGE_BYTES + (wg == 2 ? HALF_BYTES : 0);
}

__device__ __forceinline__ void multiply(const Consumer& c, const Ring& r, float (&acc)[32], uint32_t i, bool early) {
    const int next_turn = 4 + (c.wg + 1) % NUM_WG;
    if ((i | c.wg) != 0) asm volatile("bar.sync %0, 256;" ::"r"(4 + c.wg) : "memory");
    TRE(1 + c.wg * 2, i);
    const uint64_t desc = c.desc_base + (uint64_t)(r.s * (STAGE_BYTES >> 4));
    asm volatile("wgmma.fence.sync.aligned;" ::: "memory");
#pragma unroll
    for (int ks = 0; ks < 24; ks++) {
        const uint64_t d = desc + (uint64_t)((ks >> 2) * 64 + (ks & 3) * 2);
        wgmma_rs_n64(acc, &c.wreg[ks * 4], d, ks != 0);
        if (ks + 1 == EARLY_AT && early) asm volatile("bar.arrive %0, 256;" ::"r"(next_turn) : "memory");
    }
    asm volatile("wgmma.commit_group.sync.aligned;" ::: "memory");
    asm volatile("wgmma.wait_group.sync.aligned 0;" ::: "memory");
#pragma unroll
    for (int j = 0; j < 32; j++) asm volatile("" : "+f"(acc[j])::"memory");
    if (!early) asm volatile("bar.arrive %0, 256;" ::"r"(next_turn) : "memory");
    TRE(2 + c.wg * 2, i);
    if (c.lane < 2) mbar_arrive_cta(c.bars + BAR_EMPTY + 8 * r.s, c.lane);
}
__device__ __forceinline__ void write_out(const Consumer& c, const Ring& r, const uint32_t (&v)[16]) {
    const uint32_t obar = c.bars + (r.s * 4 + c.wg) * 8;
    mbar_wait_w(obar + BAR_OFREE, r.parity() ^ 1);
    const uint32_t dst = c.st_addr + r.s * HALF_BYTES;
#pragma unroll
    for (int j = 0; j < 4; j++) {
        asm volatile("stmatrix.sync.aligned.m8n8.x4.trans.shared.b16 [%0], {%1, %2, %3, %4};"
                     ::"r"(dst + j * 2048), "r"(v[4 * j]), "r"(v[4 * j + 1]), "r"(v[4 * j + 2]), "r"(v[4 * j + 3]) : "memory");
    }
    asm volatile("fence.proxy.async.shared::cta;" ::: "memory");
    __syncwarp();
    mbar_arrive_1(obar + BAR_OFULL);
}

template <int N>
__device__ __forceinline__ void hand_back(uint32_t& open) {
    if (open != 0) {
        stores_read_wait<N>();
        mbar_arrive_1(open);
        open = 0;
    }
}

__global__ void __cluster_dims__(2, 1, 1) __launch_bounds__(THREADS, 1)
conv1x1_kernel(const uint8_t* __restrict__ x_raw,
               const uint8_t* __restrict__ w_raw,
               const uint16_t* __restrict__ bias,
               uint32_t num_tiles,
               uint32_t num_clusters,
               const __grid_constant__ Maps maps,
               const __grid_constant__ Tune tune) {
    if (threadIdx.x < 96) {
        const uint32_t line = blockIdx.x % (W_LINES / PRE_W) * PRE_W + threadIdx.x;
        if (threadIdx.x < PRE_W) asm volatile("prefetch.global.L2 [%0];" ::"l"(w_raw + line * 128) : "memory");
    } else if (threadIdx.x < 128) {
        prefetch_map_1(&maps.w);
        prefetch_map_1(&maps.x);
    }
    if (threadIdx.x < NUM_WG * 128) cluster_arrive();
    if (threadIdx.x >= 128 && threadIdx.x < 128 + PRE_X * 96) {
        const uint8_t* p = x_raw + (size_t)blockIdx.x * HALF_BYTES + (threadIdx.x - 128) * 128;
        if (PRE_D0 + PRE_DT != 0) {
            const uint32_t wait = PRE_D0 + ((threadIdx.x - 128) >> 5) * PRE_DT;
            const uint32_t c0 = clock();
            while (clock() - c0 < wait) {}
        }
        asm volatile("prefetch.global.L2 [%0];" ::"l"(p) : "memory");
    }
    extern __shared__ uint8_t smem_raw[];
    const uint32_t smem = (smem_u32(smem_raw) + 1023u) & ~1023u;
    const uint32_t bars = smem + SMEM_BAR;

    const int warp = uniform(threadIdx.x >> 5);
    const int lane = threadIdx.x & 31;
    const uint32_t rank         = blockIdx.x & 1;
    const uint32_t cluster      = blockIdx.x >> 1;

    if (warp < NUM_WG * 4) {
        const int wg = warp >> 2;
        const int wq = warp & 3;
        asm volatile("setmaxnreg.inc.sync.aligned.u32 160;");
        Consumer c;
        c.wg = wg;
        c.lane = lane;
        c.bars = bars;
        c.bias_lo = bias[slice_channel(rank, wg) + wq * 16 + (lane >> 2)] * 0x10001u;
        c.bias_hi = bias[slice_channel(rank, wg) + wq * 16 + (lane >> 2) + 8] * 0x10001u;

        cluster_wait();
        TRE(1 + wg, 63);
        mbar_wait_w(bars + BAR_W + 8 * wg, 0);
        TRE(4 + wg, 63);
        {
            const int r = lane & 7, m = lane >> 3;
            const uint32_t base = smem + w_stage(wg) + ((m >> 1) * 8 + r) * 128 + (((2 * wq + (m & 1)) ^ r) << 4);
#pragma unroll
            for (int ks = 0; ks < 24; ks++) {
                asm volatile("ldmatrix.sync.aligned.m8n8.x4.trans.shared.b16 {%0, %1, %2, %3}, [%4];"
                             : "=r"(c.wreg[ks * 4 + 0]), "=r"(c.wreg[ks * 4 + 1]), "=r"(c.wreg[ks * 4 + 2]), "=r"(c.wreg[ks * 4 + 3])
                             : "r"(base + ks * 2048) : "memory");
            }
        }
        uint32_t dep = 0;
#pragma unroll
        for (int ks = 0; ks < 24; ks++) dep ^= c.wreg[ks * 4];
        dep &= num_tiles >> 31;
        __syncwarp();
        if (lane < 6 && wg < 2) mbar_arrive_cta(bars + BAR_EMPTY + 8 * (wg + 1) + dep, lane & 1);
        TRE(1 + wg, 60);

        c.st_addr = smem + SMEM_OUT + wg * SLICE_BYTES + ((lane >> 4) * 8 + (lane & 7)) * 128 + (((2 * wq + ((lane >> 3) & 1)) ^ (lane & 7)) << 4);
        c.desc_base = (uint64_t)((smem & 0x3FFFF) >> 4) | ((uint64_t)1 << 16) | ((uint64_t)(6144 >> 4) << 32) | ((uint64_t)1 << 62);

        float acc[32];
        uint32_t packed[16];
        Ring r = {0, uniform(dep)}, o = {2, 0};
        bool held = false;
        uint32_t i = 0;
        for (;; r.next_slot(tune, ++i)) {
            mbar_wait(bars + BAR_FULL + 8 * r.s, r.parity());
            const uint32_t id = lds32(bars + ID_AT + 4 * (i & (ID_SLOTS - 1)));
            if (id >= num_tiles) break;
            multiply(c, r, acc, i, id + TP(EARLY_TILES) >= num_tiles || id + 1 <= TP(EARLY_HEAD));
            if (held) {
                write_out(c, o, packed);
                o.next_buffer(tune, i);
            }
#pragma unroll
            for (int j = 0; j < 16; j++) packed[j] = pack_bias(acc[2 * j], acc[2 * j + 1], j & 1 ? c.bias_hi : c.bias_lo);
            held = id + TP(HOLD_T) < num_tiles && !mbar_test_w(bars + BAR_OFREE + (o.s * 4 + wg) * 8, o.parity() ^ 1);
            if (!held) {
                write_out(c, o, packed);
                o.next_buffer(tune, i + 1);
            }
            TRE(8 + wg, i);
        }
        if (held) {
            write_out(c, o, packed);
            o.next_buffer(tune, i);
        }
        if (wg == 0) {
            mbar_wait_w(bars + BAR_OFREE + o.s * 32, o.parity() ^ 1);
            mbar_arrive_1(bars + BAR_OFULL + o.s * 32);
            asm volatile("bar.sync 4, 256;" ::: "memory");
        }
        TRE(1 + wg, 62);
    } else {
        asm volatile("setmaxnreg.dec.sync.aligned.u32 32;");
        if (warp == NUM_WG * 4) {
#pragma unroll
            for (int j = 0; j < NUM_WG; j++) mbar_init_1(bars + BAR_W + 8 * j, 1);
            publish_barriers();
            cluster_arrive();
            sts32(bars + ID_AT, cluster);
            sts32(bars + SWITCH_AT, 0);
#pragma unroll
            for (int j = 0; j < NUM_WG; j++) {
                if (j == W_FIRST) {
                    cluster_wait();
                    TR(0, 0);
                    mbar_expect_tx_1(bars + BAR_FULL, STAGE_BYTES);
                    tma_load_x_1(smem + rank * HALF_BYTES, &maps.x, bars + BAR_FULL, cluster * 8 + rank * 4, EVICT_NORMAL);
                }
                mbar_expect_tx_1(bars + BAR_W + 8 * j, STAGE_BYTES);
                tma_load_w_1(smem + w_stage(j), &maps.w, bars + BAR_W + 8 * j, slice_channel(rank, j));
                if (j == 0) TR(2, 61);
            }
            const uint32_t first_dynamic = TP(N_STATIC) * num_clusters;
            const uint32_t wrap = num_tiles - first_dynamic + num_clusters - 1;
            uint32_t s = 0, eph = 0, next = 0, id = 0, last = 0;
            bool drawn = false;
#pragma unroll 1
            for (uint32_t i = 1;; i++) {
                s = s == 2 || (s == 1 && i >= TP(RING2_AT)) ? 0 : s + 1;
                const uint32_t slot = bars + ID_AT + 4 * (i & (ID_SLOTS - 1));
                const bool late = id + TP(DEEP_AT) >= num_tiles;
                id = cluster + i * num_clusters;
                if (i >= TP(N_STATIC)) {
                    const uint32_t b = bars + BAR_ID + 8 * ((i - TP(N_STATIC)) & (ID_BARS - 1));
                    if (rank == 0) {
                        if (!drawn) {
                            if (late) mbar_wait_w(bars + BAR_EMPTY + 8 * s, (eph >> s) & 1);
                            if (lane == 0) next = atomicInc(&g_tile_counter, wrap);
                        }
                        id = first_dynamic + next;
                        if (lane == 0) st_async_peer(slot, id, b);
                    } else {
                        mbar_expect_tx_1(b, 4);
                        mbar_wait_w(b, ((i - TP(N_STATIC)) / ID_BARS) & 1);
                        id = lds32(slot);
                    }
                    id = uniform(id);
                }
                drawn = rank == 0 && i + 1 >= TP(N_STATIC) && id + TP(AHEAD_TO) < num_tiles;
                if (drawn && lane == 0) next = atomicInc(&g_tile_counter, wrap);
                sts32(slot, id);
                TR(7, i);
                mbar_wait_w(bars + BAR_EMPTY + 8 * s, (eph >> s) & 1);
                eph ^= 1u << s;
                const uint32_t full = bars + BAR_FULL + 8 * s;
                if (id >= num_tiles) {
                    sts32(bars + ISSUED_AT, id);
                    mbar_arrive_1(full);
#pragma unroll 1
                    for (uint32_t u = 0; u < STAGES; u++)
                        if (u != s) mbar_wait_w(bars + BAR_EMPTY + 8 * u, (eph >> u) & 1);
                    break;
                }
                if (TP(LD_P) != 0) {
                    const uint32_t from = uniform(lds32(bars + SWITCH_AT));
                    uint32_t now = timer_ns();
                    if (from != 0 && (int32_t)(now - from) >= 0) {
#pragma unroll 1
                        for (uint32_t spins = 0; now - last < TP(LD_P) && spins < SPIN_LIMIT; spins++) {
                            __nanosleep(20);
                            now = timer_ns();
                        }
                    }
                    last = now;
                }
                sts32(bars + ISSUED_AT, id);
                TR(0, i);
                TRV(15, i, id);
                mbar_expect_tx_1(full, STAGE_BYTES);
                tma_load_x_1(smem + s * STAGE_BYTES + rank * HALF_BYTES, &maps.x, full, id * 8 + rank * 4,
                             id + TP(EF_TAIL) >= num_tiles ? EVICT_FIRST : EVICT_NORMAL);
            }
        } else if (warp == NUM_WG * 4 + 1) {
#pragma unroll
            for (int s = 0; s < STAGES; s++) {
                mbar_init_1(bars + BAR_FULL + 8 * s, 1);
                mbar_init_1(bars + BAR_EMPTY + 8 * s, NUM_WG * 4 * 2);
            }
#pragma unroll
            for (int s = 0; s < ID_BARS; s++) mbar_init_1(bars + BAR_ID + 8 * s, 1);
            publish_barriers();
            cluster_arrive();
            TR(0, 61);
            cluster_wait();
            prefetch_map_1(&maps.out);
        } else if (warp == NUM_WG * 4 + 2) {
#pragma unroll
            for (int b = 0; b < BUFFERS; b++) {
#pragma unroll
                for (int w = 0; w < NUM_WG; w++) {
                    mbar_init_1(bars + BAR_OFREE + b * 32 + w * 8, 1);
                    mbar_init_1(bars + BAR_OFULL + b * 32 + w * 8, 4);
                }
            }
            publish_barriers();
            cluster_arrive();
            cluster_wait();
            const uint32_t mark = num_tiles / num_clusters - TP(SW_J);
            uint32_t open = 0, due = 0, t_end = 0;
            Ring o = {2, 0};
#pragma unroll 1
            for (uint32_t j = 0;; o.next_buffer(tune, ++j)) {
                const uint32_t parity = o.parity();
                const uint32_t obar = bars + o.s * 32;
                if (!mbar_test_w(obar + BAR_OFULL, parity)) {
                    hand_back<0>(open);
                    mbar_wait_w(obar + BAR_OFULL, parity);
                }
                const uint32_t id = uniform(lds32(bars + ID_AT + 4 * (j & (ID_SLOTS - 1))));
                if (id >= num_tiles) break;
                const uint32_t src = smem + SMEM_OUT + o.s * HALF_BYTES;
                const uint32_t period = j <= TP(ST_E1) ? TP(ST_P1) : j <= TP(ST_E2) ? TP(ST_P2) : TP(ST_P3);
                uint32_t now = timer_ns();
                if (j >= TP(ST_AT)) {
                    if (j == TP(ST_AT)) due += cluster * TP(ST_STAG);
                    if (j <= mark || (int32_t)(due + period - t_end) <= 0) {
                        due += period;
                    } else {
                        float t = (float)(int32_t)(due - t_end), rest = 1.f;
                        if (t < 0.f) {
                            rest += __fdividef(t, (float)period);
                            t = 0.f;
                        }
                        const float room = (float)TP(SW_D1) - t;
                        if (room >= rest * (float)TP(ST_PT)) {
                            t += rest * (float)TP(ST_PT);
                        } else {
                            if (room > 0.f) {
                                rest -= __fdividef(room, (float)TP(ST_PT));
                                t += room;
                            }
                            t += rest * (float)TP(ST_PU);
                        }
                        due = t_end + (int32_t)t;
                    }
                    if ((int32_t)(now - due) < 0) hand_back<0>(open);
#pragma unroll 1
                    for (uint32_t spins = 0; (int32_t)(now - due) < 0 && spins < SPIN_LIMIT; spins++) {
                        __nanosleep(20);
                        now = timer_ns();
                    }
                }
                if (j < TP(ST_AT) || (int32_t)(now - TP(ST_SLACK) - due) > 0) due = now - TP(ST_SLACK);
                if (j == mark) {
                    t_end = due - cluster * TP(ST_STAG) + TP(SW_D);
                    sts32(bars + SWITCH_AT, (t_end + TP(LD_D)) | 1);
                }
                const bool whole = mbar_test_w(obar + BAR_OFULL + 8, parity) && mbar_test_w(obar + BAR_OFULL + 16, parity);
                if (whole) {
                    TR(11, j);
#pragma unroll
                    for (int w = 0; w < NUM_WG; w++) tma_store_1(&maps.out, src + w * SLICE_BYTES, slice_channel(rank, w), id * TILE_PIX);
                    TR(12, j);
                    TR(13, j);
                    hand_back<3>(open);
                    stores_read_wait<2>();
                    mbar_arrive_1(obar + BAR_OFREE);
                    stores_read_wait<1>();
                    mbar_arrive_1(obar + BAR_OFREE + 8);
                    open = obar + BAR_OFREE + 16;
                } else {
#pragma unroll 1
                    for (uint32_t w = 0; w < NUM_WG; w++) {
                        if (!mbar_test_w(obar + BAR_OFULL + w * 8, parity)) {
                            hand_back<0>(open);
                            mbar_wait_w(obar + BAR_OFULL + w * 8, parity);
                        }
                        TR(11 + w, j);
                        tma_store_1(&maps.out, src + w * SLICE_BYTES, slice_channel(rank, w), id * TILE_PIX);
                        hand_back<1>(open);
                        open = obar + BAR_OFREE + w * 8;
                    }
                }
            }
            stores_read_wait<0>();
            TR(4, 62);
        } else {
            uint32_t due = timer_ns() + TP(PM_T0) + (blockIdx.x & 3) * TP(PM_STAG);
            sts32(bars + ISSUED_AT, 0);
            cluster_arrive();
            const uint32_t step = num_clusters / 2;
#pragma unroll 1
            for (uint32_t piece = PRE_X; piece < TP(PM_E4); piece++) {
                const uint32_t t = cluster + piece / 2 * num_clusters;
                if (t >= num_tiles) break;
                uint32_t now;
#pragma unroll 1
                for (uint32_t spins = 0; spins < 16384; spins++) {
                    const uint32_t issued = uniform(lds32(bars + ISSUED_AT));
                    now = timer_ns();
                    const int lead = max((int)TP(LEAD_B), (int)TP(LEAD_A) - (max((int)issued - (int)TP(LEAD_F), 0) * (int)TP(LEAD_S) >> 4));
                    if ((int32_t)(now - due) >= 0 && cluster + piece * step <= issued + lead) break;
                    __nanosleep(20);
                }
                if ((int32_t)(now - TP(PM_SLACK) - due) > 0) due = now - TP(PM_SLACK);
                due += piece < TP(PM_E1) ? TP(PM_DT1) : piece < TP(PM_E2) ? TP(PM_DT2) : piece < TP(PM_E3) ? TP(PM_DT3) : TP(PM_DT4);
                const uint8_t* p = x_raw + (size_t)t * STAGE_BYTES + rank * HALF_BYTES + (piece % 2) * 12288 + lane * 128;
#pragma unroll
                for (int k = 0; k < 3; k++) asm volatile("prefetch.global.L2 [%0];" ::"l"(p + k * 4096) : "memory");
                if (piece % 2 == 0) TR(14, piece / 2);
            }
            cluster_wait();
        }
    }
}

typedef CUresult (*EncodeTiledFn)(CUtensorMap*, CUtensorMapDataType, cuuint32_t, void*, const cuuint64_t*,
                                  const cuuint64_t*, const cuuint32_t*, const cuuint32_t*, CUtensorMapInterleave,
                                  CUtensorMapSwizzle, CUtensorMapL2promotion, CUtensorMapFloatOOBfill);

}

extern "C" void kernel_launch(void* const* d_in, const int* in_sizes, int n_in, void* d_out, int out_size) {
    (void)n_in;
    (void)out_size;
    void* x = d_in[0];
    void* w = d_in[1];
    const uint16_t* b = (const uint16_t*)d_in[2];
    const int M = in_sizes[0] / C;
    const int num_tiles = M / TILE_PIX;

    static EncodeTiledFn encode = nullptr;
    static int sms = 0;
    if (!encode) {
        void* fn = nullptr;
        cudaDriverEntryPointQueryResult q;
        cudaGetDriverEntryPoint("cuTensorMapEncodeTiled", &fn, cudaEnableDefault, &q);
        encode = (EncodeTiledFn)fn;
        cudaDeviceGetAttribute(&sms, cudaDevAttrMultiProcessorCount, 0);
        cudaFuncSetAttribute(conv1x1_kernel, cudaFuncAttributeMaxDynamicSharedMemorySize, SMEM_TOTAL);
    }

    Maps maps;
    const cuuint32_t ones[4] = {1, 1, 1, 1};
    auto make = [&](CUtensorMap* map, int rank, void* base, const cuuint64_t* dims, const cuuint64_t* strides,
                    const cuuint32_t* box, CUtensorMapL2promotion promo) {
        encode(map, CU_TENSOR_MAP_DATA_TYPE_BFLOAT16, rank, base, dims, strides, box, ones, CU_TENSOR_MAP_INTERLEAVE_NONE,
               CU_TENSOR_MAP_SWIZZLE_128B, promo, CU_TENSOR_MAP_FLOAT_OOB_FILL_NONE);
    };
    {
        const cuuint64_t dims[4]    = {64, 8, 6, (cuuint64_t)(M / 8)};
        const cuuint64_t strides[3] = {C * 2, 128, 8 * C * 2};
        const cuuint32_t box[4]     = {64, 8, 6, TILE_PIX / 16};
        make(&maps.x, 4, x, dims, strides, box, CU_TENSOR_MAP_L2_PROMOTION_L2_128B);
    }
    {
        const cuuint64_t dims[3]    = {C, C / 2, 2};
        const cuuint64_t strides[2] = {C * 2, C * C};
        const cuuint32_t box[3]     = {64, C / 2, 2};
        make(&maps.w, 3, w, dims, strides, box, CU_TENSOR_MAP_L2_PROMOTION_L2_128B);
    }
    {
        const cuuint64_t dims[2]    = {C, (cuuint64_t)M};
        const cuuint64_t strides[1] = {C * 2};
        const cuuint32_t box[2]     = {64, TILE_PIX};
        make(&maps.out, 2, d_out, dims, strides, box, CU_TENSOR_MAP_L2_PROMOTION_NONE);
    }

    const Tune tune;
    int clusters = sms / 2;
    if (TP(N_STATIC) < 36 && clusters > num_tiles / (int)TP(N_STATIC)) clusters = num_tiles / (int)TP(N_STATIC);
    conv1x1_kernel<<<clusters * 2, THREADS, SMEM_TOTAL>>>((const uint8_t*)x, (const uint8_t*)w, b, (uint32_t)num_tiles,
                                                          (uint32_t)clusters, maps, tune);
}
```

```cpp
#include <cuda_runtime.h>
#include <cuda_bf16.h>
#include <cuda.h>
#include <stdint.h>

#define EARLY_AT 18

#define W_FIRST 2
#define PRE_X 1
#define PRE_D0 200
#define PRE_DT 300
#define PRE_W 64

#define TUNABLES(F) \
    F(EARLY_TILES, 528)    \
    F(EARLY_HEAD, 1188)       \
    F(PM_T0, 0)            \
    F(PM_DT1, 420)         \
    F(PM_E1, 17) \
    F(PM_DT2, 300) \
    F(PM_E2, 20) \
    F(PM_DT3, 820) \
    F(PM_E3, 63) \
    F(PM_DT4, 650) \
    F(PM_E4, 72) \
    F(PM_STAG, 210)        \
    F(LEAD_A, 280)        \
    F(LEAD_F, 500)         \
    F(LEAD_S, 3)           \
    F(LEAD_B, 151)        \
    F(PM_SLACK, 150)    \
    F(EF_TAIL, 500)        \
    F(ST_AT, 2)            \
    F(ST_T0, 6600)         \
    F(ST_STAG, 30)          \
    F(ST_P1, 2030)         \
    F(ST_E1, 9) \
    F(ST_P2, 1965) \
    F(ST_E2, 18) \
    F(ST_P3, 2020) \
    F(ST_SLACK, 400)       \
    F(SW_J, 12)            \
    F(SW_D, 8050)          \
    F(ST_PT, 1500)         \
    F(SW_D1, 3300)         \
    F(ST_PU, 520)          \
    F(SW_K1, 0)            \
    F(SW_K2, 10) \
    F(HOLD_T, 100)         \
    F(X0, 0) \
    F(X1, 0) \
    F(X2, 0) \
    F(X3, 0)

struct Tune {
#define F(n, v) static constexpr uint32_t n = v;
    TUNABLES(F)
#undef F
};
#define TP(n) (Tune::n)

#define TRV(slot, idx, v)
#define TR(slot, idx)
#define TRE(slot, idx)

namespace {

constexpr int C            = 384;
constexpr int TILE_PIX     = 64;
constexpr int STAGES       = 3;
constexpr int STAGE_BYTES  = TILE_PIX * C * 2;
constexpr int HALF_BYTES   = STAGE_BYTES / 2;
constexpr int SLICE_BYTES  = TILE_PIX * 128;
constexpr int W_LINES      = C * C * 2 / 128;
constexpr int NUM_WG       = 3;
constexpr int THREADS      = (NUM_WG + 1) * 128;
constexpr int SMEM_OUT     = STAGES * STAGE_BYTES;
constexpr int SMEM_BAR     = SMEM_OUT + STAGES * HALF_BYTES;
constexpr int SMEM_TOTAL   = SMEM_BAR + 512 + 1024;
constexpr uint32_t SPIN_LIMIT = 1u << 24;
constexpr int BAR_W     = 0;
constexpr int BAR_FULL  = 32;
constexpr int BAR_EMPTY = BAR_FULL + 32;
constexpr int BAR_OFREE = BAR_EMPTY + 32;
constexpr int BAR_OFULL = BAR_OFREE + 32 * STAGES;
constexpr int ISSUED_AT = BAR_OFULL + 32 * STAGES;
constexpr uint64_t EVICT_NORMAL = 0x1000000000000000ull;
constexpr uint64_t EVICT_FIRST  = 0x12F0000000000000ull;

struct Maps {
    CUtensorMap w, x, out;
};

#define ELECT "{\n.reg .pred e;\nelect.sync _|e, 0xffffffff;\n@e "

__device__ __forceinline__ uint32_t smem_u32(const void* p) {
    return (uint32_t)__cvta_generic_to_shared(p);
}
__device__ __forceinline__ void mbar_init_1(uint32_t bar, uint32_t count) {
    asm volatile(ELECT "mbarrier.init.shared::cta.b64 [%0], %1;\n}" ::"r"(bar), "r"(count) : "memory");
}
__device__ __forceinline__ void mbar_expect_tx_1(uint32_t bar, uint32_t bytes) {
    asm volatile(ELECT "mbarrier.arrive.expect_tx.shared::cta.b64 _, [%0], %1;\n}" ::"r"(bar), "r"(bytes) : "memory");
}
__device__ __forceinline__ void mbar_arrive_1(uint32_t bar) {
    asm volatile(ELECT "mbarrier.arrive.shared::cta.b64 _, [%0];\n}" ::"r"(bar) : "memory");
}
__device__ __forceinline__ void mbar_wait(uint32_t bar, uint32_t parity) {
    uint32_t done;
    uint32_t spins = 0;
    do {
        asm volatile(
            "{\n.reg .pred p;\n"
            "mbarrier.try_wait.parity.shared::cta.b64 p, [%1], %2;\n"
            "selp.u32 %0, 1, 0, p;\n}"
            : "=r"(done) : "r"(bar), "r"(parity) : "memory");
    } while (!done && ++spins < SPIN_LIMIT);
}
__device__ __forceinline__ void mbar_wait_w(uint32_t bar, uint32_t parity) {
    mbar_wait(bar, parity);
    __syncwarp();
}
__device__ __forceinline__ bool mbar_test_w(uint32_t bar, uint32_t parity) {
    uint32_t done;
    asm volatile(
        "{\n.reg .pred p;\n"
        "mbarrier.test_wait.parity.shared::cta.b64 p, [%1], %2;\n"
        "selp.u32 %0, 1, 0, p;\n}"
        : "=r"(done) : "r"(bar), "r"(parity) : "memory");
    return __all_sync(0xffffffffu, done);
}
__device__ __forceinline__ void mbar_arrive_cta(uint32_t bar, uint32_t cta) {
    asm volatile(
        "{\n.reg .b32 ra;\n"
        "mapa.shared::cluster.u32 ra, %0, %1;\n"
        "mbarrier.arrive.shared::cluster.b64 _, [ra];\n}"
        ::"r"(bar), "r"(cta) : "memory");
}
__device__ __forceinline__ uint32_t lds32(uint32_t addr) {
    uint32_t v;
    asm volatile("ld.shared.b32 %0, [%1];" : "=r"(v) : "r"(addr) : "memory");
    return v;
}
__device__ __forceinline__ uint32_t uniform(uint32_t v) {
    return __shfl_sync(0xffffffffu, v, 0);
}
__device__ __forceinline__ void sts32(uint32_t addr, uint32_t v) {
    asm volatile("st.shared.b32 [%0], %1;" ::"r"(addr), "r"(v) : "memory");
}
__device__ __forceinline__ void tma_load_w_1(uint32_t dst, const CUtensorMap* map, uint32_t bar, int n) {
    asm volatile(
        ELECT "cp.async.bulk.tensor.3d.shared::cluster.global.mbarrier::complete_tx::bytes [%0], [%1, {%3, %4, %4}], [%2];\n}"
        ::"r"(dst), "l"(map), "r"(bar), "r"(n), "r"(0) : "memory");
}
__device__ __forceinline__ void tma_load_x_1(uint32_t dst, const CUtensorMap* map, uint32_t bar, int group, uint64_t policy) {
    asm volatile(
        ELECT "cp.async.bulk.tensor.4d.shared::cluster.global.mbarrier::complete_tx::bytes.multicast::cluster.L2::cache_hint"
        " [%0], [%1, {%3, %3, %3, %4}], [%2], %5, %6;\n}"
        ::"r"(dst), "l"(map), "r"(bar), "r"(0), "r"(group), "h"((uint16_t)3), "l"(policy) : "memory");
}
__device__ __forceinline__ void tma_store_1(const CUtensorMap* map, uint32_t src, int ch, int pix) {
    asm volatile(
        ELECT "cp.async.bulk.tensor.2d.global.shared::cta.bulk_group [%0, {%2, %3}], [%1];\n}\n"
        "cp.async.bulk.commit_group;"
        ::"l"(map), "r"(src), "r"(ch), "r"(pix) : "memory");
}
template <int N>
__device__ __forceinline__ void stores_read_wait() {
    asm volatile("cp.async.bulk.wait_group.read %0;" ::"n"(N) : "memory");
}
__device__ __forceinline__ void prefetch_map_1(const CUtensorMap* map) {
    asm volatile(ELECT "prefetch.tensormap [%0];\n}" ::"l"(map) : "memory");
}
__device__ __forceinline__ uint32_t timer_ns() {
    uint32_t t;
    asm volatile("mov.u32 %0, %%globaltimer_lo;" : "=r"(t)::"memory");
    return t;
}
__device__ __forceinline__ void cluster_arrive() {
    asm volatile("barrier.cluster.arrive.relaxed.aligned;" ::: "memory");
}
__device__ __forceinline__ void cluster_wait() {
    asm volatile("barrier.cluster.wait.aligned;" ::: "memory");
}
__device__ __forceinline__ void publish_barriers() {
    asm volatile("fence.mbarrier_init.release.cluster;" ::: "memory");
    asm volatile("fence.proxy.async.shared::cta;" ::: "memory");
}

__device__ __forceinline__ void wgmma_rs_n64(float (&d)[32], const uint32_t* a, uint64_t desc, int scale_d) {
    asm volatile(
        "{\n.reg .pred p;\n"
        "setp.ne.b32 p, %37, 0;\n"
        "wgmma.mma_async.sync.aligned.m64n64k16.f32.bf16.bf16 "
        "{%0, %1, %2, %3, %4, %5, %6, %7, %8, %9, %10, %11, %12, %13, %14, %15, "
        "%16, %17, %18, %19, %20, %21, %22, %23, %24, %25, %26, %27, %28, %29, %30, %31}, "
        "{%32, %33, %34, %35}, %36, p, 1, 1, 0;\n}"
        : "+f"(d[0]), "+f"(d[1]), "+f"(d[2]), "+f"(d[3]), "+f"(d[4]), "+f"(d[5]), "+f"(d[6]), "+f"(d[7]),
          "+f"(d[8]), "+f"(d[9]), "+f"(d[10]), "+f"(d[11]), "+f"(d[12]), "+f"(d[13]), "+f"(d[14]), "+f"(d[15]),
          "+f"(d[16]), "+f"(d[17]), "+f"(d[18]), "+f"(d[19]), "+f"(d[20]), "+f"(d[21]), "+f"(d[22]), "+f"(d[23]),
          "+f"(d[24]), "+f"(d[25]), "+f"(d[26]), "+f"(d[27]), "+f"(d[28]), "+f"(d[29]), "+f"(d[30]), "+f"(d[31])
        : "r"(a[0]), "r"(a[1]), "r"(a[2]), "r"(a[3]), "l"(desc), "r"(scale_d));
}

__device__ __forceinline__ uint32_t pack_bias(float lo, float hi, uint32_t bias2) {
    uint32_t r;
    asm("{\n.reg .b32 t;\n"
        "cvt.rn.bf16x2.f32 t, %2, %1;\n"
        "add.rn.bf16x2 %0, t, %3;\n}"
        : "=r"(r) : "f"(lo), "f"(hi), "r"(bias2));
    return r;
}

__device__ __forceinline__ int slice_channel(uint32_t rank, int wg) {
    return (wg * 2 + rank) * 64;
}

struct Consumer {
    uint32_t wreg[96];
    uint32_t bias_lo, bias_hi, st_addr, bars;
    uint64_t desc_base;
    int wg, lane;
};
struct Ring {
    uint32_t s, parity;
    __device__ __forceinline__ void advance() {
        if (++s == STAGES) {
            s = 0;
            parity ^= 1;
        }
    }
};
__device__ __forceinline__ uint32_t w_stage(int wg) {
    return (wg + 1) * STAGE_BYTES + (wg == 2 ? HALF_BYTES : 0);
}

__device__ __forceinline__ void multiply(const Consumer& c, const Ring& r, float (&acc)[32], uint32_t i, bool early) {
    const int next_turn = 4 + (c.wg + 1) % NUM_WG;
    if ((i | c.wg) != 0) asm volatile("bar.sync %0, 256;" ::"r"(4 + c.wg) : "memory");
    TRE(1 + c.wg * 2, i);
    const uint64_t desc = c.desc_base + (uint64_t)(r.s * (STAGE_BYTES >> 4));
    asm volatile("wgmma.fence.sync.aligned;" ::: "memory");
#pragma unroll
    for (int ks = 0; ks < 24; ks++) {
        const uint64_t d = desc + (uint64_t)((ks >> 2) * 64 + (ks & 3) * 2);
        wgmma_rs_n64(acc, &c.wreg[ks * 4], d, ks != 0);
        if (ks + 1 == EARLY_AT && early) asm volatile("bar.arrive %0, 256;" ::"r"(next_turn) : "memory");
    }
    asm volatile("wgmma.commit_group.sync.aligned;" ::: "memory");
    asm volatile("wgmma.wait_group.sync.aligned 0;" ::: "memory");
#pragma unroll
    for (int j = 0; j < 32; j++) asm volatile("" : "+f"(acc[j])::"memory");
    if (!early) asm volatile("bar.arrive %0, 256;" ::"r"(next_turn) : "memory");
    TRE(2 + c.wg * 2, i);
    if (c.lane < 2) mbar_arrive_cta(c.bars + BAR_EMPTY + 8 * r.s, c.lane);
}
__device__ __forceinline__ void write_out(const Consumer& c, const Ring& r, const uint32_t (&v)[16]) {
    const uint32_t obar = c.bars + (r.s * 4 + c.wg) * 8;
    mbar_wait_w(obar + BAR_OFREE, r.parity ^ 1);
    const uint32_t dst = c.st_addr + r.s * HALF_BYTES;
#pragma unroll
    for (int j = 0; j < 4; j++) {
        asm volatile("stmatrix.sync.aligned.m8n8.x4.trans.shared.b16 [%0], {%1, %2, %3, %4};"
                     ::"r"(dst + j * 2048), "r"(v[4 * j]), "r"(v[4 * j + 1]), "r"(v[4 * j + 2]), "r"(v[4 * j + 3]) : "memory");
    }
    asm volatile("fence.proxy.async.shared::cta;" ::: "memory");
    __syncwarp();
    mbar_arrive_1(obar + BAR_OFULL);
}

template <int N>
__device__ __forceinline__ void hand_back(uint32_t& open) {
    if (open != 0) {
        stores_read_wait<N>();
        mbar_arrive_1(open);
        open = 0;
    }
}

__global__ void __cluster_dims__(2, 1, 1) __launch_bounds__(THREADS, 1)
conv1x1_kernel(const uint8_t* __restrict__ x_raw,
               const uint8_t* __restrict__ w_raw,
               const uint16_t* __restrict__ bias,
               uint32_t num_tiles,
               uint32_t num_clusters,
               const __grid_constant__ Maps maps,
               const __grid_constant__ Tune tune) {
    if (threadIdx.x < 96) {
        const uint32_t line = blockIdx.x % (W_LINES / PRE_W) * PRE_W + threadIdx.x;
        if (threadIdx.x < PRE_W) asm volatile("prefetch.global.L2 [%0];" ::"l"(w_raw + line * 128) : "memory");
    } else if (threadIdx.x < 128) {
        prefetch_map_1(&maps.w);
        prefetch_map_1(&maps.x);
    }
    if (threadIdx.x < NUM_WG * 128) cluster_arrive();
    if (threadIdx.x >= 128 && threadIdx.x < 128 + PRE_X * 96) {
        const uint8_t* p = x_raw + (size_t)blockIdx.x * HALF_BYTES + (threadIdx.x - 128) * 128;
        if (PRE_D0 + PRE_DT != 0) {
            const uint32_t wait = PRE_D0 + ((threadIdx.x - 128) >> 5) * PRE_DT;
            const uint32_t c0 = clock();
            while (clock() - c0 < wait) {}
        }
        asm volatile("prefetch.global.L2 [%0];" ::"l"(p) : "memory");
    }
    extern __shared__ uint8_t smem_raw[];
    const uint32_t smem = (smem_u32(smem_raw) + 1023u) & ~1023u;
    const uint32_t bars = smem + SMEM_BAR;

    const int warp = uniform(threadIdx.x >> 5);
    const int lane = threadIdx.x & 31;
    const uint32_t rank         = blockIdx.x & 1;
    const uint32_t cluster      = blockIdx.x >> 1;

    if (warp < NUM_WG * 4) {
        const int wg = warp >> 2;
        const int wq = warp & 3;
        asm volatile("setmaxnreg.inc.sync.aligned.u32 160;");
        Consumer c;
        c.wg = wg;
        c.lane = lane;
        c.bars = bars;
        c.bias_lo = bias[slice_channel(rank, wg) + wq * 16 + (lane >> 2)] * 0x10001u;
        c.bias_hi = bias[slice_channel(rank, wg) + wq * 16 + (lane >> 2) + 8] * 0x10001u;

        cluster_wait();
        TRE(1 + wg, 63);
        mbar_wait_w(bars + BAR_W + 8 * wg, 0);
        TRE(4 + wg, 63);
        {
            const int r = lane & 7, m = lane >> 3;
            const uint32_t base = smem + w_stage(wg) + ((m >> 1) * 8 + r) * 128 + (((2 * wq + (m & 1)) ^ r) << 4);
#pragma unroll
            for (int ks = 0; ks < 24; ks++) {
                asm volatile("ldmatrix.sync.aligned.m8n8.x4.trans.shared.b16 {%0, %1, %2, %3}, [%4];"
                             : "=r"(c.wreg[ks * 4 + 0]), "=r"(c.wreg[ks * 4 + 1]), "=r"(c.wreg[ks * 4 + 2]), "=r"(c.wreg[ks * 4 + 3])
                             : "r"(base + ks * 2048) : "memory");
            }
        }
        uint32_t dep = 0;
#pragma unroll
        for (int ks = 0; ks < 24; ks++) dep ^= c.wreg[ks * 4];
        dep &= num_tiles >> 31;
        __syncwarp();
        if (lane < 6 && wg < 2) mbar_arrive_cta(bars + BAR_EMPTY + 8 * (wg + 1) + dep, lane & 1);
        TRE(1 + wg, 60);

        c.st_addr = smem + SMEM_OUT + wg * SLICE_BYTES + ((lane >> 4) * 8 + (lane & 7)) * 128 + (((2 * wq + ((lane >> 3) & 1)) ^ (lane & 7)) << 4);
        c.desc_base = (uint64_t)((smem & 0x3FFFF) >> 4) | ((uint64_t)1 << 16) | ((uint64_t)(6144 >> 4) << 32) | ((uint64_t)1 << 62);

        float acc[32];
        uint32_t packed[16];
        Ring r = {0, uniform(dep)}, o = r;
        bool held = false;
        for (uint32_t i = 0, id = cluster; id < num_tiles; i++, id += num_clusters, r.advance()) {
            mbar_wait(bars + BAR_FULL + 8 * r.s, r.parity);
            multiply(c, r, acc, i, id + TP(EARLY_TILES) >= num_tiles || id + 1 <= TP(EARLY_HEAD));
            if (held) write_out(c, o, packed);
            o = r;
#pragma unroll
            for (int j = 0; j < 16; j++) packed[j] = pack_bias(acc[2 * j], acc[2 * j + 1], j & 1 ? c.bias_hi : c.bias_lo);
            held = id + TP(HOLD_T) < num_tiles && !mbar_test_w(bars + BAR_OFREE + (o.s * 4 + wg) * 8, o.parity ^ 1);
            if (!held) write_out(c, o, packed);
            TRE(8 + wg, i);
        }
        if (held) write_out(c, o, packed);
        if (wg == 0) asm volatile("bar.sync 4, 256;" ::: "memory");
        TRE(1 + wg, 62);
    } else {
        asm volatile("setmaxnreg.dec.sync.aligned.u32 32;");
        if (warp == NUM_WG * 4) {
#pragma unroll
            for (int j = 0; j < NUM_WG; j++) mbar_init_1(bars + BAR_W + 8 * j, 1);
            publish_barriers();
            cluster_arrive();
#pragma unroll
            for (int j = 0; j < NUM_WG; j++) {
                if (j == W_FIRST) {
                    cluster_wait();
                    TR(0, 0);
                    mbar_expect_tx_1(bars + BAR_FULL, STAGE_BYTES);
                    tma_load_x_1(smem + rank * HALF_BYTES, &maps.x, bars + BAR_FULL, cluster * 8 + rank * 4, EVICT_NORMAL);
                }
                mbar_expect_tx_1(bars + BAR_W + 8 * j, STAGE_BYTES);
                tma_load_w_1(smem + w_stage(j), &maps.w, bars + BAR_W + 8 * j, slice_channel(rank, j));
                if (j == 0) TR(2, 61);
            }
            Ring r = {1, 0};
#pragma unroll 1
            for (uint32_t id = cluster + num_clusters; id < num_tiles; id += num_clusters, r.advance()) {
                mbar_wait_w(bars + BAR_EMPTY + 8 * r.s, r.parity ^ (r.s == 0));
                sts32(bars + ISSUED_AT, id);
                TR(0, id / num_clusters);
                TRV(15, id / num_clusters, id);
                const uint32_t full = bars + BAR_FULL + 8 * r.s;
                mbar_expect_tx_1(full, STAGE_BYTES);
                tma_load_x_1(smem + r.s * STAGE_BYTES + rank * HALF_BYTES, &maps.x, full, id * 8 + rank * 4,
                             id + TP(EF_TAIL) >= num_tiles ? EVICT_FIRST : EVICT_NORMAL);
            }
#pragma unroll 1
            for (int k = 0; k < STAGES; k++, r.advance()) mbar_wait_w(bars + BAR_EMPTY + 8 * r.s, r.parity ^ (r.s == 0));
        } else if (warp == NUM_WG * 4 + 1) {
#pragma unroll
            for (int s = 0; s < STAGES; s++) {
                mbar_init_1(bars + BAR_FULL + 8 * s, 1);
                mbar_init_1(bars + BAR_EMPTY + 8 * s, NUM_WG * 4 * 2);
            }
            publish_barriers();
            cluster_arrive();
            TR(0, 61);
            cluster_wait();
            prefetch_map_1(&maps.out);
        } else if (warp == NUM_WG * 4 + 2) {
            uint32_t due = timer_ns() + TP(ST_T0) + cluster * TP(ST_STAG) - TP(ST_P1);
#pragma unroll
            for (int b = 0; b < STAGES; b++) {
#pragma unroll
                for (int w = 0; w < NUM_WG; w++) {
                    mbar_init_1(bars + BAR_OFREE + b * 32 + w * 8, 1);
                    mbar_init_1(bars + BAR_OFULL + b * 32 + w * 8, 4);
                }
            }
            publish_barriers();
            cluster_arrive();
            cluster_wait();
            const uint32_t mark = num_tiles / num_clusters - TP(SW_J);
            const int behind = cluster < num_tiles % num_clusters ? cluster : cluster - num_clusters;
            const float stage1 = (float)((int)TP(SW_D1) + behind * ((int)TP(SW_K1) - (int)TP(SW_K2)));
            uint32_t open = 0, t_end = 0;
            Ring o = {0, 0};
#pragma unroll 1
            for (uint32_t j = 0, id = cluster; id < num_tiles; j++, id += num_clusters, o.advance()) {
                const uint32_t parity = o.parity;
                const uint32_t obar = bars + o.s * 32;
                if (!mbar_test_w(obar + BAR_OFULL, parity)) {
                    hand_back<0>(open);
                    mbar_wait_w(obar + BAR_OFULL, parity);
                }
                const uint32_t src = smem + SMEM_OUT + o.s * HALF_BYTES;
                const uint32_t period = j <= TP(ST_E1) ? TP(ST_P1) : j <= TP(ST_E2) ? TP(ST_P2) : TP(ST_P3);
                uint32_t now = timer_ns();
                if (j >= TP(ST_AT)) {
                    if (j <= mark || (int32_t)(due + period - t_end) <= 0) {
                        due += period;
                    } else {
                        float t = (float)(int32_t)(due - t_end), rest = 1.f;
                        if (t < 0.f) {
                            rest += __fdividef(t, (float)period);
                            t = 0.f;
                        }
                        const float room = stage1 - t;
                        if (room >= rest * (float)TP(ST_PT)) {
                            t += rest * (float)TP(ST_PT);
                        } else {
                            if (room > 0.f) {
                                rest -= __fdividef(room, (float)TP(ST_PT));
                                t += room;
                            }
                            t += rest * (float)TP(ST_PU);
                        }
                        due = t_end + (int32_t)t;
                    }
                    if ((int32_t)(now - due) < 0) hand_back<0>(open);
#pragma unroll 1
                    for (uint32_t spins = 0; (int32_t)(now - due) < 0 && spins < SPIN_LIMIT; spins++) {
                        __nanosleep(20);
                        now = timer_ns();
                    }
                }
                if (j >= TP(ST_AT) && (int32_t)(now - TP(ST_SLACK) - due) > 0) due = now - TP(ST_SLACK);
                if (j == mark) t_end = due - cluster * TP(ST_STAG) + TP(SW_D) - behind * (int)TP(SW_K1);
                const bool whole = mbar_test_w(obar + BAR_OFULL + 8, parity) && mbar_test_w(obar + BAR_OFULL + 16, parity);
                if (whole) {
                    TR(11, j);
#pragma unroll
                    for (int w = 0; w < NUM_WG; w++) tma_store_1(&maps.out, src + w * SLICE_BYTES, slice_channel(rank, w), id * TILE_PIX);
                    TR(12, j);
                    TR(13, j);
                    hand_back<3>(open);
                    stores_read_wait<2>();
                    mbar_arrive_1(obar + BAR_OFREE);
                    stores_read_wait<1>();
                    mbar_arrive_1(obar + BAR_OFREE + 8);
                    open = obar + BAR_OFREE + 16;
                } else {
#pragma unroll 1
                    for (uint32_t w = 0; w < NUM_WG; w++) {
                        if (!mbar_test_w(obar + BAR_OFULL + w * 8, parity)) {
                            hand_back<0>(open);
                            mbar_wait_w(obar + BAR_OFULL + w * 8, parity);
                        }
                        TR(11 + w, j);
                        tma_store_1(&maps.out, src + w * SLICE_BYTES, slice_channel(rank, w), id * TILE_PIX);
                        hand_back<1>(open);
                        open = obar + BAR_OFREE + w * 8;
                    }
                }
            }
            stores_read_wait<0>();
            TR(4, 62);
        } else {
            uint32_t due = timer_ns() + TP(PM_T0) + (blockIdx.x & 3) * TP(PM_STAG);
            sts32(bars + ISSUED_AT, 0);
            cluster_arrive();
            const uint32_t step = num_clusters / 2;
#pragma unroll 1
            for (uint32_t piece = PRE_X; piece < TP(PM_E4); piece++) {
                const uint32_t t = cluster + piece / 2 * num_clusters;
                if (t >= num_tiles) break;
                uint32_t now;
#pragma unroll 1
                for (uint32_t spins = 0; spins < 16384; spins++) {
                    const uint32_t issued = uniform(lds32(bars + ISSUED_AT));
                    now = timer_ns();
                    const int lead = max((int)TP(LEAD_B), (int)TP(LEAD_A) - (max((int)issued - (int)TP(LEAD_F), 0) * (int)TP(LEAD_S) >> 4));
                    if ((int32_t)(now - due) >= 0 && cluster + piece * step <= issued + lead) break;
                    __nanosleep(20);
                }
                if ((int32_t)(now - TP(PM_SLACK) - due) > 0) due = now - TP(PM_SLACK);
                due += piece < TP(PM_E1) ? TP(PM_DT1) : piece < TP(PM_E2) ? TP(PM_DT2) : piece < TP(PM_E3) ? TP(PM_DT3) : TP(PM_DT4);
                const uint8_t* p = x_raw + (size_t)t * STAGE_BYTES + rank * HALF_BYTES + (piece % 2) * 12288 + lane * 128;
#pragma unroll
                for (int k = 0; k < 3; k++) asm volatile("prefetch.global.L2 [%0];" ::"l"(p + k * 4096) : "memory");
                if (piece % 2 == 0) TR(14, piece / 2);
            }
            cluster_wait();
        }
    }
}

typedef CUresult (*EncodeTiledFn)(CUtensorMap*, CUtensorMapDataType, cuuint32_t, void*, const cuuint64_t*,
                                  const cuuint64_t*, const cuuint32_t*, const cuuint32_t*, CUtensorMapInterleave,
                                  CUtensorMapSwizzle, CUtensorMapL2promotion, CUtensorMapFloatOOBfill);

}

extern "C" void kernel_launch(void* const* d_in, const int* in_sizes, int n_in, void* d_out, int out_size) {
    (void)n_in;
    (void)out_size;
    void* x = d_in[0];
    void* w = d_in[1];
    const uint16_t* b = (const uint16_t*)d_in[2];
    const int M = in_sizes[0] / C;
    const int num_tiles = M / TILE_PIX;

    static EncodeTiledFn encode = nullptr;
    static int sms = 0;
    if (!encode) {
        void* fn = nullptr;
        cudaDriverEntryPointQueryResult q;
        cudaGetDriverEntryPoint("cuTensorMapEncodeTiled", &fn, cudaEnableDefault, &q);
        encode = (EncodeTiledFn)fn;
        cudaDeviceGetAttribute(&sms, cudaDevAttrMultiProcessorCount, 0);
        cudaFuncSetAttribute(conv1x1_kernel, cudaFuncAttributeMaxDynamicSharedMemorySize, SMEM_TOTAL);
    }

    Maps maps;
    const cuuint32_t ones[4] = {1, 1, 1, 1};
    auto make = [&](CUtensorMap* map, int rank, void* base, const cuuint64_t* dims, const cuuint64_t* strides,
                    const cuuint32_t* box, CUtensorMapL2promotion promo) {
        encode(map, CU_TENSOR_MAP_DATA_TYPE_BFLOAT16, rank, base, dims, strides, box, ones, CU_TENSOR_MAP_INTERLEAVE_NONE,
               CU_TENSOR_MAP_SWIZZLE_128B, promo, CU_TENSOR_MAP_FLOAT_OOB_FILL_NONE);
    };
    {
        const cuuint64_t dims[4]    = {64, 8, 6, (cuuint64_t)(M / 8)};
        const cuuint64_t strides[3] = {C * 2, 128, 8 * C * 2};
        const cuuint32_t box[4]     = {64, 8, 6, TILE_PIX / 16};
        make(&maps.x, 4, x, dims, strides, box, CU_TENSOR_MAP_L2_PROMOTION_L2_128B);
    }
    {
        const cuuint64_t dims[3]    = {C, C / 2, 2};
        const cuuint64_t strides[2] = {C * 2, C * C};
        const cuuint32_t box[3]     = {64, C / 2, 2};
        make(&maps.w, 3, w, dims, strides, box, CU_TENSOR_MAP_L2_PROMOTION_L2_128B);
    }
    {
        const cuuint64_t dims[2]    = {C, (cuuint64_t)M};
        const cuuint64_t strides[1] = {C * 2};
        const cuuint32_t box[2]     = {64, TILE_PIX};
        make(&maps.out, 2, d_out, dims, strides, box, CU_TENSOR_MAP_L2_PROMOTION_NONE);
    }

    const Tune tune;
    int clusters = sms / 2;
    if (clusters > num_tiles) clusters = num_tiles;
    conv1x1_kernel<<<clusters * 2, THREADS, SMEM_TOTAL>>>((const uint8_t*)x, (const uint8_t*)w, b, (uint32_t)num_tiles,
                                                          (uint32_t)clusters, maps, tune);
}
```

```cpp
#include <cuda_runtime.h>
#include <cuda_bf16.h>
#include <cuda.h>
#include <stdint.h>

#define EARLY_AT 18

#define W_FIRST 2
#define PRE_X 1
#define PRE_D0 200
#define PRE_DT 300
#define PRE_W 64

#define TUNABLES(F) \
    F(EARLY_TILES, 528)    \
    F(EARLY_HEAD, 1584)       \
    F(PM_T0, 0)            \
    F(PM_DT1, 455)         \
    F(PM_E1, 17) \
    F(PM_DT2, 400) \
    F(PM_E2, 21) \
    F(PM_DT3, 820) \
    F(PM_E3, 63) \
    F(PM_DT4, 650) \
    F(PM_E4, 72) \
    F(PM_STAG, 210)        \
    F(LEAD_A, 280)        \
    F(LEAD_F, 500)         \
    F(LEAD_S, 3)           \
    F(LEAD_B, 162)        \
    F(PM_SLACK, 600)    \
    F(EF_TAIL, 500)        \
    F(ST_AT, 2)            \
    F(ST_T0, 6600)         \
    F(ST_STAG, 30)          \
    F(ST_P1, 2030)         \
    F(ST_E1, 9) \
    F(ST_P2, 1965) \
    F(ST_E2, 18) \
    F(ST_P3, 2020) \
    F(ST_SLACK, 400)       \
    F(SW_J, 12)            \
    F(SW_D, 7800)          \
    F(ST_PT, 1680)         \
    F(SW_D1, 3300)         \
    F(ST_PU, 460)          \
    F(SW_K1, 0)            \
    F(SW_K2, 10) \
    F(HOLD_T, 100)         \
    F(X0, 0) \
    F(X1, 0) \
    F(X2, 0) \
    F(X3, 0)

struct Tune {
#define F(n, v) static constexpr uint32_t n = v;
    TUNABLES(F)
#undef F
};
#define TP(n) (Tune::n)

#define TRV(slot, idx, v)
#define TR(slot, idx)
#define TRE(slot, idx)

namespace {

constexpr int C            = 384;
constexpr int TILE_PIX     = 64;
constexpr int STAGES       = 3;
constexpr int STAGE_BYTES  = TILE_PIX * C * 2;
constexpr int HALF_BYTES   = STAGE_BYTES / 2;
constexpr int SLICE_BYTES  = TILE_PIX * 128;
constexpr int W_LINES      = C * C * 2 / 128;
constexpr int NUM_WG       = 3;
constexpr int THREADS      = (NUM_WG + 1) * 128;
constexpr int SMEM_OUT     = STAGES * STAGE_BYTES;
constexpr int SMEM_BAR     = SMEM_OUT + STAGES * HALF_BYTES;
constexpr int SMEM_TOTAL   = SMEM_BAR + 512 + 1024;
constexpr uint32_t SPIN_LIMIT = 1u << 24;
constexpr int BAR_W     = 0;
constexpr int BAR_FULL  = 32;
constexpr int BAR_EMPTY = BAR_FULL + 32;
constexpr int BAR_OFREE = BAR_EMPTY + 32;
constexpr int BAR_OFULL = BAR_OFREE + 32 * STAGES;
constexpr int ISSUED_AT = BAR_OFULL + 32 * STAGES;
constexpr uint64_t EVICT_NORMAL = 0x1000000000000000ull;
constexpr uint64_t EVICT_FIRST  = 0x12F0000000000000ull;

struct Maps {
    CUtensorMap w, x, out;
};

#define ELECT "{\n.reg .pred e;\nelect.sync _|e, 0xffffffff;\n@e "

__device__ __forceinline__ uint32_t smem_u32(const void* p) {
    return (uint32_t)__cvta_generic_to_shared(p);
}
__device__ __forceinline__ void mbar_init_1(uint32_t bar, uint32_t count) {
    asm volatile(ELECT "mbarrier.init.shared::cta.b64 [%0], %1;\n}" ::"r"(bar), "r"(count) : "memory");
}
__device__ __forceinline__ void mbar_expect_tx_1(uint32_t bar, uint32_t bytes) {
    asm volatile(ELECT "mbarrier.arrive.expect_tx.shared::cta.b64 _, [%0], %1;\n}" ::"r"(bar), "r"(bytes) : "memory");
}
__device__ __forceinline__ void mbar_arrive_1(uint32_t bar) {
    asm volatile(ELECT "mbarrier.arrive.shared::cta.b64 _, [%0];\n}" ::"r"(bar) : "memory");
}
__device__ __forceinline__ void mbar_wait(uint32_t bar, uint32_t parity) {
    uint32_t done;
    uint32_t spins = 0;
    do {
        asm volatile(
            "{\n.reg .pred p;\n"
            "mbarrier.try_wait.parity.shared::cta.b64 p, [%1], %2;\n"
            "selp.u32 %0, 1, 0, p;\n}"
            : "=r"(done) : "r"(bar), "r"(parity) : "memory");
    } while (!done && ++spins < SPIN_LIMIT);
}
__device__ __forceinline__ void mbar_wait_w(uint32_t bar, uint32_t parity) {
    mbar_wait(bar, parity);
    __syncwarp();
}
__device__ __forceinline__ bool mbar_test_w(uint32_t bar, uint32_t parity) {
    uint32_t done;
    asm volatile(
        "{\n.reg .pred p;\n"
        "mbarrier.test_wait.parity.shared::cta.b64 p, [%1], %2;\n"
        "selp.u32 %0, 1, 0, p;\n}"
        : "=r"(done) : "r"(bar), "r"(parity) : "memory");
    return __all_sync(0xffffffffu, done);
}
__device__ __forceinline__ void mbar_arrive_cta(uint32_t bar, uint32_t cta) {
    asm volatile(
        "{\n.reg .b32 ra;\n"
        "mapa.shared::cluster.u32 ra, %0, %1;\n"
        "mbarrier.arrive.shared::cluster.b64 _, [ra];\n}"
        ::"r"(bar), "r"(cta) : "memory");
}
__device__ __forceinline__ uint32_t lds32(uint32_t addr) {
    uint32_t v;
    asm volatile("ld.shared.b32 %0, [%1];" : "=r"(v) : "r"(addr) : "memory");
    return v;
}
__device__ __forceinline__ uint32_t uniform(uint32_t v) {
    return __shfl_sync(0xffffffffu, v, 0);
}
__device__ __forceinline__ void sts32(uint32_t addr, uint32_t v) {
    asm volatile("st.shared.b32 [%0], %1;" ::"r"(addr), "r"(v) : "memory");
}
__device__ __forceinline__ void tma_load_w_1(uint32_t dst, const CUtensorMap* map, uint32_t bar, int n) {
    asm volatile(
        ELECT "cp.async.bulk.tensor.3d.shared::cluster.global.mbarrier::complete_tx::bytes [%0], [%1, {%3, %4, %4}], [%2];\n}"
        ::"r"(dst), "l"(map), "r"(bar), "r"(n), "r"(0) : "memory");
}
__device__ __forceinline__ void tma_load_x_1(uint32_t dst, const CUtensorMap* map, uint32_t bar, int group, uint64_t policy) {
    asm volatile(
        ELECT "cp.async.bulk.tensor.4d.shared::cluster.global.mbarrier::complete_tx::bytes.multicast::cluster.L2::cache_hint"
        " [%0], [%1, {%3, %3, %3, %4}], [%2], %5, %6;\n}"
        ::"r"(dst), "l"(map), "r"(bar), "r"(0), "r"(group), "h"((uint16_t)3), "l"(policy) : "memory");
}
__device__ __forceinline__ void tma_store_1(const CUtensorMap* map, uint32_t src, int ch, int pix) {
    asm volatile(
        ELECT "cp.async.bulk.tensor.2d.global.shared::cta.bulk_group [%0, {%2, %3}], [%1];\n}\n"
        "cp.async.bulk.commit_group;"
        ::"l"(map), "r"(src), "r"(ch), "r"(pix) : "memory");
}
template <int N>
__device__ __forceinline__ void stores_read_wait() {
    asm volatile("cp.async.bulk.wait_group.read %0;" ::"n"(N) : "memory");
}
__device__ __forceinline__ void prefetch_map_1(const CUtensorMap* map) {
    asm volatile(ELECT "prefetch.tensormap [%0];\n}" ::"l"(map) : "memory");
}
__device__ __forceinline__ uint32_t timer_ns() {
    uint32_t t;
    asm volatile("mov.u32 %0, %%globaltimer_lo;" : "=r"(t)::"memory");
    return t;
}
__device__ __forceinline__ void cluster_arrive() {
    asm volatile("barrier.cluster.arrive.relaxed.aligned;" ::: "memory");
}
__device__ __forceinline__ void cluster_wait() {
    asm volatile("barrier.cluster.wait.aligned;" ::: "memory");
}
__device__ __forceinline__ void publish_barriers() {
    asm volatile("fence.mbarrier_init.release.cluster;" ::: "memory");
    asm volatile("fence.proxy.async.shared::cta;" ::: "memory");
}

__device__ __forceinline__ void wgmma_rs_n64(float (&d)[32], const uint32_t* a, uint64_t desc, int scale_d) {
    asm volatile(
        "{\n.reg .pred p;\n"
        "setp.ne.b32 p, %37, 0;\n"
        "wgmma.mma_async.sync.aligned.m64n64k16.f32.bf16.bf16 "
        "{%0, %1, %2, %3, %4, %5, %6, %7, %8, %9, %10, %11, %12, %13, %14, %15, "
        "%16, %17, %18, %19, %20, %21, %22, %23, %24, %25, %26, %27, %28, %29, %30, %31}, "
        "{%32, %33, %34, %35}, %36, p, 1, 1, 0;\n}"
        : "+f"(d[0]), "+f"(d[1]), "+f"(d[2]), "+f"(d[3]), "+f"(d[4]), "+f"(d[5]), "+f"(d[6]), "+f"(d[7]),
          "+f"(d[8]), "+f"(d[9]), "+f"(d[10]), "+f"(d[11]), "+f"(d[12]), "+f"(d[13]), "+f"(d[14]), "+f"(d[15]),
          "+f"(d[16]), "+f"(d[17]), "+f"(d[18]), "+f"(d[19]), "+f"(d[20]), "+f"(d[21]), "+f"(d[22]), "+f"(d[23]),
          "+f"(d[24]), "+f"(d[25]), "+f"(d[26]), "+f"(d[27]), "+f"(d[28]), "+f"(d[29]), "+f"(d[30]), "+f"(d[31])
        : "r"(a[0]), "r"(a[1]), "r"(a[2]), "r"(a[3]), "l"(desc), "r"(scale_d));
}

__device__ __forceinline__ uint32_t pack_bias(float lo, float hi, uint32_t bias2) {
    uint32_t r;
    asm("{\n.reg .b32 t;\n"
        "cvt.rn.bf16x2.f32 t, %2, %1;\n"
        "add.rn.bf16x2 %0, t, %3;\n}"
        : "=r"(r) : "f"(lo), "f"(hi), "r"(bias2));
    return r;
}

__device__ __forceinline__ int slice_channel(uint32_t rank, int wg) {
    return (wg * 2 + rank) * 64;
}

struct Consumer {
    uint32_t wreg[96];
    uint32_t bias_lo, bias_hi, st_addr, bars;
    uint64_t desc_base;
    int wg, lane;
};
struct Ring {
    uint32_t s, parity;
    __device__ __forceinline__ void advance() {
        if (++s == STAGES) {
            s = 0;
            parity ^= 1;
        }
    }
};
__device__ __forceinline__ uint32_t w_stage(int wg) {
    return (wg + 1) * STAGE_BYTES + (wg == 2 ? HALF_BYTES : 0);
}

__device__ __forceinline__ void multiply(const Consumer& c, const Ring& r, float (&acc)[32], uint32_t i, bool early) {
    const int next_turn = 4 + (c.wg + 1) % NUM_WG;
    if ((i | c.wg) != 0) asm volatile("bar.sync %0, 256;" ::"r"(4 + c.wg) : "memory");
    TRE(1 + c.wg * 2, i);
    const uint64_t desc = c.desc_base + (uint64_t)(r.s * (STAGE_BYTES >> 4));
    asm volatile("wgmma.fence.sync.aligned;" ::: "memory");
#pragma unroll
    for (int ks = 0; ks < 24; ks++) {
        const uint64_t d = desc + (uint64_t)((ks >> 2) * 64 + (ks & 3) * 2);
        wgmma_rs_n64(acc, &c.wreg[ks * 4], d, ks != 0);
        if (ks + 1 == EARLY_AT && early) asm volatile("bar.arrive %0, 256;" ::"r"(next_turn) : "memory");
    }
    asm volatile("wgmma.commit_group.sync.aligned;" ::: "memory");
    asm volatile("wgmma.wait_group.sync.aligned 0;" ::: "memory");
#pragma unroll
    for (int j = 0; j < 32; j++) asm volatile("" : "+f"(acc[j])::"memory");
    if (!early) asm volatile("bar.arrive %0, 256;" ::"r"(next_turn) : "memory");
    TRE(2 + c.wg * 2, i);
    if (c.lane < 2) mbar_arrive_cta(c.bars + BAR_EMPTY + 8 * r.s, c.lane);
}
__device__ __forceinline__ void write_out(const Consumer& c, const Ring& r, const uint32_t (&v)[16]) {
    const uint32_t obar = c.bars + (r.s * 4 + c.wg) * 8;
    mbar_wait_w(obar + BAR_OFREE, r.parity ^ 1);
    const uint32_t dst = c.st_addr + r.s * HALF_BYTES;
#pragma unroll
    for (int j = 0; j < 4; j++) {
        asm volatile("stmatrix.sync.aligned.m8n8.x4.trans.shared.b16 [%0], {%1, %2, %3, %4};"
                     ::"r"(dst + j * 2048), "r"(v[4 * j]), "r"(v[4 * j + 1]), "r"(v[4 * j + 2]), "r"(v[4 * j + 3]) : "memory");
    }
    asm volatile("fence.proxy.async.shared::cta;" ::: "memory");
    __syncwarp();
    mbar_arrive_1(obar + BAR_OFULL);
}

template <int N>
__device__ __forceinline__ void hand_back(uint32_t& open) {
    if (open != 0) {
        stores_read_wait<N>();
        mbar_arrive_1(open);
        open = 0;
    }
}

__global__ void __cluster_dims__(2, 1, 1) __launch_bounds__(THREADS, 1)
conv1x1_kernel(const uint8_t* __restrict__ x_raw,
               const uint8_t* __restrict__ w_raw,
               const uint16_t* __restrict__ bias,
               uint32_t num_tiles,
               uint32_t num_clusters,
               const __grid_constant__ Maps maps,
               const __grid_constant__ Tune tune) {
    if (threadIdx.x < 96) {
        const uint32_t line = blockIdx.x % (W_LINES / PRE_W) * PRE_W + threadIdx.x;
        if (threadIdx.x < PRE_W) asm volatile("prefetch.global.L2 [%0];" ::"l"(w_raw + line * 128) : "memory");
    } else if (threadIdx.x < 128) {
        prefetch_map_1(&maps.w);
        prefetch_map_1(&maps.x);
    }
    if (threadIdx.x < NUM_WG * 128) cluster_arrive();
    if (threadIdx.x >= 128 && threadIdx.x < 128 + PRE_X * 96) {
        const uint8_t* p = x_raw + (size_t)blockIdx.x * HALF_BYTES + (threadIdx.x - 128) * 128;
        if (PRE_D0 + PRE_DT != 0) {
            const uint32_t wait = PRE_D0 + ((threadIdx.x - 128) >> 5) * PRE_DT;
            const uint32_t c0 = clock();
            while (clock() - c0 < wait) {}
        }
        asm volatile("prefetch.global.L2 [%0];" ::"l"(p) : "memory");
    }
    extern __shared__ uint8_t smem_raw[];
    const uint32_t smem = (smem_u32(smem_raw) + 1023u) & ~1023u;
    const uint32_t bars = smem + SMEM_BAR;

    const int warp = uniform(threadIdx.x >> 5);
    const int lane = threadIdx.x & 31;
    const uint32_t rank         = blockIdx.x & 1;
    const uint32_t cluster      = blockIdx.x >> 1;

    if (warp < NUM_WG * 4) {
        const int wg = warp >> 2;
        const int wq = warp & 3;
        asm volatile("setmaxnreg.inc.sync.aligned.u32 160;");
        Consumer c;
        c.wg = wg;
        c.lane = lane;
        c.bars = bars;
        c.bias_lo = bias[slice_channel(rank, wg) + wq * 16 + (lane >> 2)] * 0x10001u;
        c.bias_hi = bias[slice_channel(rank, wg) + wq * 16 + (lane >> 2) + 8] * 0x10001u;

        cluster_wait();
        TRE(1 + wg, 63);
        mbar_wait_w(bars + BAR_W + 8 * wg, 0);
        TRE(4 + wg, 63);
        {
            const int r = lane & 7, m = lane >> 3;
            const uint32_t base = smem + w_stage(wg) + ((m >> 1) * 8 + r) * 128 + (((2 * wq + (m & 1)) ^ r) << 4);
#pragma unroll
            for (int ks = 0; ks < 24; ks++) {
                asm volatile("ldmatrix.sync.aligned.m8n8.x4.trans.shared.b16 {%0, %1, %2, %3}, [%4];"
                             : "=r"(c.wreg[ks * 4 + 0]), "=r"(c.wreg[ks * 4 + 1]), "=r"(c.wreg[ks * 4 + 2]), "=r"(c.wreg[ks * 4 + 3])
                             : "r"(base + ks * 2048) : "memory");
            }
        }
        uint32_t dep = 0;
#pragma unroll
        for (int ks = 0; ks < 24; ks++) dep ^= c.wreg[ks * 4];
        dep &= num_tiles >> 31;
        __syncwarp();
        if (lane < 6 && wg < 2) mbar_arrive_cta(bars + BAR_EMPTY + 8 * (wg + 1) + dep, lane & 1);
        TRE(1 + wg, 60);

        c.st_addr = smem + SMEM_OUT + wg * SLICE_BYTES + ((lane >> 4) * 8 + (lane & 7)) * 128 + (((2 * wq + ((lane >> 3) & 1)) ^ (lane & 7)) << 4);
        c.desc_base = (uint64_t)((smem & 0x3FFFF) >> 4) | ((uint64_t)1 << 16) | ((uint64_t)(6144 >> 4) << 32) | ((uint64_t)1 << 62);

        float acc[32];
        uint32_t packed[16];
        Ring r = {0, uniform(dep)}, o = r;
        bool held = false;
        for (uint32_t i = 0, id = cluster; id < num_tiles; i++, id += num_clusters, r.advance()) {
            mbar_wait(bars + BAR_FULL + 8 * r.s, r.parity);
            multiply(c, r, acc, i, id + TP(EARLY_TILES) >= num_tiles || id + 1 <= TP(EARLY_HEAD));
            if (held) write_out(c, o, packed);
            o = r;
#pragma unroll
            for (int j = 0; j < 16; j++) packed[j] = pack_bias(acc[2 * j], acc[2 * j + 1], j & 1 ? c.bias_hi : c.bias_lo);
            held = id + TP(HOLD_T) < num_tiles && !mbar_test_w(bars + BAR_OFREE + (o.s * 4 + wg) * 8, o.parity ^ 1);
            if (!held) write_out(c, o, packed);
            TRE(8 + wg, i);
        }
        if (held) write_out(c, o, packed);
        if (wg == 0) asm volatile("bar.sync 4, 256;" ::: "memory");
        TRE(1 + wg, 62);
    } else {
        asm volatile("setmaxnreg.dec.sync.aligned.u32 32;");
        if (warp == NUM_WG * 4) {
#pragma unroll
            for (int j = 0; j < NUM_WG; j++) mbar_init_1(bars + BAR_W + 8 * j, 1);
            publish_barriers();
            cluster_arrive();
#pragma unroll
            for (int j = 0; j < NUM_WG; j++) {
                if (j == W_FIRST) {
                    cluster_wait();
                    TR(0, 0);
                    mbar_expect_tx_1(bars + BAR_FULL, STAGE_BYTES);
                    tma_load_x_1(smem + rank * HALF_BYTES, &maps.x, bars + BAR_FULL, cluster * 8 + rank * 4, EVICT_NORMAL);
                }
                mbar_expect_tx_1(bars + BAR_W + 8 * j, STAGE_BYTES);
                tma_load_w_1(smem + w_stage(j), &maps.w, bars + BAR_W + 8 * j, slice_channel(rank, j));
                if (j == 0) TR(2, 61);
            }
            Ring r = {1, 0};
#pragma unroll 1
            for (uint32_t id = cluster + num_clusters; id < num_tiles; id += num_clusters, r.advance()) {
                mbar_wait_w(bars + BAR_EMPTY + 8 * r.s, r.parity ^ (r.s == 0));
                sts32(bars + ISSUED_AT, id);
                TR(0, id / num_clusters);
                TRV(15, id / num_clusters, id);
                const uint32_t full = bars + BAR_FULL + 8 * r.s;
                mbar_expect_tx_1(full, STAGE_BYTES);
                tma_load_x_1(smem + r.s * STAGE_BYTES + rank * HALF_BYTES, &maps.x, full, id * 8 + rank * 4,
                             id + TP(EF_TAIL) >= num_tiles ? EVICT_FIRST : EVICT_NORMAL);
            }
#pragma unroll 1
            for (int k = 0; k < STAGES; k++, r.advance()) mbar_wait_w(bars + BAR_EMPTY + 8 * r.s, r.parity ^ (r.s == 0));
        } else if (warp == NUM_WG * 4 + 1) {
#pragma unroll
            for (int s = 0; s < STAGES; s++) {
                mbar_init_1(bars + BAR_FULL + 8 * s, 1);
                mbar_init_1(bars + BAR_EMPTY + 8 * s, NUM_WG * 4 * 2);
            }
            publish_barriers();
            cluster_arrive();
            TR(0, 61);
            cluster_wait();
            prefetch_map_1(&maps.out);
        } else if (warp == NUM_WG * 4 + 2) {
            uint32_t due = timer_ns() + TP(ST_T0) + cluster * TP(ST_STAG) - TP(ST_P1);
#pragma unroll
            for (int b = 0; b < STAGES; b++) {
#pragma unroll
                for (int w = 0; w < NUM_WG; w++) {
                    mbar_init_1(bars + BAR_OFREE + b * 32 + w * 8, 1);
                    mbar_init_1(bars + BAR_OFULL + b * 32 + w * 8, 4);
                }
            }
            publish_barriers();
            cluster_arrive();
            cluster_wait();
            const uint32_t mark = num_tiles / num_clusters - TP(SW_J);
            const int behind = cluster < num_tiles % num_clusters ? cluster : cluster - num_clusters;
            const float stage1 = (float)((int)TP(SW_D1) + behind * ((int)TP(SW_K1) - (int)TP(SW_K2)));
            uint32_t open = 0, t_end = 0;
            Ring o = {0, 0};
#pragma unroll 1
            for (uint32_t j = 0, id = cluster; id < num_tiles; j++, id += num_clusters, o.advance()) {
                const uint32_t parity = o.parity;
                const uint32_t obar = bars + o.s * 32;
                if (!mbar_test_w(obar + BAR_OFULL, parity)) {
                    hand_back<0>(open);
                    mbar_wait_w(obar + BAR_OFULL, parity);
                }
                const uint32_t src = smem + SMEM_OUT + o.s * HALF_BYTES;
                const uint32_t period = j <= TP(ST_E1) ? TP(ST_P1) : j <= TP(ST_E2) ? TP(ST_P2) : TP(ST_P3);
                uint32_t now = timer_ns();
                if (j >= TP(ST_AT)) {
                    if (j <= mark || (int32_t)(due + period - t_end) <= 0) {
                        due += period;
                    } else {
                        float t = (float)(int32_t)(due - t_end), rest = 1.f;
                        if (t < 0.f) {
                            rest += __fdividef(t, (float)period);
                            t = 0.f;
                        }
                        const float room = stage1 - t;
                        if (room >= rest * (float)TP(ST_PT)) {
                            t += rest * (float)TP(ST_PT);
                        } else {
                            if (room > 0.f) {
                                rest -= __fdividef(room, (float)TP(ST_PT));
                                t += room;
                            }
                            t += rest * (float)TP(ST_PU);
                        }
                        due = t_end + (int32_t)t;
                    }
                    if ((int32_t)(now - due) < 0) hand_back<0>(open);
#pragma unroll 1
                    for (uint32_t spins = 0; (int32_t)(now - due) < 0 && spins < SPIN_LIMIT; spins++) {
                        __nanosleep(20);
                        now = timer_ns();
                    }
                }
                if (j >= TP(ST_AT) && (int32_t)(now - TP(ST_SLACK) - due) > 0) due = now - TP(ST_SLACK);
                if (j == mark) t_end = due - cluster * TP(ST_STAG) + TP(SW_D) - behind * (int)TP(SW_K1);
                const bool whole = mbar_test_w(obar + BAR_OFULL + 8, parity) && mbar_test_w(obar + BAR_OFULL + 16, parity);
                if (whole) {
                    TR(11, j);
#pragma unroll
                    for (int w = 0; w < NUM_WG; w++) tma_store_1(&maps.out, src + w * SLICE_BYTES, slice_channel(rank, w), id * TILE_PIX);
                    TR(12, j);
                    TR(13, j);
                    hand_back<3>(open);
                    stores_read_wait<2>();
                    mbar_arrive_1(obar + BAR_OFREE);
                    stores_read_wait<1>();
                    mbar_arrive_1(obar + BAR_OFREE + 8);
                    open = obar + BAR_OFREE + 16;
                } else {
#pragma unroll 1
                    for (uint32_t w = 0; w < NUM_WG; w++) {
                        if (!mbar_test_w(obar + BAR_OFULL + w * 8, parity)) {
                            hand_back<0>(open);
                            mbar_wait_w(obar + BAR_OFULL + w * 8, parity);
                        }
                        TR(11 + w, j);
                        tma_store_1(&maps.out, src + w * SLICE_BYTES, slice_channel(rank, w), id * TILE_PIX);
                        hand_back<1>(open);
                        open = obar + BAR_OFREE + w * 8;
                    }
                }
            }
            stores_read_wait<0>();
            TR(4, 62);
        } else {
            uint32_t due = timer_ns() + TP(PM_T0) + (blockIdx.x & 3) * TP(PM_STAG);
            sts32(bars + ISSUED_AT, 0);
            cluster_arrive();
            const uint32_t step = num_clusters / 2;
#pragma unroll 1
            for (uint32_t piece = PRE_X; piece < TP(PM_E4); piece++) {
                const uint32_t t = cluster + piece / 2 * num_clusters;
                if (t >= num_tiles) break;
                uint32_t now;
#pragma unroll 1
                for (uint32_t spins = 0; spins < 16384; spins++) {
                    const uint32_t issued = uniform(lds32(bars + ISSUED_AT));
                    now = timer_ns();
                    const int lead = max((int)TP(LEAD_B), (int)TP(LEAD_A) - (max((int)issued - (int)TP(LEAD_F), 0) * (int)TP(LEAD_S) >> 4));
                    if ((int32_t)(now - due) >= 0) {
                        if (cluster + piece * step <= issued + lead) break;
                        due = now;
                    }
                    __nanosleep(20);
                }
                if ((int32_t)(now - TP(PM_SLACK) - due) > 0) due = now - TP(PM_SLACK);
                due += piece < TP(PM_E1) ? TP(PM_DT1) : piece < TP(PM_E2) ? TP(PM_DT2) : piece < TP(PM_E3) ? TP(PM_DT3) : TP(PM_DT4);
                const uint8_t* p = x_raw + (size_t)t * STAGE_BYTES + rank * HALF_BYTES + (piece % 2) * 12288 + lane * 128;
#pragma unroll
                for (int k = 0; k < 3; k++) asm volatile("prefetch.global.L2 [%0];" ::"l"(p + k * 4096) : "memory");
                if (piece % 2 == 0) TR(14, piece / 2);
            }
            cluster_wait();
        }
    }
}

typedef CUresult (*EncodeTiledFn)(CUtensorMap*, CUtensorMapDataType, cuuint32_t, void*, const cuuint64_t*,
                                  const cuuint64_t*, const cuuint32_t*, const cuuint32_t*, CUtensorMapInterleave,
                                  CUtensorMapSwizzle, CUtensorMapL2promotion, CUtensorMapFloatOOBfill);

}

extern "C" void kernel_launch(void* const* d_in, const int* in_sizes, int n_in, void* d_out, int out_size) {
    (void)n_in;
    (void)out_size;
    void* x = d_in[0];
    void* w = d_in[1];
    const uint16_t* b = (const uint16_t*)d_in[2];
    const int M = in_sizes[0] / C;
    const int num_tiles = M / TILE_PIX;

    static EncodeTiledFn encode = nullptr;
    static int sms = 0;
    if (!encode) {
        void* fn = nullptr;
        cudaDriverEntryPointQueryResult q;
        cudaGetDriverEntryPoint("cuTensorMapEncodeTiled", &fn, cudaEnableDefault, &q);
        encode = (EncodeTiledFn)fn;
        cudaDeviceGetAttribute(&sms, cudaDevAttrMultiProcessorCount, 0);
        cudaFuncSetAttribute(conv1x1_kernel, cudaFuncAttributeMaxDynamicSharedMemorySize, SMEM_TOTAL);
    }

    Maps maps;
    const cuuint32_t ones[4] = {1, 1, 1, 1};
    auto make = [&](CUtensorMap* map, int rank, void* base, const cuuint64_t* dims, const cuuint64_t* strides,
                    const cuuint32_t* box, CUtensorMapL2promotion promo) {
        encode(map, CU_TENSOR_MAP_DATA_TYPE_BFLOAT16, rank, base, dims, strides, box, ones, CU_TENSOR_MAP_INTERLEAVE_NONE,
               CU_TENSOR_MAP_SWIZZLE_128B, promo, CU_TENSOR_MAP_FLOAT_OOB_FILL_NONE);
    };
    {
        const cuuint64_t dims[4]    = {64, 8, 6, (cuuint64_t)(M / 8)};
        const cuuint64_t strides[3] = {C * 2, 128, 8 * C * 2};
        const cuuint32_t box[4]     = {64, 8, 6, TILE_PIX / 16};
        make(&maps.x, 4, x, dims, strides, box, CU_TENSOR_MAP_L2_PROMOTION_L2_128B);
    }
    {
        const cuuint64_t dims[3]    = {C, C / 2, 2};
        const cuuint64_t strides[2] = {C * 2, C * C};
        const cuuint32_t box[3]     = {64, C / 2, 2};
        make(&maps.w, 3, w, dims, strides, box, CU_TENSOR_MAP_L2_PROMOTION_L2_128B);
    }
    {
        const cuuint64_t dims[2]    = {C, (cuuint64_t)M};
        const cuuint64_t strides[1] = {C * 2};
        const cuuint32_t box[2]     = {64, TILE_PIX};
        make(&maps.out, 2, d_out, dims, strides, box, CU_TENSOR_MAP_L2_PROMOTION_NONE);
    }

    const Tune tune;
    int clusters = sms / 2;
    if (clusters > num_tiles) clusters = num_tiles;
    conv1x1_kernel<<<clusters * 2, THREADS, SMEM_TOTAL>>>((const uint8_t*)x, (const uint8_t*)w, b, (uint32_t)num_tiles,
                                                          (uint32_t)clusters, maps, tune);
}
```

```cpp
#include <cuda_runtime.h>
#include <cuda_bf16.h>
#include <cuda.h>
#include <stdint.h>

#define EARLY_AT 18

#define W_FIRST 2
#define PRE_X 1
#define PRE_D0 200
#define PRE_DT 300
#define PRE_W 64

#define TUNABLES(F) \
    F(EARLY_TILES, 462)    \
    F(EARLY_HEAD, 1584)       \
    F(PM_T0, 0)            \
    F(PM_DT1, 455)         \
    F(PM_E1, 17) \
    F(PM_DT2, 400) \
    F(PM_E2, 23) \
    F(PM_DT3, 820) \
    F(PM_E3, 61) \
    F(PM_DT4, 650) \
    F(PM_E4, 72) \
    F(PM_STAG, 210)        \
    F(LEAD_A, 280)        \
    F(LEAD_F, 500)         \
    F(LEAD_S, 3)           \
    F(LEAD_B, 151)        \
    F(PM_SLACK, 600)    \
    F(EF_TAIL, 500)        \
    F(ST_AT, 2)            \
    F(ST_T0, 6600)         \
    F(ST_STAG, 32)          \
    F(ST_P1, 2030)         \
    F(ST_E1, 9) \
    F(ST_P2, 1870) \
    F(ST_E2, 18) \
    F(ST_P3, 1970) \
    F(ST_SLACK, 400)       \
    F(SW_J, 12)            \
    F(SW_D, 7800)          \
    F(ST_PT, 1620)         \
    F(SW_D1, 3050)         \
    F(ST_PU, 460)          \
    F(SW_K1, 0)            \
    F(SW_K2, 10) \
    F(CC_AT, 22)           \
    F(CC_L0, 1300)         \
    F(CC_G, 12)             \
    F(CC_STEP, 600)        \
    F(CC_CAP, 1100)        \
    F(HOLD_T, 100)         \
    F(X0, 0) \
    F(X1, 0) \
    F(X2, 0) \
    F(X3, 0)

struct Tune {
#define F(n, v) static constexpr uint32_t n = v;
    TUNABLES(F)
#undef F
};
#define TP(n) (Tune::n)

#define TRV(slot, idx, v)
#define TR(slot, idx)
#define TRE(slot, idx)

namespace {

constexpr int C            = 384;
constexpr int TILE_PIX     = 64;
constexpr int STAGES       = 3;
constexpr int STAGE_BYTES  = TILE_PIX * C * 2;
constexpr int HALF_BYTES   = STAGE_BYTES / 2;
constexpr int SLICE_BYTES  = TILE_PIX * 128;
constexpr int W_LINES      = C * C * 2 / 128;
constexpr int NUM_WG       = 3;
constexpr int THREADS      = (NUM_WG + 1) * 128;
constexpr int SMEM_OUT     = STAGES * STAGE_BYTES;
constexpr int SMEM_BAR     = SMEM_OUT + STAGES * HALF_BYTES;
constexpr int SMEM_TOTAL   = SMEM_BAR + 512 + 1024;
constexpr uint32_t SPIN_LIMIT = 1u << 24;
constexpr int BAR_W     = 0;
constexpr int BAR_FULL  = 32;
constexpr int BAR_EMPTY = BAR_FULL + 32;
constexpr int BAR_OFREE = BAR_EMPTY + 32;
constexpr int BAR_OFULL = BAR_OFREE + 32 * STAGES;
constexpr int ISSUED_AT = BAR_OFULL + 32 * STAGES;
constexpr int DELAY_AT  = ISSUED_AT + 4;
constexpr int STAMP_AT  = DELAY_AT + 4;
constexpr uint64_t EVICT_NORMAL = 0x1000000000000000ull;
constexpr uint64_t EVICT_FIRST  = 0x12F0000000000000ull;

struct Maps {
    CUtensorMap w, x, out;
};

#define ELECT "{\n.reg .pred e;\nelect.sync _|e, 0xffffffff;\n@e "

__device__ __forceinline__ uint32_t smem_u32(const void* p) {
    return (uint32_t)__cvta_generic_to_shared(p);
}
__device__ __forceinline__ void mbar_init_1(uint32_t bar, uint32_t count) {
    asm volatile(ELECT "mbarrier.init.shared::cta.b64 [%0], %1;\n}" ::"r"(bar), "r"(count) : "memory");
}
__device__ __forceinline__ void mbar_expect_tx_1(uint32_t bar, uint32_t bytes) {
    asm volatile(ELECT "mbarrier.arrive.expect_tx.shared::cta.b64 _, [%0], %1;\n}" ::"r"(bar), "r"(bytes) : "memory");
}
__device__ __forceinline__ void mbar_arrive_1(uint32_t bar) {
    asm volatile(ELECT "mbarrier.arrive.shared::cta.b64 _, [%0];\n}" ::"r"(bar) : "memory");
}
__device__ __forceinline__ void mbar_wait(uint32_t bar, uint32_t parity) {
    uint32_t done;
    uint32_t spins = 0;
    do {
        asm volatile(
            "{\n.reg .pred p;\n"
            "mbarrier.try_wait.parity.shared::cta.b64 p, [%1], %2;\n"
            "selp.u32 %0, 1, 0, p;\n}"
            : "=r"(done) : "r"(bar), "r"(parity) : "memory");
    } while (!done && ++spins < SPIN_LIMIT);
}
__device__ __forceinline__ void mbar_wait_w(uint32_t bar, uint32_t parity) {
    mbar_wait(bar, parity);
    __syncwarp();
}
__device__ __forceinline__ bool mbar_test_w(uint32_t bar, uint32_t parity) {
    uint32_t done;
    asm volatile(
        "{\n.reg .pred p;\n"
        "mbarrier.test_wait.parity.shared::cta.b64 p, [%1], %2;\n"
        "selp.u32 %0, 1, 0, p;\n}"
        : "=r"(done) : "r"(bar), "r"(parity) : "memory");
    return __all_sync(0xffffffffu, done);
}
__device__ __forceinline__ void mbar_arrive_cta(uint32_t bar, uint32_t cta) {
    asm volatile(
        "{\n.reg .b32 ra;\n"
        "mapa.shared::cluster.u32 ra, %0, %1;\n"
        "mbarrier.arrive.shared::cluster.b64 _, [ra];\n}"
        ::"r"(bar), "r"(cta) : "memory");
}
__device__ __forceinline__ uint32_t lds32(uint32_t addr) {
    uint32_t v;
    asm volatile("ld.shared.b32 %0, [%1];" : "=r"(v) : "r"(addr) : "memory");
    return v;
}
__device__ __forceinline__ uint32_t uniform(uint32_t v) {
    return __shfl_sync(0xffffffffu, v, 0);
}
__device__ __forceinline__ void sts32(uint32_t addr, uint32_t v) {
    asm volatile("st.shared.b32 [%0], %1;" ::"r"(addr), "r"(v) : "memory");
}
__device__ __forceinline__ void tma_load_w_1(uint32_t dst, const CUtensorMap* map, uint32_t bar, int n) {
    asm volatile(
        ELECT "cp.async.bulk.tensor.3d.shared::cluster.global.mbarrier::complete_tx::bytes [%0], [%1, {%3, %4, %4}], [%2];\n}"
        ::"r"(dst), "l"(map), "r"(bar), "r"(n), "r"(0) : "memory");
}
__device__ __forceinline__ void tma_load_x_1(uint32_t dst, const CUtensorMap* map, uint32_t bar, int group, uint64_t policy) {
    asm volatile(
        ELECT "cp.async.bulk.tensor.4d.shared::cluster.global.mbarrier::complete_tx::bytes.multicast::cluster.L2::cache_hint"
        " [%0], [%1, {%3, %3, %3, %4}], [%2], %5, %6;\n}"
        ::"r"(dst), "l"(map), "r"(bar), "r"(0), "r"(group), "h"((uint16_t)3), "l"(policy) : "memory");
}
__device__ __forceinline__ void tma_store_1(const CUtensorMap* map, uint32_t src, int ch, int pix) {
    asm volatile(
        ELECT "cp.async.bulk.tensor.2d.global.shared::cta.bulk_group [%0, {%2, %3}], [%1];\n}\n"
        "cp.async.bulk.commit_group;"
        ::"l"(map), "r"(src), "r"(ch), "r"(pix) : "memory");
}
template <int N>
__device__ __forceinline__ void stores_read_wait() {
    asm volatile("cp.async.bulk.wait_group.read %0;" ::"n"(N) : "memory");
}
__device__ __forceinline__ void prefetch_map_1(const CUtensorMap* map) {
    asm volatile(ELECT "prefetch.tensormap [%0];\n}" ::"l"(map) : "memory");
}
__device__ __forceinline__ uint32_t timer_ns() {
    uint32_t t;
    asm volatile("mov.u32 %0, %%globaltimer_lo;" : "=r"(t)::"memory");
    return t;
}
__device__ __forceinline__ void cluster_arrive() {
    asm volatile("barrier.cluster.arrive.relaxed.aligned;" ::: "memory");
}
__device__ __forceinline__ void cluster_wait() {
    asm volatile("barrier.cluster.wait.aligned;" ::: "memory");
}
__device__ __forceinline__ void publish_barriers() {
    asm volatile("fence.mbarrier_init.release.cluster;" ::: "memory");
    asm volatile("fence.proxy.async.shared::cta;" ::: "memory");
}

__device__ __forceinline__ void wgmma_rs_n64(float (&d)[32], const uint32_t* a, uint64_t desc, int scale_d) {
    asm volatile(
        "{\n.reg .pred p;\n"
        "setp.ne.b32 p, %37, 0;\n"
        "wgmma.mma_async.sync.aligned.m64n64k16.f32.bf16.bf16 "
        "{%0, %1, %2, %3, %4, %5, %6, %7, %8, %9, %10, %11, %12, %13, %14, %15, "
        "%16, %17, %18, %19, %20, %21, %22, %23, %24, %25, %26, %27, %28, %29, %30, %31}, "
        "{%32, %33, %34, %35}, %36, p, 1, 1, 0;\n}"
        : "+f"(d[0]), "+f"(d[1]), "+f"(d[2]), "+f"(d[3]), "+f"(d[4]), "+f"(d[5]), "+f"(d[6]), "+f"(d[7]),
          "+f"(d[8]), "+f"(d[9]), "+f"(d[10]), "+f"(d[11]), "+f"(d[12]), "+f"(d[13]), "+f"(d[14]), "+f"(d[15]),
          "+f"(d[16]), "+f"(d[17]), "+f"(d[18]), "+f"(d[19]), "+f"(d[20]), "+f"(d[21]), "+f"(d[22]), "+f"(d[23]),
          "+f"(d[24]), "+f"(d[25]), "+f"(d[26]), "+f"(d[27]), "+f"(d[28]), "+f"(d[29]), "+f"(d[30]), "+f"(d[31])
        : "r"(a[0]), "r"(a[1]), "r"(a[2]), "r"(a[3]), "l"(desc), "r"(scale_d));
}

__device__ __forceinline__ uint32_t pack_bias(float lo, float hi, uint32_t bias2) {
    uint32_t r;
    asm("{\n.reg .b32 t;\n"
        "cvt.rn.bf16x2.f32 t, %2, %1;\n"
        "add.rn.bf16x2 %0, t, %3;\n}"
        : "=r"(r) : "f"(lo), "f"(hi), "r"(bias2));
    return r;
}

__device__ __forceinline__ int slice_channel(uint32_t rank, int wg) {
    return (wg * 2 + rank) * 64;
}

struct Consumer {
    uint32_t wreg[96];
    uint32_t bias_lo, bias_hi, st_addr, bars;
    uint64_t desc_base;
    int wg, lane;
};
struct Ring {
    uint32_t s, parity;
    __device__ __forceinline__ void advance() {
        if (++s == STAGES) {
            s = 0;
            parity ^= 1;
        }
    }
};
__device__ __forceinline__ uint32_t w_stage(int wg) {
    return (wg + 1) * STAGE_BYTES + (wg == 2 ? HALF_BYTES : 0);
}

__device__ __forceinline__ void multiply(const Consumer& c, const Ring& r, float (&acc)[32], uint32_t i, bool early) {
    const int next_turn = 4 + (c.wg + 1) % NUM_WG;
    if ((i | c.wg) != 0) asm volatile("bar.sync %0, 256;" ::"r"(4 + c.wg) : "memory");
    TRE(1 + c.wg * 2, i);
    const uint64_t desc = c.desc_base + (uint64_t)(r.s * (STAGE_BYTES >> 4));
    asm volatile("wgmma.fence.sync.aligned;" ::: "memory");
#pragma unroll
    for (int ks = 0; ks < 24; ks++) {
        const uint64_t d = desc + (uint64_t)((ks >> 2) * 64 + (ks & 3) * 2);
        wgmma_rs_n64(acc, &c.wreg[ks * 4], d, ks != 0);
        if (ks + 1 == EARLY_AT && early) asm volatile("bar.arrive %0, 256;" ::"r"(next_turn) : "memory");
    }
    asm volatile("wgmma.commit_group.sync.aligned;" ::: "memory");
    asm volatile("wgmma.wait_group.sync.aligned 0;" ::: "memory");
#pragma unroll
    for (int j = 0; j < 32; j++) asm volatile("" : "+f"(acc[j])::"memory");
    if (!early) asm volatile("bar.arrive %0, 256;" ::"r"(next_turn) : "memory");
    TRE(2 + c.wg * 2, i);
    if (c.lane < 2) mbar_arrive_cta(c.bars + BAR_EMPTY + 8 * r.s, c.lane);
}
__device__ __forceinline__ void write_out(const Consumer& c, const Ring& r, const uint32_t (&v)[16]) {
    const uint32_t obar = c.bars + (r.s * 4 + c.wg) * 8;
    mbar_wait_w(obar + BAR_OFREE, r.parity ^ 1);
    const uint32_t dst = c.st_addr + r.s * HALF_BYTES;
#pragma unroll
    for (int j = 0; j < 4; j++) {
        asm volatile("stmatrix.sync.aligned.m8n8.x4.trans.shared.b16 [%0], {%1, %2, %3, %4};"
                     ::"r"(dst + j * 2048), "r"(v[4 * j]), "r"(v[4 * j + 1]), "r"(v[4 * j + 2]), "r"(v[4 * j + 3]) : "memory");
    }
    asm volatile("fence.proxy.async.shared::cta;" ::: "memory");
    __syncwarp();
    mbar_arrive_1(obar + BAR_OFULL);
}

template <int N>
__device__ __forceinline__ void hand_back(uint32_t& open) {
    if (open != 0) {
        stores_read_wait<N>();
        mbar_arrive_1(open);
        open = 0;
    }
}

__global__ void __cluster_dims__(2, 1, 1) __launch_bounds__(THREADS, 1)
conv1x1_kernel(const uint8_t* __restrict__ x_raw,
               const uint8_t* __restrict__ w_raw,
               const uint16_t* __restrict__ bias,
               uint32_t num_tiles,
               uint32_t num_clusters,
               const __grid_constant__ Maps maps,
               const __grid_constant__ Tune tune) {
    if (threadIdx.x < 96) {
        const uint32_t line = blockIdx.x % (W_LINES / PRE_W) * PRE_W + threadIdx.x;
        if (threadIdx.x < PRE_W) asm volatile("prefetch.global.L2 [%0];" ::"l"(w_raw + line * 128) : "memory");
    } else if (threadIdx.x < 128) {
        prefetch_map_1(&maps.w);
        prefetch_map_1(&maps.x);
    }
    if (threadIdx.x < NUM_WG * 128) cluster_arrive();
    if (threadIdx.x >= 128 && threadIdx.x < 128 + PRE_X * 96) {
        const uint8_t* p = x_raw + (size_t)blockIdx.x * HALF_BYTES + (threadIdx.x - 128) * 128;
        if (PRE_D0 + PRE_DT != 0) {
            const uint32_t wait = PRE_D0 + ((threadIdx.x - 128) >> 5) * PRE_DT;
            const uint32_t c0 = clock();
            while (clock() - c0 < wait) {}
        }
        asm volatile("prefetch.global.L2 [%0];" ::"l"(p) : "memory");
    }
    extern __shared__ uint8_t smem_raw[];
    const uint32_t smem = (smem_u32(smem_raw) + 1023u) & ~1023u;
    const uint32_t bars = smem + SMEM_BAR;

    const int warp = uniform(threadIdx.x >> 5);
    const int lane = threadIdx.x & 31;
    const uint32_t rank         = blockIdx.x & 1;
    const uint32_t cluster      = blockIdx.x >> 1;

    if (warp < NUM_WG * 4) {
        const int wg = warp >> 2;
        const int wq = warp & 3;
        asm volatile("setmaxnreg.inc.sync.aligned.u32 160;");
        Consumer c;
        c.wg = wg;
        c.lane = lane;
        c.bars = bars;
        c.bias_lo = bias[slice_channel(rank, wg) + wq * 16 + (lane >> 2)] * 0x10001u;
        c.bias_hi = bias[slice_channel(rank, wg) + wq * 16 + (lane >> 2) + 8] * 0x10001u;

        cluster_wait();
        TRE(1 + wg, 63);
        mbar_wait_w(bars + BAR_W + 8 * wg, 0);
        TRE(4 + wg, 63);
        {
            const int r = lane & 7, m = lane >> 3;
            const uint32_t base = smem + w_stage(wg) + ((m >> 1) * 8 + r) * 128 + (((2 * wq + (m & 1)) ^ r) << 4);
#pragma unroll
            for (int ks = 0; ks < 24; ks++) {
                asm volatile("ldmatrix.sync.aligned.m8n8.x4.trans.shared.b16 {%0, %1, %2, %3}, [%4];"
                             : "=r"(c.wreg[ks * 4 + 0]), "=r"(c.wreg[ks * 4 + 1]), "=r"(c.wreg[ks * 4 + 2]), "=r"(c.wreg[ks * 4 + 3])
                             : "r"(base + ks * 2048) : "memory");
            }
        }
        uint32_t dep = 0;
#pragma unroll
        for (int ks = 0; ks < 24; ks++) dep ^= c.wreg[ks * 4];
        dep &= num_tiles >> 31;
        __syncwarp();
        if (lane < 6 && wg < 2) mbar_arrive_cta(bars + BAR_EMPTY + 8 * (wg + 1) + dep, lane & 1);
        TRE(1 + wg, 60);

        c.st_addr = smem + SMEM_OUT + wg * SLICE_BYTES + ((lane >> 4) * 8 + (lane & 7)) * 128 + (((2 * wq + ((lane >> 3) & 1)) ^ (lane & 7)) << 4);
        c.desc_base = (uint64_t)((smem & 0x3FFFF) >> 4) | ((uint64_t)1 << 16) | ((uint64_t)(6144 >> 4) << 32) | ((uint64_t)1 << 62);

        float acc[32];
        uint32_t packed[16];
        Ring r = {0, uniform(dep)}, o = r;
        bool held = false;
        for (uint32_t i = 0, id = cluster; id < num_tiles; i++, id += num_clusters, r.advance()) {
            mbar_wait(bars + BAR_FULL + 8 * r.s, r.parity);
            multiply(c, r, acc, i, id + TP(EARLY_TILES) >= num_tiles || id + 1 <= TP(EARLY_HEAD));
            if (held) write_out(c, o, packed);
            o = r;
#pragma unroll
            for (int j = 0; j < 16; j++) packed[j] = pack_bias(acc[2 * j], acc[2 * j + 1], j & 1 ? c.bias_hi : c.bias_lo);
            held = id + TP(HOLD_T) < num_tiles && !mbar_test_w(bars + BAR_OFREE + (o.s * 4 + wg) * 8, o.parity ^ 1);
            if (!held) write_out(c, o, packed);
            TRE(8 + wg, i);
        }
        if (held) write_out(c, o, packed);
        if (wg == 0) asm volatile("bar.sync 4, 256;" ::: "memory");
        TRE(1 + wg, 62);
    } else {
        asm volatile("setmaxnreg.dec.sync.aligned.u32 32;");
        if (warp == NUM_WG * 4) {
#pragma unroll
            for (int j = 0; j < NUM_WG; j++) mbar_init_1(bars + BAR_W + 8 * j, 1);
            publish_barriers();
            cluster_arrive();
#pragma unroll
            for (int j = 0; j < NUM_WG; j++) {
                if (j == W_FIRST) {
                    cluster_wait();
                    TR(0, 0);
                    mbar_expect_tx_1(bars + BAR_FULL, STAGE_BYTES);
                    tma_load_x_1(smem + rank * HALF_BYTES, &maps.x, bars + BAR_FULL, cluster * 8 + rank * 4, EVICT_NORMAL);
                }
                mbar_expect_tx_1(bars + BAR_W + 8 * j, STAGE_BYTES);
                tma_load_w_1(smem + w_stage(j), &maps.w, bars + BAR_W + 8 * j, slice_channel(rank, j));
                if (j == 0) TR(2, 61);
            }
            Ring r = {1, 0};
#pragma unroll 1
            for (uint32_t i = 1, id = cluster + num_clusters; id < num_tiles; i++, id += num_clusters, r.advance()) {
                mbar_wait_w(bars + BAR_EMPTY + 8 * r.s, r.parity ^ (r.s == 0));
                sts32(bars + ISSUED_AT, id);
                sts32(bars + STAMP_AT + 4 * r.s, timer_ns());
                TR(0, i);
                TRV(15, i, id);
                const uint32_t full = bars + BAR_FULL + 8 * r.s;
                mbar_expect_tx_1(full, STAGE_BYTES);
                tma_load_x_1(smem + r.s * STAGE_BYTES + rank * HALF_BYTES, &maps.x, full, id * 8 + rank * 4,
                             id + TP(EF_TAIL) >= num_tiles ? EVICT_FIRST : EVICT_NORMAL);
            }
#pragma unroll 1
            for (int k = 0; k < STAGES; k++, r.advance()) mbar_wait_w(bars + BAR_EMPTY + 8 * r.s, r.parity ^ (r.s == 0));
        } else if (warp == NUM_WG * 4 + 1) {
            sts32(bars + DELAY_AT, 0);
#pragma unroll
            for (int s = 0; s < STAGES; s++) {
                mbar_init_1(bars + BAR_FULL + 8 * s, 1);
                mbar_init_1(bars + BAR_EMPTY + 8 * s, NUM_WG * 4 * 2);
            }
            publish_barriers();
            cluster_arrive();
            TR(0, 61);
            cluster_wait();
            prefetch_map_1(&maps.out);
            uint32_t delay = 0;
            Ring r = {0, 0};
#pragma unroll 1
            for (uint32_t i = 0, id = cluster; id < num_tiles; i++, id += num_clusters, r.advance()) {
                mbar_wait_w(bars + BAR_FULL + 8 * r.s, r.parity);
                TR(7, i);
                const int late = (int)(timer_ns() - lds32(bars + STAMP_AT + 4 * r.s) - TP(CC_L0));
                if (i >= TP(CC_AT) && late > 0) {
                    delay = min(delay + min((uint32_t)late * TP(CC_G) >> 4, TP(CC_STEP)), TP(CC_CAP));
                    sts32(bars + DELAY_AT, delay);
                }
            }
        } else if (warp == NUM_WG * 4 + 2) {
            uint32_t due = timer_ns() + TP(ST_T0) + cluster * TP(ST_STAG) - TP(ST_P1);
#pragma unroll
            for (int b = 0; b < STAGES; b++) {
#pragma unroll
                for (int w = 0; w < NUM_WG; w++) {
                    mbar_init_1(bars + BAR_OFREE + b * 32 + w * 8, 1);
                    mbar_init_1(bars + BAR_OFULL + b * 32 + w * 8, 4);
                }
            }
            publish_barriers();
            cluster_arrive();
            cluster_wait();
            const uint32_t mark = num_tiles / num_clusters - TP(SW_J);
            const int behind = cluster < num_tiles % num_clusters ? cluster : cluster - num_clusters;
            const float stage1 = (float)((int)TP(SW_D1) + behind * ((int)TP(SW_K1) - (int)TP(SW_K2)));
            uint32_t open = 0, t_end = 0, delay = 0;
            Ring o = {0, 0};
#pragma unroll 1
            for (uint32_t j = 0, id = cluster; id < num_tiles; j++, id += num_clusters, o.advance()) {
                const uint32_t parity = o.parity;
                const uint32_t obar = bars + o.s * 32;
                if (!mbar_test_w(obar + BAR_OFULL, parity)) {
                    hand_back<0>(open);
                    mbar_wait_w(obar + BAR_OFULL, parity);
                }
                const uint32_t src = smem + SMEM_OUT + o.s * HALF_BYTES;
                const uint32_t period = j <= TP(ST_E1) ? TP(ST_P1) : j <= TP(ST_E2) ? TP(ST_P2) : TP(ST_P3);
                uint32_t now = timer_ns();
                if (j >= TP(ST_AT)) {
                    if (j <= mark || (int32_t)(due + period - t_end) <= 0) {
                        due += period;
                    } else {
                        float t = (float)(int32_t)(due - t_end), rest = 1.f;
                        if (t < 0.f) {
                            rest += __fdividef(t, (float)period);
                            t = 0.f;
                        }
                        const float room = stage1 - t;
                        if (room >= rest * (float)TP(ST_PT)) {
                            t += rest * (float)TP(ST_PT);
                        } else {
                            if (room > 0.f) {
                                rest -= __fdividef(room, (float)TP(ST_PT));
                                t += room;
                            }
                            t += rest * (float)TP(ST_PU);
                        }
                        due = t_end + (int32_t)t;
                    }
#pragma unroll 1
                    for (uint32_t spins = 0; spins < SPIN_LIMIT; spins++) {
                        const uint32_t more = uniform(lds32(bars + DELAY_AT)) - delay;
                        delay += more;
                        due += more;
                        t_end += more;
                        if ((int32_t)(now - due) >= 0) break;
                        hand_back<0>(open);
                        __nanosleep(20);
                        now = timer_ns();
                    }
                }
                if (j >= TP(ST_AT) && (int32_t)(now - TP(ST_SLACK) - due) > 0) due = now - TP(ST_SLACK);
                if (j == mark) t_end = due - cluster * TP(ST_STAG) + TP(SW_D) - behind * (int)TP(SW_K1);
                const bool whole = mbar_test_w(obar + BAR_OFULL + 8, parity) && mbar_test_w(obar + BAR_OFULL + 16, parity);
                if (whole) {
                    TR(11, j);
#pragma unroll
                    for (int w = 0; w < NUM_WG; w++) tma_store_1(&maps.out, src + w * SLICE_BYTES, slice_channel(rank, w), id * TILE_PIX);
                    hand_back<3>(open);
                    stores_read_wait<2>();
                    TR(12, j);
                    mbar_arrive_1(obar + BAR_OFREE);
                    stores_read_wait<1>();
                    TR(13, j);
                    mbar_arrive_1(obar + BAR_OFREE + 8);
                    open = obar + BAR_OFREE + 16;
                } else {
#pragma unroll 1
                    for (uint32_t w = 0; w < NUM_WG; w++) {
                        if (!mbar_test_w(obar + BAR_OFULL + w * 8, parity)) {
                            hand_back<0>(open);
                            mbar_wait_w(obar + BAR_OFULL + w * 8, parity);
                        }
                        TR(11 + w, j);
                        tma_store_1(&maps.out, src + w * SLICE_BYTES, slice_channel(rank, w), id * TILE_PIX);
                        hand_back<1>(open);
                        open = obar + BAR_OFREE + w * 8;
                    }
                }
            }
            stores_read_wait<0>();
            TR(4, 62);
        } else {
            uint32_t due = timer_ns() + TP(PM_T0) + (blockIdx.x & 3) * TP(PM_STAG);
            sts32(bars + ISSUED_AT, 0);
            cluster_arrive();
            const uint32_t step = num_clusters / 2;
#pragma unroll 1
            for (uint32_t piece = PRE_X; piece < TP(PM_E4); piece++) {
                const uint32_t t = cluster + piece / 2 * num_clusters;
                if (t >= num_tiles) break;
                uint32_t now;
#pragma unroll 1
                for (uint32_t spins = 0; spins < 16384; spins++) {
                    const uint32_t issued = uniform(lds32(bars + ISSUED_AT));
                    now = timer_ns();
                    const int lead = max((int)TP(LEAD_B), (int)TP(LEAD_A) - (max((int)issued - (int)TP(LEAD_F), 0) * (int)TP(LEAD_S) >> 4));
                    if ((int32_t)(now - due) >= 0) {
                        if (cluster + piece * step <= issued + lead) break;
                        due = now;
                    }
                    __nanosleep(20);
                }
                if ((int32_t)(now - TP(PM_SLACK) - due) > 0) due = now - TP(PM_SLACK);
                due += piece < TP(PM_E1) ? TP(PM_DT1) : piece < TP(PM_E2) ? TP(PM_DT2) : piece < TP(PM_E3) ? TP(PM_DT3) : TP(PM_DT4);
                const uint8_t* p = x_raw + (size_t)t * STAGE_BYTES + rank * HALF_BYTES + (piece % 2) * 12288 + lane * 128;
#pragma unroll
                for (int k = 0; k < 3; k++) asm volatile("prefetch.global.L2 [%0];" ::"l"(p + k * 4096) : "memory");
                if (piece % 2 == 0) TR(14, piece / 2);
            }
            cluster_wait();
        }
    }
}

typedef CUresult (*EncodeTiledFn)(CUtensorMap*, CUtensorMapDataType, cuuint32_t, void*, const cuuint64_t*,
                                  const cuuint64_t*, const cuuint32_t*, const cuuint32_t*, CUtensorMapInterleave,
                                  CUtensorMapSwizzle, CUtensorMapL2promotion, CUtensorMapFloatOOBfill);

}

extern "C" void kernel_launch(void* const* d_in, const int* in_sizes, int n_in, void* d_out, int out_size) {
    (void)n_in;
    (void)out_size;
    void* x = d_in[0];
    void* w = d_in[1];
    const uint16_t* b = (const uint16_t*)d_in[2];
    const int M = in_sizes[0] / C;
    const int num_tiles = M / TILE_PIX;

    static EncodeTiledFn encode = nullptr;
    static int sms = 0;
    if (!encode) {
        void* fn = nullptr;
        cudaDriverEntryPointQueryResult q;
        cudaGetDriverEntryPoint("cuTensorMapEncodeTiled", &fn, cudaEnableDefault, &q);
        encode = (EncodeTiledFn)fn;
        cudaDeviceGetAttribute(&sms, cudaDevAttrMultiProcessorCount, 0);
        cudaFuncSetAttribute(conv1x1_kernel, cudaFuncAttributeMaxDynamicSharedMemorySize, SMEM_TOTAL);
    }

    Maps maps;
    const cuuint32_t ones[4] = {1, 1, 1, 1};
    auto make = [&](CUtensorMap* map, int rank, void* base, const cuuint64_t* dims, const cuuint64_t* strides,
                    const cuuint32_t* box, CUtensorMapL2promotion promo) {
        encode(map, CU_TENSOR_MAP_DATA_TYPE_BFLOAT16, rank, base, dims, strides, box, ones, CU_TENSOR_MAP_INTERLEAVE_NONE,
               CU_TENSOR_MAP_SWIZZLE_128B, promo, CU_TENSOR_MAP_FLOAT_OOB_FILL_NONE);
    };
    {
        const cuuint64_t dims[4]    = {64, 8, 6, (cuuint64_t)(M / 8)};
        const cuuint64_t strides[3] = {C * 2, 128, 8 * C * 2};
        const cuuint32_t box[4]     = {64, 8, 6, TILE_PIX / 16};
        make(&maps.x, 4, x, dims, strides, box, CU_TENSOR_MAP_L2_PROMOTION_L2_128B);
    }
    {
        const cuuint64_t dims[3]    = {C, C / 2, 2};
        const cuuint64_t strides[2] = {C * 2, C * C};
        const cuuint32_t box[3]     = {64, C / 2, 2};
        make(&maps.w, 3, w, dims, strides, box, CU_TENSOR_MAP_L2_PROMOTION_L2_128B);
    }
    {
        const cuuint64_t dims[2]    = {C, (cuuint64_t)M};
        const cuuint64_t strides[1] = {C * 2};
        const cuuint32_t box[2]     = {64, TILE_PIX};
        make(&maps.out, 2, d_out, dims, strides, box, CU_TENSOR_MAP_L2_PROMOTION_NONE);
    }

    const Tune tune;
    int clusters = sms / 2;
    if (clusters > num_tiles) clusters = num_tiles;
    conv1x1_kernel<<<clusters * 2, THREADS, SMEM_TOTAL>>>((const uint8_t*)x, (const uint8_t*)w, b, (uint32_t)num_tiles,
                                                          (uint32_t)clusters, maps, tune);
}
```

```cpp
#include <cuda_runtime.h>
#include <cuda_bf16.h>
#include <cuda.h>
#include <stdint.h>

#define EARLY_AT 18

#define W_FIRST 2
#define PRE_X 1
#define PRE_D0 100
#define PRE_DT 300
#define PRE_NEAR 1
#define PRE_W 64

#define TUNABLES(F) \
    F(EARLY_TILES, 462)    \
    F(EARLY_HEAD, 1584)       \
    F(PM_T0, 150)            \
    F(PM_DT1, 400)         \
    F(PM_E1, 8) \
    F(PM_DT2, 475) \
    F(PM_E2, 23) \
    F(PM_DT3, 820) \
    F(PM_E3, 61) \
    F(PM_DT4, 650) \
    F(PM_E4, 72) \
    F(PM_STAG, 210)        \
    F(LEAD_A, 280)        \
    F(LEAD_F, 500)         \
    F(LEAD_S, 3)           \
    F(LEAD_B, 151)        \
    F(PM_SLACK, 600)    \
    F(EF_TAIL, 500)        \
    F(ST_AT, 2)            \
    F(ST_T0, 6800)         \
    F(ST_STAG, 32)          \
    F(ST_P1, 2030)         \
    F(ST_E1, 9) \
    F(ST_P2, 1870) \
    F(ST_E2, 18) \
    F(ST_P3, 1970) \
    F(ST_SLACK, 400)       \
    F(SW_J, 12)            \
    F(SW_D, 7800)          \
    F(ST_PT, 1620)         \
    F(SW_D1, 3050)         \
    F(ST_PU, 460)          \
    F(SW_K1, 0)            \
    F(SW_K2, 10) \
    F(CC_AT, 22)           \
    F(CC_L0, 1300)         \
    F(CC_G, 12)             \
    F(CC_STEP, 600)        \
    F(CC_CAP, 1100)        \
    F(HOLD_T, 100)         \
    F(X0, 0) \
    F(X1, 0) \
    F(X2, 0) \
    F(X3, 0)

struct Tune {
#define F(n, v) static constexpr uint32_t n = v;
    TUNABLES(F)
#undef F
};
#define TP(n) (Tune::n)

#define TRV(slot, idx, v)
#define TR(slot, idx)
#define TRE(slot, idx)

namespace {

constexpr int C            = 384;
constexpr int TILE_PIX     = 64;
constexpr int STAGES       = 3;
constexpr int STAGE_BYTES  = TILE_PIX * C * 2;
constexpr int HALF_BYTES   = STAGE_BYTES / 2;
constexpr int SLICE_BYTES  = TILE_PIX * 128;
constexpr int W_LINES      = C * C * 2 / 128;
constexpr int NUM_WG       = 3;
constexpr int THREADS      = (NUM_WG + 1) * 128;
constexpr int SMEM_OUT     = STAGES * STAGE_BYTES;
constexpr int SMEM_BAR     = SMEM_OUT + STAGES * HALF_BYTES;
constexpr int SMEM_TOTAL   = SMEM_BAR + 512 + 1024;
constexpr uint32_t SPIN_LIMIT = 1u << 24;
constexpr int BAR_W     = 0;
constexpr int BAR_FULL  = 32;
constexpr int BAR_EMPTY = BAR_FULL + 32;
constexpr int BAR_OFREE = BAR_EMPTY + 32;
constexpr int BAR_OFULL = BAR_OFREE + 32 * STAGES;
constexpr int ISSUED_AT = BAR_OFULL + 32 * STAGES;
constexpr int DELAY_AT  = ISSUED_AT + 4;
constexpr int STAMP_AT  = DELAY_AT + 4;
constexpr uint64_t EVICT_NORMAL = 0x1000000000000000ull;
constexpr uint64_t EVICT_FIRST  = 0x12F0000000000000ull;

struct Maps {
    CUtensorMap w, x, out;
};

#define ELECT "{\n.reg .pred e;\nelect.sync _|e, 0xffffffff;\n@e "

__device__ __forceinline__ uint32_t smem_u32(const void* p) {
    return (uint32_t)__cvta_generic_to_shared(p);
}
__device__ __forceinline__ void mbar_init_1(uint32_t bar, uint32_t count) {
    asm volatile(ELECT "mbarrier.init.shared::cta.b64 [%0], %1;\n}" ::"r"(bar), "r"(count) : "memory");
}
__device__ __forceinline__ void mbar_expect_tx_1(uint32_t bar, uint32_t bytes) {
    asm volatile(ELECT "mbarrier.arrive.expect_tx.shared::cta.b64 _, [%0], %1;\n}" ::"r"(bar), "r"(bytes) : "memory");
}
__device__ __forceinline__ void mbar_arrive_1(uint32_t bar) {
    asm volatile(ELECT "mbarrier.arrive.shared::cta.b64 _, [%0];\n}" ::"r"(bar) : "memory");
}
__device__ __forceinline__ void mbar_wait(uint32_t bar, uint32_t parity) {
    uint32_t done;
    uint32_t spins = 0;
    do {
        asm volatile(
            "{\n.reg .pred p;\n"
            "mbarrier.try_wait.parity.shared::cta.b64 p, [%1], %2;\n"
            "selp.u32 %0, 1, 0, p;\n}"
            : "=r"(done) : "r"(bar), "r"(parity) : "memory");
    } while (!done && ++spins < SPIN_LIMIT);
}
__device__ __forceinline__ void mbar_wait_w(uint32_t bar, uint32_t parity) {
    mbar_wait(bar, parity);
    __syncwarp();
}
__device__ __forceinline__ bool mbar_test_w(uint32_t bar, uint32_t parity) {
    uint32_t done;
    asm volatile(
        "{\n.reg .pred p;\n"
        "mbarrier.test_wait.parity.shared::cta.b64 p, [%1], %2;\n"
        "selp.u32 %0, 1, 0, p;\n}"
        : "=r"(done) : "r"(bar), "r"(parity) : "memory");
    return __all_sync(0xffffffffu, done);
}
__device__ __forceinline__ void mbar_arrive_cta(uint32_t bar, uint32_t cta) {
    asm volatile(
        "{\n.reg .b32 ra;\n"
        "mapa.shared::cluster.u32 ra, %0, %1;\n"
        "mbarrier.arrive.shared::cluster.b64 _, [ra];\n}"
        ::"r"(bar), "r"(cta) : "memory");
}
__device__ __forceinline__ uint32_t lds32(uint32_t addr) {
    uint32_t v;
    asm volatile("ld.shared.b32 %0, [%1];" : "=r"(v) : "r"(addr) : "memory");
    return v;
}
__device__ __forceinline__ uint32_t uniform(uint32_t v) {
    return __shfl_sync(0xffffffffu, v, 0);
}
__device__ __forceinline__ void sts32(uint32_t addr, uint32_t v) {
    asm volatile("st.shared.b32 [%0], %1;" ::"r"(addr), "r"(v) : "memory");
}
__device__ __forceinline__ void tma_load_w_1(uint32_t dst, const CUtensorMap* map, uint32_t bar, int n) {
    asm volatile(
        ELECT "cp.async.bulk.tensor.3d.shared::cluster.global.mbarrier::complete_tx::bytes [%0], [%1, {%3, %4, %4}], [%2];\n}"
        ::"r"(dst), "l"(map), "r"(bar), "r"(n), "r"(0) : "memory");
}
__device__ __forceinline__ void tma_load_x_1(uint32_t dst, const CUtensorMap* map, uint32_t bar, int group, uint64_t policy) {
    asm volatile(
        ELECT "cp.async.bulk.tensor.4d.shared::cluster.global.mbarrier::complete_tx::bytes.multicast::cluster.L2::cache_hint"
        " [%0], [%1, {%3, %3, %3, %4}], [%2], %5, %6;\n}"
        ::"r"(dst), "l"(map), "r"(bar), "r"(0), "r"(group), "h"((uint16_t)3), "l"(policy) : "memory");
}
__device__ __forceinline__ void tma_store_1(const CUtensorMap* map, uint32_t src, int ch, int pix) {
    asm volatile(
        ELECT "cp.async.bulk.tensor.2d.global.shared::cta.bulk_group [%0, {%2, %3}], [%1];\n}\n"
        "cp.async.bulk.commit_group;"
        ::"l"(map), "r"(src), "r"(ch), "r"(pix) : "memory");
}
template <int N>
__device__ __forceinline__ void stores_read_wait() {
    asm volatile("cp.async.bulk.wait_group.read %0;" ::"n"(N) : "memory");
}
__device__ __forceinline__ void prefetch_map_1(const CUtensorMap* map) {
    asm volatile(ELECT "prefetch.tensormap [%0];\n}" ::"l"(map) : "memory");
}
__device__ __forceinline__ uint32_t timer_ns() {
    uint32_t t;
    asm volatile("mov.u32 %0, %%globaltimer_lo;" : "=r"(t)::"memory");
    return t;
}
__device__ __forceinline__ void cluster_arrive() {
    asm volatile("barrier.cluster.arrive.relaxed.aligned;" ::: "memory");
}
__device__ __forceinline__ void cluster_wait() {
    asm volatile("barrier.cluster.wait.aligned;" ::: "memory");
}
__device__ __forceinline__ void publish_barriers() {
    asm volatile("fence.mbarrier_init.release.cluster;" ::: "memory");
    asm volatile("fence.proxy.async.shared::cta;" ::: "memory");
}

__device__ __forceinline__ void wgmma_rs_n64(float (&d)[32], const uint32_t* a, uint64_t desc, int scale_d) {
    asm volatile(
        "{\n.reg .pred p;\n"
        "setp.ne.b32 p, %37, 0;\n"
        "wgmma.mma_async.sync.aligned.m64n64k16.f32.bf16.bf16 "
        "{%0, %1, %2, %3, %4, %5, %6, %7, %8, %9, %10, %11, %12, %13, %14, %15, "
        "%16, %17, %18, %19, %20, %21, %22, %23, %24, %25, %26, %27, %28, %29, %30, %31}, "
        "{%32, %33, %34, %35}, %36, p, 1, 1, 0;\n}"
        : "+f"(d[0]), "+f"(d[1]), "+f"(d[2]), "+f"(d[3]), "+f"(d[4]), "+f"(d[5]), "+f"(d[6]), "+f"(d[7]),
          "+f"(d[8]), "+f"(d[9]), "+f"(d[10]), "+f"(d[11]), "+f"(d[12]), "+f"(d[13]), "+f"(d[14]), "+f"(d[15]),
          "+f"(d[16]), "+f"(d[17]), "+f"(d[18]), "+f"(d[19]), "+f"(d[20]), "+f"(d[21]), "+f"(d[22]), "+f"(d[23]),
          "+f"(d[24]), "+f"(d[25]), "+f"(d[26]), "+f"(d[27]), "+f"(d[28]), "+f"(d[29]), "+f"(d[30]), "+f"(d[31])
        : "r"(a[0]), "r"(a[1]), "r"(a[2]), "r"(a[3]), "l"(desc), "r"(scale_d));
}

__device__ __forceinline__ uint32_t pack_bias(float lo, float hi, uint32_t bias2) {
    uint32_t r;
    asm("{\n.reg .b32 t;\n"
        "cvt.rn.bf16x2.f32 t, %2, %1;\n"
        "add.rn.bf16x2 %0, t, %3;\n}"
        : "=r"(r) : "f"(lo), "f"(hi), "r"(bias2));
    return r;
}

__device__ __forceinline__ int slice_channel(uint32_t rank, int wg) {
    return (wg * 2 + rank) * 64;
}

struct Consumer {
    uint32_t wreg[96];
    uint32_t bias_lo, bias_hi, st_addr, bars;
    uint64_t desc_base;
    int wg, lane;
};
struct Ring {
    uint32_t s, parity;
    __device__ __forceinline__ void advance() {
        if (++s == STAGES) {
            s = 0;
            parity ^= 1;
        }
    }
};
__device__ __forceinline__ uint32_t w_stage(int wg) {
    return (wg + 1) * STAGE_BYTES + (wg == 2 ? HALF_BYTES : 0);
}

__device__ __forceinline__ void multiply(const Consumer& c, const Ring& r, float (&acc)[32], uint32_t i, bool early) {
    const int next_turn = 4 + (c.wg + 1) % NUM_WG;
    if ((i | c.wg) != 0) asm volatile("bar.sync %0, 256;" ::"r"(4 + c.wg) : "memory");
    TRE(1 + c.wg * 2, i);
    const uint64_t desc = c.desc_base + (uint64_t)(r.s * (STAGE_BYTES >> 4));
    asm volatile("wgmma.fence.sync.aligned;" ::: "memory");
#pragma unroll
    for (int ks = 0; ks < 24; ks++) {
        const uint64_t d = desc + (uint64_t)((ks >> 2) * 64 + (ks & 3) * 2);
        wgmma_rs_n64(acc, &c.wreg[ks * 4], d, ks != 0);
        if (ks + 1 == EARLY_AT && early) asm volatile("bar.arrive %0, 256;" ::"r"(next_turn) : "memory");
    }
    asm volatile("wgmma.commit_group.sync.aligned;" ::: "memory");
    asm volatile("wgmma.wait_group.sync.aligned 0;" ::: "memory");
#pragma unroll
    for (int j = 0; j < 32; j++) asm volatile("" : "+f"(acc[j])::"memory");
    if (!early) asm volatile("bar.arrive %0, 256;" ::"r"(next_turn) : "memory");
    TRE(2 + c.wg * 2, i);
    if (c.lane < 2) mbar_arrive_cta(c.bars + BAR_EMPTY + 8 * r.s, c.lane);
}
__device__ __forceinline__ void write_out(const Consumer& c, const Ring& r, const uint32_t (&v)[16]) {
    const uint32_t obar = c.bars + (r.s * 4 + c.wg) * 8;
    mbar_wait_w(obar + BAR_OFREE, r.parity ^ 1);
    const uint32_t dst = c.st_addr + r.s * HALF_BYTES;
#pragma unroll
    for (int j = 0; j < 4; j++) {
        asm volatile("stmatrix.sync.aligned.m8n8.x4.trans.shared.b16 [%0], {%1, %2, %3, %4};"
                     ::"r"(dst + j * 2048), "r"(v[4 * j]), "r"(v[4 * j + 1]), "r"(v[4 * j + 2]), "r"(v[4 * j + 3]) : "memory");
    }
    asm volatile("fence.proxy.async.shared::cta;" ::: "memory");
    __syncwarp();
    mbar_arrive_1(obar + BAR_OFULL);
}

template <int N>
__device__ __forceinline__ void hand_back(uint32_t& open) {
    if (open != 0) {
        stores_read_wait<N>();
        mbar_arrive_1(open);
        open = 0;
    }
}

__global__ void __cluster_dims__(2, 1, 1) __launch_bounds__(THREADS, 1)
conv1x1_kernel(const uint8_t* __restrict__ x_raw,
               const uint8_t* __restrict__ w_raw,
               const uint16_t* __restrict__ bias,
               uint32_t num_tiles,
               uint32_t num_clusters,
               const __grid_constant__ Maps maps,
               const __grid_constant__ Tune tune) {
    const uint32_t t_entry = timer_ns();
    extern __shared__ uint8_t smem_raw[];
    const uint32_t smem = (smem_u32(smem_raw) + 1023u) & ~1023u;
    const uint32_t bars = smem + SMEM_BAR;
    if (threadIdx.x < 96) {
        const uint32_t line = blockIdx.x % (W_LINES / PRE_W) * PRE_W + threadIdx.x;
        if (threadIdx.x < PRE_W) asm volatile("prefetch.global.L2 [%0];" ::"l"(w_raw + line * 128) : "memory");
    } else if (threadIdx.x < 128) {
        prefetch_map_1(&maps.w);
        prefetch_map_1(&maps.x);
    }
    if (threadIdx.x < NUM_WG * 128) cluster_arrive();
    if (threadIdx.x >= 128 && threadIdx.x < 128 + PRE_X * 96) {
        const uint8_t* p = x_raw + (size_t)blockIdx.x * HALF_BYTES + (threadIdx.x - 128) * 128;
        if (PRE_D0 + PRE_DT != 0) {
            const uint32_t wait = PRE_D0 + ((threadIdx.x - 128) >> 5) * PRE_DT;
            const uint32_t c0 = clock();
            while (clock() - c0 < wait) {}
        }
        if (PRE_NEAR == 0) asm volatile("prefetch.global.L2 [%0];" ::"l"(p) : "memory");
        if (PRE_NEAR == 1) asm volatile("cp.async.ca.shared.global.L2::128B [%0], [%1], 4;" ::"r"(bars + 384 + (threadIdx.x & 31) * 4), "l"(p) : "memory");
    }

    const int warp = uniform(threadIdx.x >> 5);
    const int lane = threadIdx.x & 31;
    const uint32_t rank         = blockIdx.x & 1;
    const uint32_t cluster      = blockIdx.x >> 1;

    if (warp < NUM_WG * 4) {
        const int wg = warp >> 2;
        const int wq = warp & 3;
        asm volatile("setmaxnreg.inc.sync.aligned.u32 160;");
        Consumer c;
        c.wg = wg;
        c.lane = lane;
        c.bars = bars;
        c.bias_lo = bias[slice_channel(rank, wg) + wq * 16 + (lane >> 2)] * 0x10001u;
        c.bias_hi = bias[slice_channel(rank, wg) + wq * 16 + (lane >> 2) + 8] * 0x10001u;

        cluster_wait();
        TRE(1 + wg, 63);
        mbar_wait_w(bars + BAR_W + 8 * wg, 0);
        TRE(4 + wg, 63);
        {
            const int r = lane & 7, m = lane >> 3;
            const uint32_t base = smem + w_stage(wg) + ((m >> 1) * 8 + r) * 128 + (((2 * wq + (m & 1)) ^ r) << 4);
#pragma unroll
            for (int ks = 0; ks < 24; ks++) {
                asm volatile("ldmatrix.sync.aligned.m8n8.x4.trans.shared.b16 {%0, %1, %2, %3}, [%4];"
                             : "=r"(c.wreg[ks * 4 + 0]), "=r"(c.wreg[ks * 4 + 1]), "=r"(c.wreg[ks * 4 + 2]), "=r"(c.wreg[ks * 4 + 3])
                             : "r"(base + ks * 2048) : "memory");
            }
        }
        uint32_t dep = 0;
#pragma unroll
        for (int ks = 0; ks < 24; ks++) dep ^= c.wreg[ks * 4];
        dep &= num_tiles >> 31;
        __syncwarp();
        if (lane < 6 && wg < 2) mbar_arrive_cta(bars + BAR_EMPTY + 8 * (wg + 1) + dep, lane & 1);
        asm volatile("cp.async.wait_all;" ::: "memory");
        TRE(1 + wg, 60);

        c.st_addr = smem + SMEM_OUT + wg * SLICE_BYTES + ((lane >> 4) * 8 + (lane & 7)) * 128 + (((2 * wq + ((lane >> 3) & 1)) ^ (lane & 7)) << 4);
        c.desc_base = (uint64_t)((smem & 0x3FFFF) >> 4) | ((uint64_t)1 << 16) | ((uint64_t)(6144 >> 4) << 32) | ((uint64_t)1 << 62);

        float acc[32];
        uint32_t packed[16];
        Ring r = {0, uniform(dep)}, o = r;
        bool held = false;
        for (uint32_t i = 0, id = cluster; id < num_tiles; i++, id += num_clusters, r.advance()) {
            mbar_wait(bars + BAR_FULL + 8 * r.s, r.parity);
            multiply(c, r, acc, i, id + TP(EARLY_TILES) >= num_tiles || id + 1 <= TP(EARLY_HEAD));
            if (held) write_out(c, o, packed);
            o = r;
#pragma unroll
            for (int j = 0; j < 16; j++) packed[j] = pack_bias(acc[2 * j], acc[2 * j + 1], j & 1 ? c.bias_hi : c.bias_lo);
            held = id + TP(HOLD_T) < num_tiles && !mbar_test_w(bars + BAR_OFREE + (o.s * 4 + wg) * 8, o.parity ^ 1);
            if (!held) write_out(c, o, packed);
            TRE(8 + wg, i);
        }
        if (held) write_out(c, o, packed);
        if (wg == 0) asm volatile("bar.sync 4, 256;" ::: "memory");
        TRE(1 + wg, 62);
    } else {
        asm volatile("setmaxnreg.dec.sync.aligned.u32 32;");
        if (warp == NUM_WG * 4) {
#pragma unroll
            for (int j = 0; j < NUM_WG; j++) mbar_init_1(bars + BAR_W + 8 * j, 1);
            publish_barriers();
            cluster_arrive();
#pragma unroll
            for (int j = 0; j < NUM_WG; j++) {
                if (j == W_FIRST) {
                    cluster_wait();
                    TR(0, 0);
                    mbar_expect_tx_1(bars + BAR_FULL, STAGE_BYTES);
                    tma_load_x_1(smem + rank * HALF_BYTES, &maps.x, bars + BAR_FULL, cluster * 8 + rank * 4, EVICT_NORMAL);
                }
                mbar_expect_tx_1(bars + BAR_W + 8 * j, STAGE_BYTES);
                tma_load_w_1(smem + w_stage(j), &maps.w, bars + BAR_W + 8 * j, slice_channel(rank, j));
                if (j == 0) TR(2, 61);
            }
            Ring r = {1, 0};
#pragma unroll 1
            for (uint32_t i = 1, id = cluster + num_clusters; id < num_tiles; i++, id += num_clusters, r.advance()) {
                mbar_wait_w(bars + BAR_EMPTY + 8 * r.s, r.parity ^ (r.s == 0));
                sts32(bars + ISSUED_AT, id);
                sts32(bars + STAMP_AT + 4 * r.s, timer_ns());
                TR(0, i);
                TRV(15, i, id);
                const uint32_t full = bars + BAR_FULL + 8 * r.s;
                mbar_expect_tx_1(full, STAGE_BYTES);
                tma_load_x_1(smem + r.s * STAGE_BYTES + rank * HALF_BYTES, &maps.x, full, id * 8 + rank * 4,
                             id + TP(EF_TAIL) >= num_tiles ? EVICT_FIRST : EVICT_NORMAL);
            }
#pragma unroll 1
            for (int k = 0; k < STAGES; k++, r.advance()) mbar_wait_w(bars + BAR_EMPTY + 8 * r.s, r.parity ^ (r.s == 0));
        } else if (warp == NUM_WG * 4 + 1) {
#pragma unroll
            for (int s = 0; s < STAGES; s++) {
                mbar_init_1(bars + BAR_FULL + 8 * s, 1);
                mbar_init_1(bars + BAR_EMPTY + 8 * s, NUM_WG * 4 * 2);
            }
            publish_barriers();
            cluster_arrive();
            TR(0, 61);
            cluster_wait();
            prefetch_map_1(&maps.out);
            uint32_t delay = 0;
            Ring r = {0, 0};
#pragma unroll 1
            for (uint32_t i = 0, id = cluster; id < num_tiles; i++, id += num_clusters, r.advance()) {
                mbar_wait_w(bars + BAR_FULL + 8 * r.s, r.parity);
                TR(7, i);
                const int late = (int)(timer_ns() - lds32(bars + STAMP_AT + 4 * r.s) - TP(CC_L0));
                if (i >= TP(CC_AT) && late > 0) {
                    delay = min(delay + min((uint32_t)late * TP(CC_G) >> 4, TP(CC_STEP)), TP(CC_CAP));
                    sts32(bars + DELAY_AT, delay);
                }
            }
        } else if (warp == NUM_WG * 4 + 2) {
            sts32(bars + DELAY_AT, 0);
            uint32_t due = t_entry + TP(ST_T0) + cluster * TP(ST_STAG) - TP(ST_P1);
#pragma unroll
            for (int b = 0; b < STAGES; b++) {
#pragma unroll
                for (int w = 0; w < NUM_WG; w++) {
                    mbar_init_1(bars + BAR_OFREE + b * 32 + w * 8, 1);
                    mbar_init_1(bars + BAR_OFULL + b * 32 + w * 8, 4);
                }
            }
            publish_barriers();
            cluster_arrive();
            cluster_wait();
            const uint32_t mark = num_tiles / num_clusters - TP(SW_J);
            const int behind = cluster < num_tiles % num_clusters ? cluster : cluster - num_clusters;
            const float stage1 = (float)((int)TP(SW_D1) + behind * ((int)TP(SW_K1) - (int)TP(SW_K2)));
            uint32_t open = 0, t_end = 0, delay = 0;
            Ring o = {0, 0};
#pragma unroll 1
            for (uint32_t j = 0, id = cluster; id < num_tiles; j++, id += num_clusters, o.advance()) {
                const uint32_t parity = o.parity;
                const uint32_t obar = bars + o.s * 32;
                if (!mbar_test_w(obar + BAR_OFULL, parity)) {
                    hand_back<0>(open);
                    mbar_wait_w(obar + BAR_OFULL, parity);
                }
                const uint32_t src = smem + SMEM_OUT + o.s * HALF_BYTES;
                const uint32_t period = j <= TP(ST_E1) ? TP(ST_P1) : j <= TP(ST_E2) ? TP(ST_P2) : TP(ST_P3);
                uint32_t now = timer_ns();
                if (j >= TP(ST_AT)) {
                    if (j <= mark || (int32_t)(due + period - t_end) <= 0) {
                        due += period;
                    } else {
                        float t = (float)(int32_t)(due - t_end), rest = 1.f;
                        if (t < 0.f) {
                            rest += __fdividef(t, (float)period);
                            t = 0.f;
                        }
                        const float room = stage1 - t;
                        if (room >= rest * (float)TP(ST_PT)) {
                            t += rest * (float)TP(ST_PT);
                        } else {
                            if (room > 0.f) {
                                rest -= __fdividef(room, (float)TP(ST_PT));
                                t += room;
                            }
                            t += rest * (float)TP(ST_PU);
                        }
                        due = t_end + (int32_t)t;
                    }
#pragma unroll 1
                    for (uint32_t spins = 0; spins < SPIN_LIMIT; spins++) {
                        const uint32_t more = uniform(lds32(bars + DELAY_AT)) - delay;
                        delay += more;
                        due += more;
                        t_end += more;
                        if ((int32_t)(now - due) >= 0) break;
                        hand_back<0>(open);
                        __nanosleep(20);
                        now = timer_ns();
                    }
                }
                if (j >= TP(ST_AT) && (int32_t)(now - TP(ST_SLACK) - due) > 0) due = now - TP(ST_SLACK);
                if (j == mark) t_end = due - cluster * TP(ST_STAG) + TP(SW_D) - behind * (int)TP(SW_K1);
                const bool whole = mbar_test_w(obar + BAR_OFULL + 8, parity) && mbar_test_w(obar + BAR_OFULL + 16, parity);
                if (whole) {
                    TR(11, j);
#pragma unroll
                    for (int w = 0; w < NUM_WG; w++) tma_store_1(&maps.out, src + w * SLICE_BYTES, slice_channel(rank, w), id * TILE_PIX);
                    hand_back<3>(open);
                    stores_read_wait<2>();
                    TR(12, j);
                    mbar_arrive_1(obar + BAR_OFREE);
                    stores_read_wait<1>();
                    TR(13, j);
                    mbar_arrive_1(obar + BAR_OFREE + 8);
                    open = obar + BAR_OFREE + 16;
                } else {
#pragma unroll 1
                    for (uint32_t w = 0; w < NUM_WG; w++) {
                        if (!mbar_test_w(obar + BAR_OFULL + w * 8, parity)) {
                            hand_back<0>(open);
                            mbar_wait_w(obar + BAR_OFULL + w * 8, parity);
                        }
                        TR(11 + w, j);
                        tma_store_1(&maps.out, src + w * SLICE_BYTES, slice_channel(rank, w), id * TILE_PIX);
                        hand_back<1>(open);
                        open = obar + BAR_OFREE + w * 8;
                    }
                }
            }
            stores_read_wait<0>();
            TR(4, 62);
        } else {
            uint32_t due = t_entry + TP(PM_T0) + (blockIdx.x & 3) * TP(PM_STAG);
            sts32(bars + ISSUED_AT, 0);
            cluster_arrive();
            const uint32_t step = num_clusters / 2;
#pragma unroll 1
            for (uint32_t piece = PRE_X; piece < TP(PM_E4); piece++) {
                const uint32_t t = cluster + piece / 2 * num_clusters;
                if (t >= num_tiles) break;
                uint32_t now;
#pragma unroll 1
                for (uint32_t spins = 0; spins < 16384; spins++) {
                    const uint32_t issued = uniform(lds32(bars + ISSUED_AT));
                    now = timer_ns();
                    const int lead = max((int)TP(LEAD_B), (int)TP(LEAD_A) - (max((int)issued - (int)TP(LEAD_F), 0) * (int)TP(LEAD_S) >> 4));
                    if ((int32_t)(now - due) >= 0) {
                        if (cluster + piece * step <= issued + lead) break;
                        due = now;
                    }
                    __nanosleep(20);
                }
                if ((int32_t)(now - TP(PM_SLACK) - due) > 0) due = now - TP(PM_SLACK);
                due += piece < TP(PM_E1) ? TP(PM_DT1) : piece < TP(PM_E2) ? TP(PM_DT2) : piece < TP(PM_E3) ? TP(PM_DT3) : TP(PM_DT4);
                const uint8_t* p = x_raw + (size_t)t * STAGE_BYTES + rank * HALF_BYTES + (piece % 2) * 12288 + lane * 128;
#pragma unroll
                for (int k = 0; k < 3; k++) asm volatile("prefetch.global.L2 [%0];" ::"l"(p + k * 4096) : "memory");
                if (piece % 2 == 0) TR(14, piece / 2);
            }
            cluster_wait();
        }
    }
}

typedef CUresult (*EncodeTiledFn)(CUtensorMap*, CUtensorMapDataType, cuuint32_t, void*, const cuuint64_t*,
                                  const cuuint64_t*, const cuuint32_t*, const cuuint32_t*, CUtensorMapInterleave,
                                  CUtensorMapSwizzle, CUtensorMapL2promotion, CUtensorMapFloatOOBfill);

}

extern "C" void kernel_launch(void* const* d_in, const int* in_sizes, int n_in, void* d_out, int out_size) {
    (void)n_in;
    (void)out_size;
    void* x = d_in[0];
    void* w = d_in[1];
    const uint16_t* b = (const uint16_t*)d_in[2];
    const int M = in_sizes[0] / C;
    const int num_tiles = M / TILE_PIX;

    static EncodeTiledFn encode = nullptr;
    static int sms = 0;
    if (!encode) {
        void* fn = nullptr;
        cudaDriverEntryPointQueryResult q;
        cudaGetDriverEntryPoint("cuTensorMapEncodeTiled", &fn, cudaEnableDefault, &q);
        encode = (EncodeTiledFn)fn;
        cudaDeviceGetAttribute(&sms, cudaDevAttrMultiProcessorCount, 0);
        cudaFuncSetAttribute(conv1x1_kernel, cudaFuncAttributeMaxDynamicSharedMemorySize, SMEM_TOTAL);
    }

    Maps maps;
    const cuuint32_t ones[4] = {1, 1, 1, 1};
    auto make = [&](CUtensorMap* map, int rank, void* base, const cuuint64_t* dims, const cuuint64_t* strides,
                    const cuuint32_t* box, CUtensorMapL2promotion promo) {
        encode(map, CU_TENSOR_MAP_DATA_TYPE_BFLOAT16, rank, base, dims, strides, box, ones, CU_TENSOR_MAP_INTERLEAVE_NONE,
               CU_TENSOR_MAP_SWIZZLE_128B, promo, CU_TENSOR_MAP_FLOAT_OOB_FILL_NONE);
    };
    {
        const cuuint64_t dims[4]    = {64, 8, 6, (cuuint64_t)(M / 8)};
        const cuuint64_t strides[3] = {C * 2, 128, 8 * C * 2};
        const cuuint32_t box[4]     = {64, 8, 6, TILE_PIX / 16};
        make(&maps.x, 4, x, dims, strides, box, CU_TENSOR_MAP_L2_PROMOTION_L2_128B);
    }
    {
        const cuuint64_t dims[3]    = {C, C / 2, 2};
        const cuuint64_t strides[2] = {C * 2, C * C};
        const cuuint32_t box[3]     = {64, C / 2, 2};
        make(&maps.w, 3, w, dims, strides, box, CU_TENSOR_MAP_L2_PROMOTION_L2_128B);
    }
    {
        const cuuint64_t dims[2]    = {C, (cuuint64_t)M};
        const cuuint64_t strides[1] = {C * 2};
        const cuuint32_t box[2]     = {64, TILE_PIX};
        make(&maps.out, 2, d_out, dims, strides, box, CU_TENSOR_MAP_L2_PROMOTION_NONE);
    }

    const Tune tune;
    int clusters = sms / 2;
    if (clusters > num_tiles) clusters = num_tiles;
    conv1x1_kernel<<<clusters * 2, THREADS, SMEM_TOTAL>>>((const uint8_t*)x, (const uint8_t*)w, b, (uint32_t)num_tiles,
                                                          (uint32_t)clusters, maps, tune);
}
```

```cpp
#include <cuda_runtime.h>
#include <cuda_bf16.h>
#include <cuda.h>
#include <stdint.h>

#define TUNABLES(F) \
    F(PM_T0, 150)        \
    F(PM_STAG, 210)      \
    F(PM_DT1, 400)       \
    F(PM_E1, 8) \
    F(PM_DT2, 475) \
    F(PM_E2, 23) \
    F(PM_DT3, 820) \
    F(PM_SLACK, 600)     \
    F(LEAD_A, 280)       \
    F(LEAD_F, 500)       \
    F(LEAD_S, 3)         \
    F(LEAD_B, 151)       \
    F(EF_TAIL, 500)      \
    F(ST_AT, 2)          \
    F(ST_T0, 6800)       \
    F(ST_STAG, 32)       \
    F(ST_P1, 2030)       \
    F(ST_E1, 9) \
    F(ST_P2, 1870) \
    F(ST_E2, 18) \
    F(ST_P3, 1970) \
    F(ST_SLACK, 400)     \
    F(SW_J, 12)          \
    F(SW_D, 7800)        \
    F(ST_PT, 1670)       \
    F(SW_D1, 3050)       \
    F(SW_K, 10)          \
    F(CC_AT, 22)         \
    F(CC_L0, 1300)       \
    F(CC_G, 12)          \
    F(CC_STEP, 600)      \
    F(CC_CAP, 1100)

struct Tune {
#define F(n, v) uint32_t n = v;
    TUNABLES(F)
#undef F
};

#define TRV(slot, idx, v)
#define TR(slot, idx)
#define TRE(slot, idx)
#define TRACE_BYTES 0

namespace {

constexpr int C            = 384;
constexpr int TILE_PIX     = 64;
constexpr int STAGES       = 3;
constexpr int STAGE_BYTES  = TILE_PIX * C * 2;
constexpr int HALF_BYTES   = STAGE_BYTES / 2;
constexpr int PIECE_BYTES  = HALF_BYTES / 2;
constexpr int SLICE_BYTES  = TILE_PIX * 128;
constexpr int NUM_WG       = 3;
constexpr int THREADS      = (NUM_WG + 1) * 128;
constexpr int SMEM_OUT     = STAGES * STAGE_BYTES;
constexpr int SMEM_BAR     = SMEM_OUT + STAGES * HALF_BYTES;
constexpr int SMEM_TOTAL   = SMEM_BAR + 512 + TRACE_BYTES + 1024;
constexpr int HAND_AT      = 18;
constexpr int W_FIRST      = 2;
constexpr int W_LINES      = C * C * 2 / 128;
constexpr int PRE_W        = 64;
constexpr int PRE_D0       = 100;
constexpr int PRE_DT       = 300;
constexpr uint32_t SPIN_LIMIT = 1u << 22;
constexpr int BAR_W     = 0;
constexpr int BAR_FULL  = 32;
constexpr int BAR_EMPTY = 64;
constexpr int BAR_OFREE = 96;
constexpr int BAR_OFULL = BAR_OFREE + 32 * STAGES;
constexpr int ISSUED_AT = BAR_OFULL + 32 * STAGES;
constexpr int DELAY_AT  = ISSUED_AT + 4;
constexpr int STAMP_AT  = DELAY_AT + 4;
constexpr int SINK_AT   = 384;

struct Maps {
    CUtensorMap w, x, out;
};

#define ELECT "{\n.reg .pred e;\nelect.sync _|e, 0xffffffff;\n@e "

__device__ __forceinline__ uint32_t smem_u32(const void* p) {
    return (uint32_t)__cvta_generic_to_shared(p);
}
__device__ __forceinline__ void mbar_init_1(uint32_t bar, uint32_t count) {
    asm volatile(ELECT "mbarrier.init.shared::cta.b64 [%0], %1;\n}" ::"r"(bar), "r"(count) : "memory");
}
__device__ __forceinline__ void mbar_expect_tx_1(uint32_t bar, uint32_t bytes) {
    asm volatile(ELECT "mbarrier.arrive.expect_tx.shared::cta.b64 _, [%0], %1;\n}" ::"r"(bar), "r"(bytes) : "memory");
}
__device__ __forceinline__ void mbar_arrive_1(uint32_t bar) {
    asm volatile(ELECT "mbarrier.arrive.shared::cta.b64 _, [%0];\n}" ::"r"(bar) : "memory");
}
__device__ __forceinline__ void mbar_wait(uint32_t bar, uint32_t parity) {
    uint32_t done;
    uint32_t spins = 0;
    do {
        asm volatile(
            "{\n.reg .pred p;\n"
            "mbarrier.try_wait.parity.shared::cta.b64 p, [%1], %2;\n"
            "selp.u32 %0, 1, 0, p;\n}"
            : "=r"(done) : "r"(bar), "r"(parity) : "memory");
    } while (!done && ++spins < SPIN_LIMIT);
    __syncwarp();
}
__device__ __forceinline__ bool mbar_test(uint32_t bar, uint32_t parity) {
    uint32_t done;
    asm volatile(
        "{\n.reg .pred p;\n"
        "mbarrier.test_wait.parity.shared::cta.b64 p, [%1], %2;\n"
        "selp.u32 %0, 1, 0, p;\n}"
        : "=r"(done) : "r"(bar), "r"(parity) : "memory");
    return __all_sync(0xffffffffu, done);
}
__device__ __forceinline__ void mbar_arrive_cta(uint32_t bar, uint32_t cta) {
    asm volatile(
        "{\n.reg .b32 ra;\n"
        "mapa.shared::cluster.u32 ra, %0, %1;\n"
        "mbarrier.arrive.shared::cluster.b64 _, [ra];\n}"
        ::"r"(bar), "r"(cta) : "memory");
}
__device__ __forceinline__ uint32_t lds32(uint32_t addr) {
    uint32_t v;
    asm volatile("ld.volatile.shared.b32 %0, [%1];" : "=r"(v) : "r"(addr) : "memory");
    return v;
}
__device__ __forceinline__ void sts32(uint32_t addr, uint32_t v) {
    asm volatile("st.volatile.shared.b32 [%0], %1;" ::"r"(addr), "r"(v) : "memory");
}
__device__ __forceinline__ uint32_t uniform(uint32_t v) {
    return __shfl_sync(0xffffffffu, v, 0);
}
__device__ __forceinline__ void tma_load_w_1(uint32_t dst, const CUtensorMap* map, uint32_t bar, int n) {
    asm volatile(
        ELECT "cp.async.bulk.tensor.3d.shared::cluster.global.mbarrier::complete_tx::bytes [%0], [%1, {%3, %4, %4}], [%2];\n}"
        ::"r"(dst), "l"(map), "r"(bar), "r"(n), "r"(0) : "memory");
}
__device__ __forceinline__ void tma_load_x_1(uint32_t dst, const CUtensorMap* map, uint32_t bar, int group) {
    asm volatile(
        ELECT "cp.async.bulk.tensor.4d.shared::cluster.global.mbarrier::complete_tx::bytes.multicast::cluster"
        " [%0], [%1, {%3, %3, %3, %4}], [%2], %5;\n}"
        ::"r"(dst), "l"(map), "r"(bar), "r"(0), "r"(group), "h"((uint16_t)3) : "memory");
}
__device__ __forceinline__ void tma_load_x_evict_first_1(uint32_t dst, const CUtensorMap* map, uint32_t bar, int group) {
    asm volatile(
        "{\n.reg .b64 pol;\n"
        "createpolicy.fractional.L2::evict_first.b64 pol, 1.0;\n"
        ELECT "cp.async.bulk.tensor.4d.shared::cluster.global.mbarrier::complete_tx::bytes.multicast::cluster.L2::cache_hint"
        " [%0], [%1, {%3, %3, %3, %4}], [%2], %5, pol;\n}\n}"
        ::"r"(dst), "l"(map), "r"(bar), "r"(0), "r"(group), "h"((uint16_t)3) : "memory");
}
__device__ __forceinline__ void tma_store_1(const CUtensorMap* map, uint32_t src, int ch, int pix) {
    asm volatile(
        ELECT "cp.async.bulk.tensor.2d.global.shared::cta.bulk_group [%0, {%2, %3}], [%1];\n}\n"
        "cp.async.bulk.commit_group;"
        ::"l"(map), "r"(src), "r"(ch), "r"(pix) : "memory");
}
template <int N>
__device__ __forceinline__ void stores_read_wait() {
    asm volatile("cp.async.bulk.wait_group.read %0;" ::"n"(N) : "memory");
}
__device__ __forceinline__ void prefetch_map_1(const CUtensorMap* map) {
    asm volatile(ELECT "prefetch.tensormap [%0];\n}" ::"l"(map) : "memory");
}
__device__ __forceinline__ void prefetch_l2(const void* p) {
    asm volatile("prefetch.global.L2 [%0];" ::"l"(p) : "memory");
}
__device__ __forceinline__ uint32_t timer_ns() {
    uint32_t t;
    asm volatile("mov.u32 %0, %%globaltimer_lo;" : "=r"(t)::"memory");
    return t;
}
__device__ __forceinline__ bool reached(uint32_t now, uint32_t t) {
    return (int32_t)(now - t) >= 0;
}
__device__ __forceinline__ void cluster_arrive() {
    asm volatile("barrier.cluster.arrive.relaxed.aligned;" ::: "memory");
}
__device__ __forceinline__ void cluster_wait() {
    asm volatile("barrier.cluster.wait.aligned;" ::: "memory");
}
__device__ __forceinline__ void publish_barriers() {
    asm volatile("fence.mbarrier_init.release.cluster;" ::: "memory");
    asm volatile("fence.proxy.async.shared::cta;" ::: "memory");
}

__device__ __forceinline__ void wgmma_rs_n64(float (&d)[32], const uint32_t* a, uint64_t desc, int scale_d) {
    asm volatile(
        "{\n.reg .pred p;\n"
        "setp.ne.b32 p, %37, 0;\n"
        "wgmma.mma_async.sync.aligned.m64n64k16.f32.bf16.bf16 "
        "{%0, %1, %2, %3, %4, %5, %6, %7, %8, %9, %10, %11, %12, %13, %14, %15, "
        "%16, %17, %18, %19, %20, %21, %22, %23, %24, %25, %26, %27, %28, %29, %30, %31}, "
        "{%32, %33, %34, %35}, %36, p, 1, 1, 0;\n}"
        : "+f"(d[0]), "+f"(d[1]), "+f"(d[2]), "+f"(d[3]), "+f"(d[4]), "+f"(d[5]), "+f"(d[6]), "+f"(d[7]),
          "+f"(d[8]), "+f"(d[9]), "+f"(d[10]), "+f"(d[11]), "+f"(d[12]), "+f"(d[13]), "+f"(d[14]), "+f"(d[15]),
          "+f"(d[16]), "+f"(d[17]), "+f"(d[18]), "+f"(d[19]), "+f"(d[20]), "+f"(d[21]), "+f"(d[22]), "+f"(d[23]),
          "+f"(d[24]), "+f"(d[25]), "+f"(d[26]), "+f"(d[27]), "+f"(d[28]), "+f"(d[29]), "+f"(d[30]), "+f"(d[31])
        : "r"(a[0]), "r"(a[1]), "r"(a[2]), "r"(a[3]), "l"(desc), "r"(scale_d));
}

__device__ __forceinline__ uint32_t pack_bias(float lo, float hi, uint32_t bias2) {
    uint32_t r;
    asm("{\n.reg .b32 t;\n"
        "cvt.rn.bf16x2.f32 t, %2, %1;\n"
        "add.rn.bf16x2 %0, t, %3;\n}"
        : "=r"(r) : "f"(lo), "f"(hi), "r"(bias2));
    return r;
}

__device__ __forceinline__ int slice_channel(uint32_t rank, int wg) {
    return (wg * 2 + rank) * 64;
}
__device__ __forceinline__ uint32_t w_stage(int wg) {
    return (wg + 1) * STAGE_BYTES + (wg == 2 ? HALF_BYTES : 0);
}

struct Ring {
    uint32_t s, parity;
    __device__ __forceinline__ void advance() {
        if (++s == STAGES) {
            s = 0;
            parity ^= 1;
        }
    }
};

__device__ __forceinline__ void write_out(uint32_t wg_bars, uint32_t st_addr, const Ring& r, const uint32_t (&v)[16]) {
    mbar_wait(wg_bars + BAR_OFREE + r.s * 32, r.parity ^ 1);
    const uint32_t dst = st_addr + r.s * HALF_BYTES;
#pragma unroll
    for (int j = 0; j < 4; j++) {
        asm volatile("stmatrix.sync.aligned.m8n8.x4.trans.shared.b16 [%0], {%1, %2, %3, %4};"
                     ::"r"(dst + j * 2048), "r"(v[4 * j]), "r"(v[4 * j + 1]), "r"(v[4 * j + 2]), "r"(v[4 * j + 3]) : "memory");
    }
    asm volatile("fence.proxy.async.shared::cta;" ::: "memory");
    __syncwarp();
    mbar_arrive_1(wg_bars + BAR_OFULL + r.s * 32);
}

template <int N>
__device__ __forceinline__ void hand_back(uint32_t& open) {
    if (open != 0) {
        stores_read_wait<N>();
        mbar_arrive_1(open);
        open = 0;
    }
}

__global__ void __cluster_dims__(2, 1, 1) __launch_bounds__(THREADS, 1)
conv1x1_kernel(const uint8_t* __restrict__ x_raw,
               const uint8_t* __restrict__ w_raw,
               const uint16_t* __restrict__ bias,
               uint32_t num_tiles,
               uint32_t num_clusters,
               const __grid_constant__ Maps maps,
               const __grid_constant__ Tune tune) {
    const uint32_t t_entry = timer_ns();
    extern __shared__ uint8_t smem_raw[];
    const uint32_t smem = (smem_u32(smem_raw) + 1023u) & ~1023u;
    const uint32_t bars = smem + SMEM_BAR;

    if (threadIdx.x < PRE_W) {
        prefetch_l2(w_raw + (blockIdx.x % (W_LINES / PRE_W) * PRE_W + threadIdx.x) * 128);
    } else if (threadIdx.x >= 96 && threadIdx.x < 128) {
        prefetch_map_1(&maps.w);
        prefetch_map_1(&maps.x);
    }
    if (threadIdx.x < NUM_WG * 128) cluster_arrive();
    if (threadIdx.x >= 128 && threadIdx.x < 128 + PIECE_BYTES / 128) {
        const uint8_t* p = x_raw + (size_t)blockIdx.x * HALF_BYTES + (threadIdx.x - 128) * 128;
        const uint32_t wait = PRE_D0 + ((threadIdx.x - 128) >> 5) * PRE_DT;
        const uint32_t c0 = clock();
        while (clock() - c0 < wait) {}
        asm volatile("cp.async.ca.shared.global.L2::128B [%0], [%1], 4;" ::"r"(bars + SINK_AT + (threadIdx.x & 31) * 4), "l"(p) : "memory");
    }
    if (threadIdx.x == 0) TRV(0, 63, t_entry);

    const int warp = uniform(threadIdx.x >> 5);
    const int lane = threadIdx.x & 31;
    const uint32_t rank    = blockIdx.x & 1;
    const uint32_t cluster = blockIdx.x >> 1;

    if (warp < NUM_WG * 4) {
        asm volatile("setmaxnreg.inc.sync.aligned.u32 160;");
        const int wg = warp >> 2;
        const int wq = warp & 3;
        const uint32_t bias_lo = bias[slice_channel(rank, wg) + wq * 16 + (lane >> 2)] * 0x10001u;
        const uint32_t bias_hi = bias[slice_channel(rank, wg) + wq * 16 + (lane >> 2) + 8] * 0x10001u;

        cluster_wait();
        TRE(1 + wg, 63);
        mbar_wait(bars + BAR_W + 8 * wg, 0);
        TRE(4 + wg, 63);
        uint32_t wreg[96];
        {
            const int r = lane & 7, m = lane >> 3;
            const uint32_t base = smem + w_stage(wg) + ((m >> 1) * 8 + r) * 128 + (((2 * wq + (m & 1)) ^ r) << 4);
#pragma unroll
            for (int ks = 0; ks < 24; ks++) {
                asm volatile("ldmatrix.sync.aligned.m8n8.x4.trans.shared.b16 {%0, %1, %2, %3}, [%4];"
                             : "=r"(wreg[ks * 4 + 0]), "=r"(wreg[ks * 4 + 1]), "=r"(wreg[ks * 4 + 2]), "=r"(wreg[ks * 4 + 3])
                             : "r"(base + ks * 2048) : "memory");
            }
        }
        uint32_t dep = 0;
#pragma unroll
        for (int ks = 0; ks < 24; ks++) dep ^= wreg[ks * 4];
        dep = uniform(dep & (num_tiles >> 31));
        if (lane < 6 && wg < 2) mbar_arrive_cta(bars + BAR_EMPTY + 8 * (wg + 1) + dep, lane & 1);
        asm volatile("cp.async.wait_all;" ::: "memory");
        TRE(1 + wg, 60);

        const uint32_t wg_bars = bars + wg * 8;
        const uint32_t st_addr = smem + SMEM_OUT + wg * SLICE_BYTES + ((lane >> 4) * 8 + (lane & 7)) * 128 +
                                 (((2 * wq + ((lane >> 3) & 1)) ^ (lane & 7)) << 4);
        const uint64_t desc_base =
            (uint64_t)((smem & 0x3FFFF) >> 4) | ((uint64_t)1 << 16) | ((uint64_t)(6144 >> 4) << 32) | ((uint64_t)1 << 62);
        const int next_turn = 4 + (wg + 1) % NUM_WG;

        float acc[32];
        uint32_t packed[16];
        Ring r = {0, dep}, o = r;
        bool held = false;
        for (uint32_t i = 0, id = cluster; id < num_tiles; i++, id += num_clusters, r.advance()) {
            mbar_wait(bars + BAR_FULL + 8 * r.s, r.parity);
            if ((i | wg) != 0) asm volatile("bar.sync %0, 256;" ::"r"(4 + wg) : "memory");
            TRE(1 + wg * 2, i);
            const uint64_t desc = desc_base + (uint64_t)(r.s * (STAGE_BYTES >> 4));
            asm volatile("wgmma.fence.sync.aligned;" ::: "memory");
#pragma unroll
            for (int ks = 0; ks < 24; ks++) {
                wgmma_rs_n64(acc, &wreg[ks * 4], desc + (uint64_t)((ks >> 2) * 64 + (ks & 3) * 2), ks != 0);
                if (ks + 1 == HAND_AT) asm volatile("bar.arrive %0, 256;" ::"r"(next_turn) : "memory");
            }
            asm volatile("wgmma.commit_group.sync.aligned;" ::: "memory");
            asm volatile("wgmma.wait_group.sync.aligned 0;" ::: "memory");
#pragma unroll
            for (int j = 0; j < 32; j++) asm volatile("" : "+f"(acc[j])::"memory");
            TRE(2 + wg * 2, i);
            if (lane < 2) mbar_arrive_cta(bars + BAR_EMPTY + 8 * r.s, lane);

            if (held) write_out(wg_bars, st_addr, o, packed);
            o = r;
#pragma unroll
            for (int j = 0; j < 16; j++) packed[j] = pack_bias(acc[2 * j], acc[2 * j + 1], j & 1 ? bias_hi : bias_lo);
            held = !mbar_test(wg_bars + BAR_OFREE + o.s * 32, o.parity ^ 1);
            if (!held) write_out(wg_bars, st_addr, o, packed);
            TRE(8 + wg, i);
        }
        if (held) write_out(wg_bars, st_addr, o, packed);
        if (wg == 0) asm volatile("bar.sync 4, 256;" ::: "memory");
        TRE(1 + wg, 62);
    } else {
        asm volatile("setmaxnreg.dec.sync.aligned.u32 32;");
        if (warp == NUM_WG * 4) {
#pragma unroll
            for (int j = 0; j < NUM_WG; j++) mbar_init_1(bars + BAR_W + 8 * j, 1);
            publish_barriers();
            cluster_arrive();
#pragma unroll
            for (int j = 0; j < NUM_WG; j++) {
                if (j == W_FIRST) {
                    cluster_wait();
                    TR(0, 0);
                    mbar_expect_tx_1(bars + BAR_FULL, STAGE_BYTES);
                    tma_load_x_1(smem + rank * HALF_BYTES, &maps.x, bars + BAR_FULL, cluster * 8 + rank * 4);
                }
                mbar_expect_tx_1(bars + BAR_W + 8 * j, STAGE_BYTES);
                tma_load_w_1(smem + w_stage(j), &maps.w, bars + BAR_W + 8 * j, slice_channel(rank, j));
                if (j == 0) TR(2, 61);
            }
            Ring r = {1, 0};
#pragma unroll 1
            for (uint32_t i = 1, id = cluster + num_clusters; id < num_tiles; i++, id += num_clusters, r.advance()) {
                mbar_wait(bars + BAR_EMPTY + 8 * r.s, r.parity ^ (r.s == 0));
                sts32(bars + ISSUED_AT, id);
                sts32(bars + STAMP_AT + 4 * r.s, timer_ns());
                TR(0, i);
                TRV(15, i, id);
                const uint32_t full = bars + BAR_FULL + 8 * r.s;
                const uint32_t dst = smem + r.s * STAGE_BYTES + rank * HALF_BYTES;
                mbar_expect_tx_1(full, STAGE_BYTES);
                if (id + tune.EF_TAIL < num_tiles) tma_load_x_1(dst, &maps.x, full, id * 8 + rank * 4);
                else tma_load_x_evict_first_1(dst, &maps.x, full, id * 8 + rank * 4);
            }
#pragma unroll 1
            for (int k = 0; k < STAGES; k++, r.advance()) mbar_wait(bars + BAR_EMPTY + 8 * r.s, r.parity ^ (r.s == 0));
        } else if (warp == NUM_WG * 4 + 1) {
#pragma unroll
            for (int s = 0; s < STAGES; s++) {
                mbar_init_1(bars + BAR_FULL + 8 * s, 1);
                mbar_init_1(bars + BAR_EMPTY + 8 * s, NUM_WG * 4 * 2);
            }
            publish_barriers();
            cluster_arrive();
            TR(0, 61);
            cluster_wait();
            prefetch_map_1(&maps.out);
            uint32_t delay = 0;
            Ring r = {0, 0};
#pragma unroll 1
            for (uint32_t i = 0, id = cluster; id < num_tiles; i++, id += num_clusters, r.advance()) {
                mbar_wait(bars + BAR_FULL + 8 * r.s, r.parity);
                TR(7, i);
                const int late = (int)(timer_ns() - lds32(bars + STAMP_AT + 4 * r.s) - tune.CC_L0);
                if (i >= tune.CC_AT && late > 0) {
                    delay = min(delay + min((uint32_t)late * tune.CC_G >> 4, tune.CC_STEP), tune.CC_CAP);
                    sts32(bars + DELAY_AT, delay);
                }
            }
        } else if (warp == NUM_WG * 4 + 2) {
            sts32(bars + DELAY_AT, 0);
#pragma unroll
            for (int b = 0; b < STAGES; b++) {
#pragma unroll
                for (int w = 0; w < NUM_WG; w++) {
                    mbar_init_1(bars + BAR_OFREE + b * 32 + w * 8, 1);
                    mbar_init_1(bars + BAR_OFULL + b * 32 + w * 8, 4);
                }
            }
            publish_barriers();
            cluster_arrive();
            cluster_wait();
            const uint32_t mark = num_tiles / num_clusters - tune.SW_J;
            const int behind = cluster < num_tiles % num_clusters ? cluster : cluster - num_clusters;
            const int stage = (int)tune.SW_D1 - behind * (int)tune.SW_K;
            uint32_t due = t_entry + tune.ST_T0 + cluster * tune.ST_STAG - tune.ST_P1;
            uint32_t open = 0, t_end = 0, delay = 0;
            Ring o = {0, 0};
#pragma unroll 1
            for (uint32_t j = 0, id = cluster; id < num_tiles; j++, id += num_clusters, o.advance()) {
                const uint32_t obar = bars + o.s * 32;
                if (!mbar_test(obar + BAR_OFULL, o.parity)) {
                    hand_back<0>(open);
                    mbar_wait(obar + BAR_OFULL, o.parity);
                }
                if (j >= tune.ST_AT) {
                    const uint32_t period = j <= tune.ST_E1 ? tune.ST_P1 : j <= tune.ST_E2 ? tune.ST_P2 : tune.ST_P3;
                    const int over = (int)(due + period - t_end);
                    if (j <= mark || over <= 0) {
                        due += period;
                    } else {
                        const int t = over < (int)period ? over * (int)tune.ST_PT / (int)period : over - (int)period + (int)tune.ST_PT;
                        due = t_end + min(t, stage);
                    }
                    uint32_t now;
#pragma unroll 1
                    for (uint32_t spins = 0; spins < SPIN_LIMIT; spins++) {
                        const uint32_t more = uniform(lds32(bars + DELAY_AT)) - delay;
                        delay += more;
                        due += more;
                        t_end += more;
                        now = timer_ns();
                        if (reached(now, due)) break;
                        hand_back<0>(open);
                        __nanosleep(20);
                    }
                    if (reached(now - tune.ST_SLACK, due)) due = now - tune.ST_SLACK;
                    if (j == mark) t_end = due - cluster * tune.ST_STAG + tune.SW_D;
                }
                const uint32_t src = smem + SMEM_OUT + o.s * HALF_BYTES;
                if (mbar_test(obar + BAR_OFULL + 8, o.parity) && mbar_test(obar + BAR_OFULL + 16, o.parity)) {
                    TR(11, j);
#pragma unroll
                    for (int w = 0; w < NUM_WG; w++) tma_store_1(&maps.out, src + w * SLICE_BYTES, slice_channel(rank, w), id * TILE_PIX);
                    hand_back<3>(open);
                    stores_read_wait<2>();
                    TR(12, j);
                    mbar_arrive_1(obar + BAR_OFREE);
                    stores_read_wait<1>();
                    TR(13, j);
                    mbar_arrive_1(obar + BAR_OFREE + 8);
                    open = obar + BAR_OFREE + 16;
                } else {
#pragma unroll 1
                    for (uint32_t w = 0; w < NUM_WG; w++) {
                        if (!mbar_test(obar + BAR_OFULL + w * 8, o.parity)) {
                            hand_back<0>(open);
                            mbar_wait(obar + BAR_OFULL + w * 8, o.parity);
                        }
                        TR(11 + w, j);
                        tma_store_1(&maps.out, src + w * SLICE_BYTES, slice_channel(rank, w), id * TILE_PIX);
                        hand_back<1>(open);
                        open = obar + BAR_OFREE + w * 8;
                    }
                }
            }
            stores_read_wait<0>();
            TR(4, 62);
        } else {
            sts32(bars + ISSUED_AT, 0);
            cluster_arrive();
            uint32_t due = t_entry + tune.PM_T0 + (blockIdx.x & 3) * tune.PM_STAG;
            const uint32_t step = num_clusters / 2;
#pragma unroll 1
            for (uint32_t piece = 1;; piece++) {
                const uint32_t t = cluster + piece / 2 * num_clusters;
                if (t >= num_tiles) break;
                uint32_t now;
#pragma unroll 1
                for (uint32_t spins = 0; spins < 16384; spins++) {
                    const uint32_t issued = uniform(lds32(bars + ISSUED_AT));
                    now = timer_ns();
                    const int lead = max((int)tune.LEAD_B, (int)tune.LEAD_A - (max((int)issued - (int)tune.LEAD_F, 0) * (int)tune.LEAD_S >> 4));
                    if (reached(now, due)) {
                        if (cluster + piece * step <= issued + lead) break;
                        due = now;
                    }
                    __nanosleep(20);
                }
                if (reached(now - tune.PM_SLACK, due)) due = now - tune.PM_SLACK;
                due += piece < tune.PM_E1 ? tune.PM_DT1 : piece < tune.PM_E2 ? tune.PM_DT2 : tune.PM_DT3;
                const uint8_t* p = x_raw + (size_t)t * STAGE_BYTES + rank * HALF_BYTES + (piece % 2) * PIECE_BYTES + lane * 128;
#pragma unroll
                for (int k = 0; k < PIECE_BYTES / 4096; k++) prefetch_l2(p + k * 4096);
                if (piece % 2 == 0) TR(14, piece / 2);
            }
            cluster_wait();
        }
    }
}

typedef CUresult (*EncodeTiledFn)(CUtensorMap*, CUtensorMapDataType, cuuint32_t, void*, const cuuint64_t*,
                                  const cuuint64_t*, const cuuint32_t*, const cuuint32_t*, CUtensorMapInterleave,
                                  CUtensorMapSwizzle, CUtensorMapL2promotion, CUtensorMapFloatOOBfill);

}

extern "C" void kernel_launch(void* const* d_in, const int* in_sizes, int n_in, void* d_out, int out_size) {
    (void)n_in;
    (void)out_size;
    void* x = d_in[0];
    void* w = d_in[1];
    const uint16_t* b = (const uint16_t*)d_in[2];
    const int M = in_sizes[0] / C;
    const int num_tiles = M / TILE_PIX;

    static EncodeTiledFn encode = nullptr;
    static int sms = 0;
    if (!encode) {
        void* fn = nullptr;
        cudaDriverEntryPointQueryResult q;
        cudaGetDriverEntryPoint("cuTensorMapEncodeTiled", &fn, cudaEnableDefault, &q);
        encode = (EncodeTiledFn)fn;
        cudaDeviceGetAttribute(&sms, cudaDevAttrMultiProcessorCount, 0);
        cudaFuncSetAttribute(conv1x1_kernel, cudaFuncAttributeMaxDynamicSharedMemorySize, SMEM_TOTAL);
    }

    Maps maps;
    const cuuint32_t ones[4] = {1, 1, 1, 1};
    auto make = [&](CUtensorMap* map, int rank, void* base, const cuuint64_t* dims, const cuuint64_t* strides,
                    const cuuint32_t* box, CUtensorMapL2promotion promo) {
        encode(map, CU_TENSOR_MAP_DATA_TYPE_BFLOAT16, rank, base, dims, strides, box, ones, CU_TENSOR_MAP_INTERLEAVE_NONE,
               CU_TENSOR_MAP_SWIZZLE_128B, promo, CU_TENSOR_MAP_FLOAT_OOB_FILL_NONE);
    };
    {
        const cuuint64_t dims[4]    = {64, 8, 6, (cuuint64_t)(M / 8)};
        const cuuint64_t strides[3] = {C * 2, 128, 8 * C * 2};
        const cuuint32_t box[4]     = {64, 8, 6, TILE_PIX / 16};
        make(&maps.x, 4, x, dims, strides, box, CU_TENSOR_MAP_L2_PROMOTION_L2_128B);
    }
    {
        const cuuint64_t dims[3]    = {C, C / 2, 2};
        const cuuint64_t strides[2] = {C * 2, C * C};
        const cuuint32_t box[3]     = {64, C / 2, 2};
        make(&maps.w, 3, w, dims, strides, box, CU_TENSOR_MAP_L2_PROMOTION_L2_128B);
    }
    {
        const cuuint64_t dims[2]    = {C, (cuuint64_t)M};
        const cuuint64_t strides[1] = {C * 2};
        const cuuint32_t box[2]     = {64, TILE_PIX};
        make(&maps.out, 2, d_out, dims, strides, box, CU_TENSOR_MAP_L2_PROMOTION_NONE);
    }

    const Tune tune;
    int clusters = sms / 2;
    if (clusters > num_tiles) clusters = num_tiles;
    conv1x1_kernel<<<clusters * 2, THREADS, SMEM_TOTAL>>>((const uint8_t*)x, (const uint8_t*)w, b, (uint32_t)num_tiles,
                                                          (uint32_t)clusters, maps, tune);
}
```

```cpp
#include <cuda_runtime.h>
#include <cuda_bf16.h>
#include <cuda.h>
#include <stdint.h>

#define TUNABLES(F) \
    F(PM_T0, 350)        \
    F(PM_STAG, 120)      \
    F(PM_DT1, 400)       \
    F(PM_E1, 7) \
    F(PM_DT2, 475) \
    F(PM_E2, 23) \
    F(PM_DT3, 820) \
    F(PM_SLACK, 600)     \
    F(LEAD_A, 280)       \
    F(LEAD_F, 500)       \
    F(LEAD_S, 3)         \
    F(LEAD_B, 151)       \
    F(EF_TAIL, 500)      \
    F(ST_AT, 2)          \
    F(ST_T0, 6800)       \
    F(ST_STAG, 32)       \
    F(ST_P1, 2030)       \
    F(ST_E1, 9) \
    F(ST_P2, 1860) \
    F(ST_E2, 18) \
    F(ST_P3, 1970) \
    F(ST_SLACK, 400)     \
    F(SW_J, 12)          \
    F(SW_D, 7800)        \
    F(ST_PT, 1670)       \
    F(SW_D1, 3050)       \
    F(SW_K, 10)          \
    F(CC_AT, 22)         \
    F(CC_L0, 1300)       \
    F(CC_G, 12)          \
    F(CC_STEP, 600)      \
    F(CC_CAP, 1100)

struct Tune {
#define F(n, v) uint32_t n = v;
    TUNABLES(F)
#undef F
};

#define TRV(slot, idx, v)
#define TR(slot, idx)
#define TRE(slot, idx)
#define TRACE_BYTES 0

namespace {

constexpr int C            = 384;
constexpr int TILE_PIX     = 64;
constexpr int STAGES       = 3;
constexpr int STAGE_BYTES  = TILE_PIX * C * 2;
constexpr int HALF_BYTES   = STAGE_BYTES / 2;
constexpr int PIECE_BYTES  = HALF_BYTES / 2;
constexpr int SLICE_BYTES  = TILE_PIX * 128;
constexpr int NUM_WG       = 3;
constexpr int THREADS      = (NUM_WG + 1) * 128;
constexpr int SMEM_OUT     = STAGES * STAGE_BYTES;
constexpr int SMEM_BAR     = SMEM_OUT + STAGES * HALF_BYTES;
constexpr int SMEM_TOTAL   = SMEM_BAR + 512 + TRACE_BYTES + 1024;
constexpr int HAND_AT      = 18;
constexpr int W_LINES      = C * C * 2 / 128;
constexpr int PRE_W        = 64;
#define PD0 0
#define PDT 330
constexpr int PRE_D0       = PD0;
constexpr int PRE_DT       = PDT;
constexpr uint32_t SPIN_LIMIT = 1u << 22;
constexpr int BAR_W     = 0;
constexpr int BAR_FULL  = 32;
constexpr int BAR_EMPTY = 64;
constexpr int BAR_OFREE = 96;
constexpr int BAR_OFULL = BAR_OFREE + 32 * STAGES;
constexpr int ISSUED_AT = BAR_OFULL + 32 * STAGES;
constexpr int DELAY_AT  = ISSUED_AT + 4;
constexpr int STAMP_AT  = DELAY_AT + 4;
constexpr int SINK_AT   = 384;

struct Maps {
    CUtensorMap w, x, out;
};

#define ELECT "{\n.reg .pred e;\nelect.sync _|e, 0xffffffff;\n@e "

__device__ __forceinline__ uint32_t smem_u32(const void* p) {
    return (uint32_t)__cvta_generic_to_shared(p);
}
__device__ __forceinline__ void mbar_init_1(uint32_t bar, uint32_t count) {
    asm volatile(ELECT "mbarrier.init.shared::cta.b64 [%0], %1;\n}" ::"r"(bar), "r"(count) : "memory");
}
__device__ __forceinline__ void mbar_expect_tx_1(uint32_t bar, uint32_t bytes) {
    asm volatile(ELECT "mbarrier.arrive.expect_tx.shared::cta.b64 _, [%0], %1;\n}" ::"r"(bar), "r"(bytes) : "memory");
}
__device__ __forceinline__ void mbar_arrive_1(uint32_t bar) {
    asm volatile(ELECT "mbarrier.arrive.shared::cta.b64 _, [%0];\n}" ::"r"(bar) : "memory");
}
__device__ __forceinline__ void mbar_wait(uint32_t bar, uint32_t parity) {
    uint32_t done;
    uint32_t spins = 0;
    do {
        asm volatile(
            "{\n.reg .pred p;\n"
            "mbarrier.try_wait.parity.shared::cta.b64 p, [%1], %2;\n"
            "selp.u32 %0, 1, 0, p;\n}"
            : "=r"(done) : "r"(bar), "r"(parity) : "memory");
    } while (!done && ++spins < SPIN_LIMIT);
    __syncwarp();
}
__device__ __forceinline__ bool mbar_test(uint32_t bar, uint32_t parity) {
    uint32_t done;
    asm volatile(
        "{\n.reg .pred p;\n"
        "mbarrier.test_wait.parity.shared::cta.b64 p, [%1], %2;\n"
        "selp.u32 %0, 1, 0, p;\n}"
        : "=r"(done) : "r"(bar), "r"(parity) : "memory");
    return __all_sync(0xffffffffu, done);
}
__device__ __forceinline__ void mbar_arrive_cta(uint32_t bar, uint32_t cta) {
    asm volatile(
        "{\n.reg .b32 ra;\n"
        "mapa.shared::cluster.u32 ra, %0, %1;\n"
        "mbarrier.arrive.shared::cluster.b64 _, [ra];\n}"
        ::"r"(bar), "r"(cta) : "memory");
}
__device__ __forceinline__ uint32_t lds32(uint32_t addr) {
    uint32_t v;
    asm volatile("ld.volatile.shared.b32 %0, [%1];" : "=r"(v) : "r"(addr) : "memory");
    return v;
}
__device__ __forceinline__ void sts32(uint32_t addr, uint32_t v) {
    asm volatile("st.volatile.shared.b32 [%0], %1;" ::"r"(addr), "r"(v) : "memory");
}
__device__ __forceinline__ uint32_t uniform(uint32_t v) {
    return __shfl_sync(0xffffffffu, v, 0);
}
__device__ __forceinline__ void tma_load_w_1(uint32_t dst, const CUtensorMap* map, uint32_t bar, int n) {
    asm volatile(
        ELECT "cp.async.bulk.tensor.3d.shared::cluster.global.mbarrier::complete_tx::bytes [%0], [%1, {%3, %4, %4}], [%2];\n}"
        ::"r"(dst), "l"(map), "r"(bar), "r"(n), "r"(0) : "memory");
}
__device__ __forceinline__ void tma_load_x_1(uint32_t dst, const CUtensorMap* map, uint32_t bar, int group) {
    asm volatile(
        ELECT "cp.async.bulk.tensor.4d.shared::cluster.global.mbarrier::complete_tx::bytes.multicast::cluster"
        " [%0], [%1, {%3, %3, %3, %4}], [%2], %5;\n}"
        ::"r"(dst), "l"(map), "r"(bar), "r"(0), "r"(group), "h"((uint16_t)3) : "memory");
}
__device__ __forceinline__ void tma_load_x_evict_first_1(uint32_t dst, const CUtensorMap* map, uint32_t bar, int group) {
    asm volatile(
        "{\n.reg .b64 pol;\n"
        "createpolicy.fractional.L2::evict_first.b64 pol, 1.0;\n"
        ELECT "cp.async.bulk.tensor.4d.shared::cluster.global.mbarrier::complete_tx::bytes.multicast::cluster.L2::cache_hint"
        " [%0], [%1, {%3, %3, %3, %4}], [%2], %5, pol;\n}\n}"
        ::"r"(dst), "l"(map), "r"(bar), "r"(0), "r"(group), "h"((uint16_t)3) : "memory");
}
__device__ __forceinline__ void tma_store_1(const CUtensorMap* map, uint32_t src, int ch, int pix) {
    asm volatile(
        ELECT "cp.async.bulk.tensor.2d.global.shared::cta.bulk_group [%0, {%2, %3}], [%1];\n}\n"
        "cp.async.bulk.commit_group;"
        ::"l"(map), "r"(src), "r"(ch), "r"(pix) : "memory");
}
template <int N>
__device__ __forceinline__ void stores_read_wait() {
    asm volatile("cp.async.bulk.wait_group.read %0;" ::"n"(N) : "memory");
}
__device__ __forceinline__ void prefetch_map_1(const CUtensorMap* map) {
    asm volatile(ELECT "prefetch.tensormap [%0];\n}" ::"l"(map) : "memory");
}
__device__ __forceinline__ void prefetch_l2(const void* p) {
    asm volatile("prefetch.global.L2 [%0];" ::"l"(p) : "memory");
}
__device__ __forceinline__ uint32_t timer_ns() {
    uint32_t t;
    asm volatile("mov.u32 %0, %%globaltimer_lo;" : "=r"(t)::"memory");
    return t;
}
__device__ __forceinline__ bool reached(uint32_t now, uint32_t t) {
    return (int32_t)(now - t) >= 0;
}
__device__ __forceinline__ void cluster_arrive() {
    asm volatile("barrier.cluster.arrive.relaxed.aligned;" ::: "memory");
}
__device__ __forceinline__ void cluster_wait() {
    asm volatile("barrier.cluster.wait.aligned;" ::: "memory");
}
__device__ __forceinline__ void publish_barriers() {
    asm volatile("fence.mbarrier_init.release.cluster;" ::: "memory");
    asm volatile("fence.proxy.async.shared::cta;" ::: "memory");
}

__device__ __forceinline__ void wgmma_rs_n64(float (&d)[32], const uint32_t* a, uint64_t desc, int scale_d) {
    asm volatile(
        "{\n.reg .pred p;\n"
        "setp.ne.b32 p, %37, 0;\n"
        "wgmma.mma_async.sync.aligned.m64n64k16.f32.bf16.bf16 "
        "{%0, %1, %2, %3, %4, %5, %6, %7, %8, %9, %10, %11, %12, %13, %14, %15, "
        "%16, %17, %18, %19, %20, %21, %22, %23, %24, %25, %26, %27, %28, %29, %30, %31}, "
        "{%32, %33, %34, %35}, %36, p, 1, 1, 0;\n}"
        : "+f"(d[0]), "+f"(d[1]), "+f"(d[2]), "+f"(d[3]), "+f"(d[4]), "+f"(d[5]), "+f"(d[6]), "+f"(d[7]),
          "+f"(d[8]), "+f"(d[9]), "+f"(d[10]), "+f"(d[11]), "+f"(d[12]), "+f"(d[13]), "+f"(d[14]), "+f"(d[15]),
          "+f"(d[16]), "+f"(d[17]), "+f"(d[18]), "+f"(d[19]), "+f"(d[20]), "+f"(d[21]), "+f"(d[22]), "+f"(d[23]),
          "+f"(d[24]), "+f"(d[25]), "+f"(d[26]), "+f"(d[27]), "+f"(d[28]), "+f"(d[29]), "+f"(d[30]), "+f"(d[31])
        : "r"(a[0]), "r"(a[1]), "r"(a[2]), "r"(a[3]), "l"(desc), "r"(scale_d));
}

__device__ __forceinline__ uint32_t pack_bias(float lo, float hi, uint32_t bias2) {
    uint32_t r;
    asm("{\n.reg .b32 t;\n"
        "cvt.rn.bf16x2.f32 t, %2, %1;\n"
        "add.rn.bf16x2 %0, t, %3;\n}"
        : "=r"(r) : "f"(lo), "f"(hi), "r"(bias2));
    return r;
}

__device__ __forceinline__ int slice_channel(uint32_t rank, int wg) {
    return (wg * 2 + rank) * 64;
}
__device__ __forceinline__ uint32_t w_stage(int wg) {
    return (wg + 1) * STAGE_BYTES + (wg == 2 ? HALF_BYTES : 0);
}

struct Ring {
    uint32_t s, parity;
    __device__ __forceinline__ void advance() {
        if (++s == STAGES) {
            s = 0;
            parity ^= 1;
        }
    }
};

__device__ __forceinline__ void write_out(uint32_t wg_bars, uint32_t st_addr, const Ring& r, const uint32_t (&v)[16]) {
    mbar_wait(wg_bars + BAR_OFREE + r.s * 32, r.parity ^ 1);
    const uint32_t dst = st_addr + r.s * HALF_BYTES;
#pragma unroll
    for (int j = 0; j < 4; j++) {
        asm volatile("stmatrix.sync.aligned.m8n8.x4.trans.shared.b16 [%0], {%1, %2, %3, %4};"
                     ::"r"(dst + j * 2048), "r"(v[4 * j]), "r"(v[4 * j + 1]), "r"(v[4 * j + 2]), "r"(v[4 * j + 3]) : "memory");
    }
    asm volatile("fence.proxy.async.shared::cta;" ::: "memory");
    __syncwarp();
    mbar_arrive_1(wg_bars + BAR_OFULL + r.s * 32);
}

template <int N>
__device__ __forceinline__ void hand_back(uint32_t& open) {
    if (open != 0) {
        stores_read_wait<N>();
        mbar_arrive_1(open);
        open = 0;
    }
}

__global__ void __cluster_dims__(2, 1, 1) __launch_bounds__(THREADS, 1)
conv1x1_kernel(const uint8_t* __restrict__ x_raw,
               const uint8_t* __restrict__ w_raw,
               const uint16_t* __restrict__ bias,
               uint32_t num_tiles,
               uint32_t num_clusters,
               const __grid_constant__ Maps maps,
               const __grid_constant__ Tune tune) {
    const uint32_t t_entry = timer_ns();
    extern __shared__ uint8_t smem_raw[];
    const uint32_t smem = (smem_u32(smem_raw) + 1023u) & ~1023u;
    const uint32_t bars = smem + SMEM_BAR;

    if (threadIdx.x < PRE_W) {
        prefetch_l2(w_raw + (blockIdx.x % (W_LINES / PRE_W) * PRE_W + threadIdx.x) * 128);
    } else if (threadIdx.x >= 96 && threadIdx.x < 128) {
        prefetch_map_1(&maps.w);
        prefetch_map_1(&maps.x);
    }
    if (threadIdx.x < NUM_WG * 128) cluster_arrive();
    if (threadIdx.x >= 128 && threadIdx.x < 128 + PIECE_BYTES / 128) {
        const uint8_t* p = x_raw + (size_t)blockIdx.x * HALF_BYTES + (threadIdx.x - 128) * 128;
        const uint32_t wait = PRE_D0 + ((threadIdx.x - 128) >> 5) * PRE_DT;
        const uint32_t c0 = (uint32_t)clock();
        while ((uint32_t)clock() - c0 < wait) {}
        asm volatile("cp.async.ca.shared.global.L2::128B [%0], [%1], 4;" ::"r"(bars + SINK_AT + (threadIdx.x & 31) * 4), "l"(p) : "memory");
    }
    if (threadIdx.x == 0) TRV(0, 63, t_entry);

    const int warp = uniform(threadIdx.x >> 5);
    const int lane = threadIdx.x & 31;
    const uint32_t rank    = blockIdx.x & 1;
    const uint32_t cluster = blockIdx.x >> 1;

    if (warp < NUM_WG * 4) {
        asm volatile("setmaxnreg.inc.sync.aligned.u32 160;");
        const int wg = warp >> 2;
        const int wq = warp & 3;
        const uint32_t bias_lo = bias[slice_channel(rank, wg) + wq * 16 + (lane >> 2)] * 0x10001u;
        const uint32_t bias_hi = bias[slice_channel(rank, wg) + wq * 16 + (lane >> 2) + 8] * 0x10001u;

        cluster_wait();
        TRE(1 + wg, 63);
        mbar_wait(bars + BAR_W + 8 * wg, 0);
        TRE(4 + wg, 63);
        uint32_t wreg[96];
        {
            const int r = lane & 7, m = lane >> 3;
            const uint32_t base = smem + w_stage(wg) + ((m >> 1) * 8 + r) * 128 + (((2 * wq + (m & 1)) ^ r) << 4);
#pragma unroll
            for (int ks = 0; ks < 24; ks++) {
                asm volatile("ldmatrix.sync.aligned.m8n8.x4.trans.shared.b16 {%0, %1, %2, %3}, [%4];"
                             : "=r"(wreg[ks * 4 + 0]), "=r"(wreg[ks * 4 + 1]), "=r"(wreg[ks * 4 + 2]), "=r"(wreg[ks * 4 + 3])
                             : "r"(base + ks * 2048) : "memory");
            }
        }
        uint32_t dep = 0;
#pragma unroll
        for (int ks = 0; ks < 24; ks++) dep ^= wreg[ks * 4];
        dep = uniform(dep & (num_tiles >> 31));
        if (lane < 6 && wg < 2) mbar_arrive_cta(bars + BAR_EMPTY + 8 * (wg + 1) + dep, lane & 1);
        asm volatile("cp.async.wait_all;" ::: "memory");
        TRE(1 + wg, 60);

        const uint32_t wg_bars = bars + wg * 8;
        const uint32_t st_addr = smem + SMEM_OUT + wg * SLICE_BYTES + ((lane >> 4) * 8 + (lane & 7)) * 128 +
                                 (((2 * wq + ((lane >> 3) & 1)) ^ (lane & 7)) << 4);
        const uint64_t desc_base =
            (uint64_t)((smem & 0x3FFFF) >> 4) | ((uint64_t)1 << 16) | ((uint64_t)(6144 >> 4) << 32) | ((uint64_t)1 << 62);
        const int next_turn = 4 + (wg + 1) % NUM_WG;

        float acc[32];
        uint32_t packed[16];
        Ring r = {0, dep}, o = r;
        bool held = false;
        for (uint32_t i = 0, id = cluster; id < num_tiles; i++, id += num_clusters, r.advance()) {
            mbar_wait(bars + BAR_FULL + 8 * r.s, r.parity);
            if ((i | wg) != 0) asm volatile("bar.sync %0, 256;" ::"r"(4 + wg) : "memory");
            TRE(1 + wg * 2, i);
            const uint64_t desc = desc_base + (uint64_t)(r.s * (STAGE_BYTES >> 4));
            asm volatile("wgmma.fence.sync.aligned;" ::: "memory");
#pragma unroll
            for (int ks = 0; ks < 24; ks++) {
                wgmma_rs_n64(acc, &wreg[ks * 4], desc + (uint64_t)((ks >> 2) * 64 + (ks & 3) * 2), ks != 0);
                if (ks + 1 == HAND_AT) asm volatile("bar.arrive %0, 256;" ::"r"(next_turn) : "memory");
            }
            asm volatile("wgmma.commit_group.sync.aligned;" ::: "memory");
            asm volatile("wgmma.wait_group.sync.aligned 0;" ::: "memory");
#pragma unroll
            for (int j = 0; j < 32; j++) asm volatile("" : "+f"(acc[j])::"memory");
            TRE(2 + wg * 2, i);
            if (lane < 2) mbar_arrive_cta(bars + BAR_EMPTY + 8 * r.s, lane);

            if (held) write_out(wg_bars, st_addr, o, packed);
            o = r;
#pragma unroll
            for (int j = 0; j < 16; j++) packed[j] = pack_bias(acc[2 * j], acc[2 * j + 1], j & 1 ? bias_hi : bias_lo);
            held = !mbar_test(wg_bars + BAR_OFREE + o.s * 32, o.parity ^ 1);
            if (!held) write_out(wg_bars, st_addr, o, packed);
            TRE(8 + wg, i);
        }
        if (held) write_out(wg_bars, st_addr, o, packed);
        if (wg == 0) asm volatile("bar.sync 4, 256;" ::: "memory");
        TRE(1 + wg, 62);
    } else {
        asm volatile("setmaxnreg.dec.sync.aligned.u32 32;");
        if (warp == NUM_WG * 4) {
#pragma unroll
            for (int j = 0; j < NUM_WG; j++) mbar_init_1(bars + BAR_W + 8 * j, 1);
            publish_barriers();
            cluster_arrive();
#pragma unroll
            for (int j = 0; j < NUM_WG; j++) {
                mbar_expect_tx_1(bars + BAR_W + 8 * j, STAGE_BYTES);
                tma_load_w_1(smem + w_stage(j), &maps.w, bars + BAR_W + 8 * j, slice_channel(rank, j));
                if (j == 0) TR(2, 61);
            }
            cluster_wait();
            TR(0, 0);
            mbar_expect_tx_1(bars + BAR_FULL, STAGE_BYTES);
            tma_load_x_1(smem + rank * HALF_BYTES, &maps.x, bars + BAR_FULL, cluster * 8 + rank * 4);
            Ring r = {1, 0};
#pragma unroll 1
            for (uint32_t i = 1, id = cluster + num_clusters; id < num_tiles; i++, id += num_clusters, r.advance()) {
                mbar_wait(bars + BAR_EMPTY + 8 * r.s, r.parity ^ (r.s == 0));
                sts32(bars + ISSUED_AT, id);
                sts32(bars + STAMP_AT + 4 * r.s, timer_ns());
                TR(0, i);
                TRV(15, i, id);
                const uint32_t full = bars + BAR_FULL + 8 * r.s;
                const uint32_t dst = smem + r.s * STAGE_BYTES + rank * HALF_BYTES;
                mbar_expect_tx_1(full, STAGE_BYTES);
                if (id + tune.EF_TAIL < num_tiles) tma_load_x_1(dst, &maps.x, full, id * 8 + rank * 4);
                else tma_load_x_evict_first_1(dst, &maps.x, full, id * 8 + rank * 4);
            }
#pragma unroll 1
            for (int k = 0; k < STAGES; k++, r.advance()) mbar_wait(bars + BAR_EMPTY + 8 * r.s, r.parity ^ (r.s == 0));
        } else if (warp == NUM_WG * 4 + 1) {
#pragma unroll
            for (int s = 0; s < STAGES; s++) {
                mbar_init_1(bars + BAR_FULL + 8 * s, 1);
                mbar_init_1(bars + BAR_EMPTY + 8 * s, NUM_WG * 4 * 2);
            }
            publish_barriers();
            cluster_arrive();
            TR(0, 61);
            cluster_wait();
            prefetch_map_1(&maps.out);
            uint32_t delay = 0;
            Ring r = {0, 0};
#pragma unroll 1
            for (uint32_t i = 0, id = cluster; id < num_tiles; i++, id += num_clusters, r.advance()) {
                mbar_wait(bars + BAR_FULL + 8 * r.s, r.parity);
                TR(7, i);
                const int late = (int)(timer_ns() - lds32(bars + STAMP_AT + 4 * r.s) - tune.CC_L0);
                if (i >= tune.CC_AT && late > 0) {
                    delay = min(delay + min((uint32_t)late * tune.CC_G >> 4, tune.CC_STEP), tune.CC_CAP);
                    sts32(bars + DELAY_AT, delay);
                }
            }
        } else if (warp == NUM_WG * 4 + 2) {
            sts32(bars + DELAY_AT, 0);
#pragma unroll
            for (int b = 0; b < STAGES; b++) {
#pragma unroll
                for (int w = 0; w < NUM_WG; w++) {
                    mbar_init_1(bars + BAR_OFREE + b * 32 + w * 8, 1);
                    mbar_init_1(bars + BAR_OFULL + b * 32 + w * 8, 4);
                }
            }
            publish_barriers();
            cluster_arrive();
            cluster_wait();
            const uint32_t mark = num_tiles / num_clusters - tune.SW_J;
            const int behind = cluster < num_tiles % num_clusters ? cluster : cluster - num_clusters;
            const int stage = (int)tune.SW_D1 - behind * (int)tune.SW_K;
            uint32_t due = t_entry + tune.ST_T0 + cluster * tune.ST_STAG - tune.ST_P1;
            uint32_t open = 0, t_end = 0, delay = 0;
            Ring o = {0, 0};
#pragma unroll 1
            for (uint32_t j = 0, id = cluster; id < num_tiles; j++, id += num_clusters, o.advance()) {
                const uint32_t obar = bars + o.s * 32;
                if (!mbar_test(obar + BAR_OFULL, o.parity)) {
                    hand_back<0>(open);
                    mbar_wait(obar + BAR_OFULL, o.parity);
                }
                if (j >= tune.ST_AT) {
                    const uint32_t period = j <= tune.ST_E1 ? tune.ST_P1 : j <= tune.ST_E2 ? tune.ST_P2 : tune.ST_P3;
                    const int over = (int)(due + period - t_end);
                    if (j <= mark || over <= 0) {
                        due += period;
                    } else {
                        const int t = over < (int)period ? over * (int)tune.ST_PT / (int)period : over - (int)period + (int)tune.ST_PT;
                        due = t_end + min(t, stage);
                    }
                    uint32_t now;
#pragma unroll 1
                    for (uint32_t spins = 0; spins < SPIN_LIMIT; spins++) {
                        const uint32_t more = uniform(lds32(bars + DELAY_AT)) - delay;
                        delay += more;
                        due += more;
                        t_end += more;
                        now = timer_ns();
                        if (reached(now, due)) break;
                        hand_back<0>(open);
                        __nanosleep(20);
                    }
                    if (reached(now - tune.ST_SLACK, due)) due = now - tune.ST_SLACK;
                    if (j == mark) t_end = due - cluster * tune.ST_STAG + tune.SW_D;
                }
                const uint32_t src = smem + SMEM_OUT + o.s * HALF_BYTES;
                if (mbar_test(obar + BAR_OFULL + 8, o.parity) && mbar_test(obar + BAR_OFULL + 16, o.parity)) {
                    TR(11, j);
#pragma unroll
                    for (int w = 0; w < NUM_WG; w++) tma_store_1(&maps.out, src + w * SLICE_BYTES, slice_channel(rank, w), id * TILE_PIX);
                    hand_back<3>(open);
                    stores_read_wait<2>();
                    TR(12, j);
                    mbar_arrive_1(obar + BAR_OFREE);
                    stores_read_wait<1>();
                    TR(13, j);
                    mbar_arrive_1(obar + BAR_OFREE + 8);
                    open = obar + BAR_OFREE + 16;
                } else {
#pragma unroll 1
                    for (uint32_t w = 0; w < NUM_WG; w++) {
                        if (!mbar_test(obar + BAR_OFULL + w * 8, o.parity)) {
                            hand_back<0>(open);
                            mbar_wait(obar + BAR_OFULL + w * 8, o.parity);
                        }
                        TR(11 + w, j);
                        tma_store_1(&maps.out, src + w * SLICE_BYTES, slice_channel(rank, w), id * TILE_PIX);
                        hand_back<1>(open);
                        open = obar + BAR_OFREE + w * 8;
                    }
                }
            }
            stores_read_wait<0>();
            TR(4, 62);
        } else {
            sts32(bars + ISSUED_AT, 0);
            cluster_arrive();
            uint32_t due = t_entry + tune.PM_T0 + (blockIdx.x & 3) * tune.PM_STAG;
            const uint32_t step = num_clusters / 2;
#pragma unroll 1
            for (uint32_t piece = 1;; piece++) {
                const uint32_t t = cluster + piece / 2 * num_clusters;
                if (t >= num_tiles) break;
                uint32_t now;
#pragma unroll 1
                for (uint32_t spins = 0; spins < 16384; spins++) {
                    const uint32_t issued = uniform(lds32(bars + ISSUED_AT));
                    now = timer_ns();
                    const int lead = max((int)tune.LEAD_B, (int)tune.LEAD_A - (max((int)issued - (int)tune.LEAD_F, 0) * (int)tune.LEAD_S >> 4));
                    if (reached(now, due)) {
                        if (cluster + piece * step <= issued + lead) break;
                        due = now;
                    }
                    __nanosleep(20);
                }
                if (reached(now - tune.PM_SLACK, due)) due = now - tune.PM_SLACK;
                due += piece < tune.PM_E1 ? tune.PM_DT1 : piece < tune.PM_E2 ? tune.PM_DT2 : tune.PM_DT3;
                const uint8_t* p = x_raw + (size_t)t * STAGE_BYTES + rank * HALF_BYTES + (piece % 2) * PIECE_BYTES + lane * 128;
#pragma unroll
                for (int k = 0; k < PIECE_BYTES / 4096; k++) prefetch_l2(p + k * 4096);
                if (piece % 2 == 0) TR(14, piece / 2);
            }
            cluster_wait();
        }
    }
}

typedef CUresult (*EncodeTiledFn)(CUtensorMap*, CUtensorMapDataType, cuuint32_t, void*, const cuuint64_t*,
                                  const cuuint64_t*, const cuuint32_t*, const cuuint32_t*, CUtensorMapInterleave,
                                  CUtensorMapSwizzle, CUtensorMapL2promotion, CUtensorMapFloatOOBfill);

}

extern "C" void kernel_launch(void* const* d_in, const int* in_sizes, int n_in, void* d_out, int out_size) {
    (void)n_in;
    (void)out_size;
    void* x = d_in[0];
    void* w = d_in[1];
    const uint16_t* b = (const uint16_t*)d_in[2];
    const int M = in_sizes[0] / C;
    const int num_tiles = M / TILE_PIX;

    static EncodeTiledFn encode = nullptr;
    static int sms = 0;
    if (!encode) {
        void* fn = nullptr;
        cudaDriverEntryPointQueryResult q;
        cudaGetDriverEntryPoint("cuTensorMapEncodeTiled", &fn, cudaEnableDefault, &q);
        encode = (EncodeTiledFn)fn;
        cudaDeviceGetAttribute(&sms, cudaDevAttrMultiProcessorCount, 0);
        cudaFuncSetAttribute(conv1x1_kernel, cudaFuncAttributeMaxDynamicSharedMemorySize, SMEM_TOTAL);
    }

    Maps maps;
    const cuuint32_t ones[4] = {1, 1, 1, 1};
    auto make = [&](CUtensorMap* map, int rank, void* base, const cuuint64_t* dims, const cuuint64_t* strides,
                    const cuuint32_t* box, CUtensorMapL2promotion promo) {
        encode(map, CU_TENSOR_MAP_DATA_TYPE_BFLOAT16, rank, base, dims, strides, box, ones, CU_TENSOR_MAP_INTERLEAVE_NONE,
               CU_TENSOR_MAP_SWIZZLE_128B, promo, CU_TENSOR_MAP_FLOAT_OOB_FILL_NONE);
    };
    {
        const cuuint64_t dims[4]    = {64, 8, 6, (cuuint64_t)(M / 8)};
        const cuuint64_t strides[3] = {C * 2, 128, 8 * C * 2};
        const cuuint32_t box[4]     = {64, 8, 6, TILE_PIX / 16};
        make(&maps.x, 4, x, dims, strides, box, CU_TENSOR_MAP_L2_PROMOTION_L2_128B);
    }
    {
        const cuuint64_t dims[3]    = {C, C / 2, 2};
        const cuuint64_t strides[2] = {C * 2, C * C};
        const cuuint32_t box[3]     = {64, C / 2, 2};
        make(&maps.w, 3, w, dims, strides, box, CU_TENSOR_MAP_L2_PROMOTION_L2_128B);
    }
    {
        const cuuint64_t dims[2]    = {C, (cuuint64_t)M};
        const cuuint64_t strides[1] = {C * 2};
        const cuuint32_t box[2]     = {64, TILE_PIX};
        make(&maps.out, 2, d_out, dims, strides, box, CU_TENSOR_MAP_L2_PROMOTION_NONE);
    }

    const Tune tune;
    int clusters = sms / 2;
    if (clusters > num_tiles) clusters = num_tiles;
    conv1x1_kernel<<<clusters * 2, THREADS, SMEM_TOTAL>>>((const uint8_t*)x, (const uint8_t*)w, b, (uint32_t)num_tiles,
                                                          (uint32_t)clusters, maps, tune);
}
```

```cpp
#include <cuda_runtime.h>
#include <cuda_bf16.h>
#include <cuda.h>
#include <stdint.h>

#define TUNABLES(F) \
    F(PM_T0, 350)        \
    F(PM_STAG, 120)      \
    F(PM_DT1, 400)       \
    F(PM_E1, 7) \
    F(PM_DT2, 475) \
    F(PM_E2, 23) \
    F(PM_DT3, 860) \
    F(PM_SLACK, 600)     \
    F(LEAD_A, 280)       \
    F(LEAD_F, 500)       \
    F(LEAD_S, 3)         \
    F(LEAD_B, 151)       \
    F(LEAD_T, 264)         \
    F(LEAD_C, 170)       \
    F(PM_DT4, 820)       \
    F(EF_TAIL, 500)      \
    F(ST_AT, 2)          \
    F(ST_T0, 6800)       \
    F(ST_STAG, 32)       \
    F(ST_P1, 2030)       \
    F(ST_E1, 9) \
    F(ST_P2, 1860) \
    F(ST_E2, 18) \
    F(ST_P3, 1970) \
    F(ST_SLACK, 400)     \
    F(SW_J, 12)          \
    F(SW_D, 7800)        \
    F(ST_PT, 1670)       \
    F(SW_D1, 2800)       \
    F(SW_K, 10)          \
    F(CC_AT, 22)         \
    F(CC_L0, 1200)       \
    F(CC_G, 12)          \
    F(CC_STEP, 900)      \
    F(CC_CAP, 1200)

struct Tune {
#define F(n, v) uint32_t n = v;
    TUNABLES(F)
#undef F
};

#define TRV(slot, idx, v)
#define TR(slot, idx)
#define TRE(slot, idx)
#define TRACE_BYTES 0

namespace {

constexpr int C            = 384;
constexpr int TILE_PIX     = 64;
constexpr int STAGES       = 3;
constexpr int STAGE_BYTES  = TILE_PIX * C * 2;
constexpr int HALF_BYTES   = STAGE_BYTES / 2;
constexpr int PIECE_BYTES  = HALF_BYTES / 2;
constexpr int SLICE_BYTES  = TILE_PIX * 128;
constexpr int NUM_WG       = 3;
constexpr int THREADS      = (NUM_WG + 1) * 128;
constexpr int SMEM_OUT     = STAGES * STAGE_BYTES;
constexpr int SMEM_BAR     = SMEM_OUT + STAGES * HALF_BYTES;
constexpr int SMEM_TOTAL   = SMEM_BAR + 512 + TRACE_BYTES + 1024;
constexpr int HAND_AT      = 18;
constexpr int W_LINES      = C * C * 2 / 128;
constexpr int PRE_W        = 64;
#define PD0 0
#define PDT 330
constexpr int PRE_D0       = PD0;
constexpr int PRE_DT       = PDT;
constexpr uint32_t SPIN_LIMIT = 1u << 22;
constexpr int BAR_W     = 0;
constexpr int BAR_FULL  = 32;
constexpr int BAR_EMPTY = 64;
constexpr int BAR_OFREE = 96;
constexpr int BAR_OFULL = BAR_OFREE + 32 * STAGES;
constexpr int ISSUED_AT = BAR_OFULL + 32 * STAGES;
constexpr int DELAY_AT  = ISSUED_AT + 4;
constexpr int STAMP_AT  = DELAY_AT + 4;
constexpr int SINK_AT   = 384;

struct Maps {
    CUtensorMap w, x, out;
};

#define ELECT "{\n.reg .pred e;\nelect.sync _|e, 0xffffffff;\n@e "

__device__ __forceinline__ uint32_t smem_u32(const void* p) {
    return (uint32_t)__cvta_generic_to_shared(p);
}
__device__ __forceinline__ void mbar_init_1(uint32_t bar, uint32_t count) {
    asm volatile(ELECT "mbarrier.init.shared::cta.b64 [%0], %1;\n}" ::"r"(bar), "r"(count) : "memory");
}
__device__ __forceinline__ void mbar_expect_tx_1(uint32_t bar, uint32_t bytes) {
    asm volatile(ELECT "mbarrier.arrive.expect_tx.shared::cta.b64 _, [%0], %1;\n}" ::"r"(bar), "r"(bytes) : "memory");
}
__device__ __forceinline__ void mbar_arrive_1(uint32_t bar) {
    asm volatile(ELECT "mbarrier.arrive.shared::cta.b64 _, [%0];\n}" ::"r"(bar) : "memory");
}
__device__ __forceinline__ void mbar_wait(uint32_t bar, uint32_t parity) {
    uint32_t done;
    uint32_t spins = 0;
    do {
        asm volatile(
            "{\n.reg .pred p;\n"
            "mbarrier.try_wait.parity.shared::cta.b64 p, [%1], %2;\n"
            "selp.u32 %0, 1, 0, p;\n}"
            : "=r"(done) : "r"(bar), "r"(parity) : "memory");
    } while (!done && ++spins < SPIN_LIMIT);
    __syncwarp();
}
__device__ __forceinline__ bool mbar_test(uint32_t bar, uint32_t parity) {
    uint32_t done;
    asm volatile(
        "{\n.reg .pred p;\n"
        "mbarrier.test_wait.parity.shared::cta.b64 p, [%1], %2;\n"
        "selp.u32 %0, 1, 0, p;\n}"
        : "=r"(done) : "r"(bar), "r"(parity) : "memory");
    return __all_sync(0xffffffffu, done);
}
__device__ __forceinline__ void mbar_arrive_cta(uint32_t bar, uint32_t cta) {
    asm volatile(
        "{\n.reg .b32 ra;\n"
        "mapa.shared::cluster.u32 ra, %0, %1;\n"
        "mbarrier.arrive.shared::cluster.b64 _, [ra];\n}"
        ::"r"(bar), "r"(cta) : "memory");
}
__device__ __forceinline__ uint32_t lds32(uint32_t addr) {
    uint32_t v;
    asm volatile("ld.volatile.shared.b32 %0, [%1];" : "=r"(v) : "r"(addr) : "memory");
    return v;
}
__device__ __forceinline__ void sts32(uint32_t addr, uint32_t v) {
    asm volatile("st.volatile.shared.b32 [%0], %1;" ::"r"(addr), "r"(v) : "memory");
}
__device__ __forceinline__ uint32_t uniform(uint32_t v) {
    return __shfl_sync(0xffffffffu, v, 0);
}
__device__ __forceinline__ void tma_load_w_1(uint32_t dst, const CUtensorMap* map, uint32_t bar, int n) {
    asm volatile(
        ELECT "cp.async.bulk.tensor.3d.shared::cluster.global.mbarrier::complete_tx::bytes [%0], [%1, {%3, %4, %4}], [%2];\n}"
        ::"r"(dst), "l"(map), "r"(bar), "r"(n), "r"(0) : "memory");
}
__device__ __forceinline__ void tma_load_x_1(uint32_t dst, const CUtensorMap* map, uint32_t bar, int group) {
    asm volatile(
        ELECT "cp.async.bulk.tensor.4d.shared::cluster.global.mbarrier::complete_tx::bytes.multicast::cluster"
        " [%0], [%1, {%3, %3, %3, %4}], [%2], %5;\n}"
        ::"r"(dst), "l"(map), "r"(bar), "r"(0), "r"(group), "h"((uint16_t)3) : "memory");
}
__device__ __forceinline__ void tma_load_x_evict_first_1(uint32_t dst, const CUtensorMap* map, uint32_t bar, int group) {
    asm volatile(
        "{\n.reg .b64 pol;\n"
        "createpolicy.fractional.L2::evict_first.b64 pol, 1.0;\n"
        ELECT "cp.async.bulk.tensor.4d.shared::cluster.global.mbarrier::complete_tx::bytes.multicast::cluster.L2::cache_hint"
        " [%0], [%1, {%3, %3, %3, %4}], [%2], %5, pol;\n}\n}"
        ::"r"(dst), "l"(map), "r"(bar), "r"(0), "r"(group), "h"((uint16_t)3) : "memory");
}
__device__ __forceinline__ void tma_store_1(const CUtensorMap* map, uint32_t src, int ch, int pix) {
    asm volatile(
        ELECT "cp.async.bulk.tensor.2d.global.shared::cta.bulk_group [%0, {%2, %3}], [%1];\n}\n"
        "cp.async.bulk.commit_group;"
        ::"l"(map), "r"(src), "r"(ch), "r"(pix) : "memory");
}
template <int N>
__device__ __forceinline__ void stores_read_wait() {
    asm volatile("cp.async.bulk.wait_group.read %0;" ::"n"(N) : "memory");
}
__device__ __forceinline__ void prefetch_map_1(const CUtensorMap* map) {
    asm volatile(ELECT "prefetch.tensormap [%0];\n}" ::"l"(map) : "memory");
}
__device__ __forceinline__ void prefetch_l2(const void* p) {
    asm volatile("prefetch.global.L2 [%0];" ::"l"(p) : "memory");
}
__device__ __forceinline__ uint32_t timer_ns() {
    uint32_t t;
    asm volatile("mov.u32 %0, %%globaltimer_lo;" : "=r"(t)::"memory");
    return t;
}
__device__ __forceinline__ bool reached(uint32_t now, uint32_t t) {
    return (int32_t)(now - t) >= 0;
}
__device__ __forceinline__ void cluster_arrive() {
    asm volatile("barrier.cluster.arrive.relaxed.aligned;" ::: "memory");
}
__device__ __forceinline__ void cluster_wait() {
    asm volatile("barrier.cluster.wait.aligned;" ::: "memory");
}
__device__ __forceinline__ void publish_barriers() {
    asm volatile("fence.mbarrier_init.release.cluster;" ::: "memory");
    asm volatile("fence.proxy.async.shared::cta;" ::: "memory");
}

__device__ __forceinline__ void wgmma_rs_n64(float (&d)[32], const uint32_t* a, uint64_t desc, int scale_d) {
    asm volatile(
        "{\n.reg .pred p;\n"
        "setp.ne.b32 p, %37, 0;\n"
        "wgmma.mma_async.sync.aligned.m64n64k16.f32.bf16.bf16 "
        "{%0, %1, %2, %3, %4, %5, %6, %7, %8, %9, %10, %11, %12, %13, %14, %15, "
        "%16, %17, %18, %19, %20, %21, %22, %23, %24, %25, %26, %27, %28, %29, %30, %31}, "
        "{%32, %33, %34, %35}, %36, p, 1, 1, 0;\n}"
        : "+f"(d[0]), "+f"(d[1]), "+f"(d[2]), "+f"(d[3]), "+f"(d[4]), "+f"(d[5]), "+f"(d[6]), "+f"(d[7]),
          "+f"(d[8]), "+f"(d[9]), "+f"(d[10]), "+f"(d[11]), "+f"(d[12]), "+f"(d[13]), "+f"(d[14]), "+f"(d[15]),
          "+f"(d[16]), "+f"(d[17]), "+f"(d[18]), "+f"(d[19]), "+f"(d[20]), "+f"(d[21]), "+f"(d[22]), "+f"(d[23]),
          "+f"(d[24]), "+f"(d[25]), "+f"(d[26]), "+f"(d[27]), "+f"(d[28]), "+f"(d[29]), "+f"(d[30]), "+f"(d[31])
        : "r"(a[0]), "r"(a[1]), "r"(a[2]), "r"(a[3]), "l"(desc), "r"(scale_d));
}

__device__ __forceinline__ uint32_t pack_bias(float lo, float hi, uint32_t bias2) {
    uint32_t r;
    asm("{\n.reg .b32 t;\n"
        "cvt.rn.bf16x2.f32 t, %2, %1;\n"
        "add.rn.bf16x2 %0, t, %3;\n}"
        : "=r"(r) : "f"(lo), "f"(hi), "r"(bias2));
    return r;
}

__device__ __forceinline__ int slice_channel(uint32_t rank, int wg) {
    return (wg * 2 + rank) * 64;
}
__device__ __forceinline__ uint32_t w_stage(int wg) {
    return (wg + 1) * STAGE_BYTES + (wg == 2 ? HALF_BYTES : 0);
}

struct Ring {
    uint32_t s, parity;
    __device__ __forceinline__ void advance() {
        if (++s == STAGES) {
            s = 0;
            parity ^= 1;
        }
    }
};

__device__ __forceinline__ void write_out(uint32_t wg_bars, uint32_t st_addr, const Ring& r, const uint32_t (&v)[16]) {
    mbar_wait(wg_bars + BAR_OFREE + r.s * 32, r.parity ^ 1);
    const uint32_t dst = st_addr + r.s * HALF_BYTES;
#pragma unroll
    for (int j = 0; j < 4; j++) {
        asm volatile("stmatrix.sync.aligned.m8n8.x4.trans.shared.b16 [%0], {%1, %2, %3, %4};"
                     ::"r"(dst + j * 2048), "r"(v[4 * j]), "r"(v[4 * j + 1]), "r"(v[4 * j + 2]), "r"(v[4 * j + 3]) : "memory");
    }
    asm volatile("fence.proxy.async.shared::cta;" ::: "memory");
    __syncwarp();
    mbar_arrive_1(wg_bars + BAR_OFULL + r.s * 32);
}

template <int N>
__device__ __forceinline__ void hand_back(uint32_t& open) {
    if (open != 0) {
        stores_read_wait<N>();
        mbar_arrive_1(open);
        open = 0;
    }
}

__global__ void __cluster_dims__(2, 1, 1) __launch_bounds__(THREADS, 1)
conv1x1_kernel(const uint8_t* __restrict__ x_raw,
               const uint8_t* __restrict__ w_raw,
               const uint16_t* __restrict__ bias,
               uint32_t num_tiles,
               uint32_t num_clusters,
               const __grid_constant__ Maps maps,
               const __grid_constant__ Tune tune) {
    const uint32_t t_entry = timer_ns();
    extern __shared__ uint8_t smem_raw[];
    const uint32_t smem = (smem_u32(smem_raw) + 1023u) & ~1023u;
    const uint32_t bars = smem + SMEM_BAR;

    if (threadIdx.x < PRE_W) {
        prefetch_l2(w_raw + (blockIdx.x % (W_LINES / PRE_W) * PRE_W + threadIdx.x) * 128);
    } else if (threadIdx.x >= 96 && threadIdx.x < 128) {
        prefetch_map_1(&maps.w);
        prefetch_map_1(&maps.x);
    }
    if (threadIdx.x < NUM_WG * 128) cluster_arrive();
    if (threadIdx.x >= 128 && threadIdx.x < 128 + PIECE_BYTES / 128) {
        const uint8_t* p = x_raw + (size_t)blockIdx.x * HALF_BYTES + (threadIdx.x - 128) * 128;
        const uint32_t wait = PRE_D0 + ((threadIdx.x - 128) >> 5) * PRE_DT;
        const uint32_t c0 = (uint32_t)clock();
        while ((uint32_t)clock() - c0 < wait) {}
        asm volatile("cp.async.ca.shared.global.L2::128B [%0], [%1], 4;" ::"r"(bars + SINK_AT + (threadIdx.x & 31) * 4), "l"(p) : "memory");
    }
    if (threadIdx.x == 0) TRV(0, 63, t_entry);

    const int warp = uniform(threadIdx.x >> 5);
    const int lane = threadIdx.x & 31;
    const uint32_t rank    = blockIdx.x & 1;
    const uint32_t cluster = blockIdx.x >> 1;

    if (warp < NUM_WG * 4) {
        asm volatile("setmaxnreg.inc.sync.aligned.u32 160;");
        const int wg = warp >> 2;
        const int wq = warp & 3;
        const uint32_t bias_lo = bias[slice_channel(rank, wg) + wq * 16 + (lane >> 2)] * 0x10001u;
        const uint32_t bias_hi = bias[slice_channel(rank, wg) + wq * 16 + (lane >> 2) + 8] * 0x10001u;

        cluster_wait();
        TRE(1 + wg, 63);
        mbar_wait(bars + BAR_W + 8 * wg, 0);
        TRE(4 + wg, 63);
        uint32_t wreg[96];
        {
            const int r = lane & 7, m = lane >> 3;
            const uint32_t base = smem + w_stage(wg) + ((m >> 1) * 8 + r) * 128 + (((2 * wq + (m & 1)) ^ r) << 4);
#pragma unroll
            for (int ks = 0; ks < 24; ks++) {
                asm volatile("ldmatrix.sync.aligned.m8n8.x4.trans.shared.b16 {%0, %1, %2, %3}, [%4];"
                             : "=r"(wreg[ks * 4 + 0]), "=r"(wreg[ks * 4 + 1]), "=r"(wreg[ks * 4 + 2]), "=r"(wreg[ks * 4 + 3])
                             : "r"(base + ks * 2048) : "memory");
            }
        }
        uint32_t dep = 0;
#pragma unroll
        for (int ks = 0; ks < 24; ks++) dep ^= wreg[ks * 4];
        dep = uniform(dep & (num_tiles >> 31));
        if (lane < 6 && wg < 2) mbar_arrive_cta(bars + BAR_EMPTY + 8 * (wg + 1) + dep, lane & 1);
        asm volatile("cp.async.wait_all;" ::: "memory");
        TRE(1 + wg, 60);

        const uint32_t wg_bars = bars + wg * 8;
        const uint32_t st_addr = smem + SMEM_OUT + wg * SLICE_BYTES + ((lane >> 4) * 8 + (lane & 7)) * 128 +
                                 (((2 * wq + ((lane >> 3) & 1)) ^ (lane & 7)) << 4);
        const uint64_t desc_base =
            (uint64_t)((smem & 0x3FFFF) >> 4) | ((uint64_t)1 << 16) | ((uint64_t)(6144 >> 4) << 32) | ((uint64_t)1 << 62);
        const int next_turn = 4 + (wg + 1) % NUM_WG;

        float acc[32];
        uint32_t packed[16];
        Ring r = {0, dep}, o = r;
        bool held = false;
        for (uint32_t i = 0, id = cluster; id < num_tiles; i++, id += num_clusters, r.advance()) {
            mbar_wait(bars + BAR_FULL + 8 * r.s, r.parity);
            if ((i | wg) != 0) asm volatile("bar.sync %0, 256;" ::"r"(4 + wg) : "memory");
            TRE(1 + wg * 2, i);
            const uint64_t desc = desc_base + (uint64_t)(r.s * (STAGE_BYTES >> 4));
            asm volatile("wgmma.fence.sync.aligned;" ::: "memory");
#pragma unroll
            for (int ks = 0; ks < 24; ks++) {
                wgmma_rs_n64(acc, &wreg[ks * 4], desc + (uint64_t)((ks >> 2) * 64 + (ks & 3) * 2), ks != 0);
                if (ks + 1 == HAND_AT) asm volatile("bar.arrive %0, 256;" ::"r"(next_turn) : "memory");
            }
            asm volatile("wgmma.commit_group.sync.aligned;" ::: "memory");
            asm volatile("wgmma.wait_group.sync.aligned 0;" ::: "memory");
#pragma unroll
            for (int j = 0; j < 32; j++) asm volatile("" : "+f"(acc[j])::"memory");
            TRE(2 + wg * 2, i);
            if (lane < 2) mbar_arrive_cta(bars + BAR_EMPTY + 8 * r.s, lane);

            if (held) write_out(wg_bars, st_addr, o, packed);
            o = r;
#pragma unroll
            for (int j = 0; j < 16; j++) packed[j] = pack_bias(acc[2 * j], acc[2 * j + 1], j & 1 ? bias_hi : bias_lo);
            held = !mbar_test(wg_bars + BAR_OFREE + o.s * 32, o.parity ^ 1);
            if (!held) write_out(wg_bars, st_addr, o, packed);
            TRE(8 + wg, i);
        }
        if (held) write_out(wg_bars, st_addr, o, packed);
        if (wg == 0) asm volatile("bar.sync 4, 256;" ::: "memory");
        TRE(1 + wg, 62);
    } else {
        asm volatile("setmaxnreg.dec.sync.aligned.u32 32;");
        if (warp == NUM_WG * 4) {
#pragma unroll
            for (int j = 0; j < NUM_WG; j++) mbar_init_1(bars + BAR_W + 8 * j, 1);
            publish_barriers();
            cluster_arrive();
#pragma unroll
            for (int j = 0; j < NUM_WG; j++) {
                mbar_expect_tx_1(bars + BAR_W + 8 * j, STAGE_BYTES);
                tma_load_w_1(smem + w_stage(j), &maps.w, bars + BAR_W + 8 * j, slice_channel(rank, j));
                if (j == 0) TR(2, 61);
            }
            cluster_wait();
            TR(0, 0);
            mbar_expect_tx_1(bars + BAR_FULL, STAGE_BYTES);
            tma_load_x_1(smem + rank * HALF_BYTES, &maps.x, bars + BAR_FULL, cluster * 8 + rank * 4);
            Ring r = {1, 0};
#pragma unroll 1
            for (uint32_t i = 1, id = cluster + num_clusters; id < num_tiles; i++, id += num_clusters, r.advance()) {
                mbar_wait(bars + BAR_EMPTY + 8 * r.s, r.parity ^ (r.s == 0));
                sts32(bars + ISSUED_AT, id);
                sts32(bars + STAMP_AT + 4 * r.s, timer_ns());
                TR(0, i);
                TRV(15, i, id);
                const uint32_t full = bars + BAR_FULL + 8 * r.s;
                const uint32_t dst = smem + r.s * STAGE_BYTES + rank * HALF_BYTES;
                mbar_expect_tx_1(full, STAGE_BYTES);
                if (id + tune.EF_TAIL < num_tiles) tma_load_x_1(dst, &maps.x, full, id * 8 + rank * 4);
                else tma_load_x_evict_first_1(dst, &maps.x, full, id * 8 + rank * 4);
            }
#pragma unroll 1
            for (int k = 0; k < STAGES; k++, r.advance()) mbar_wait(bars + BAR_EMPTY + 8 * r.s, r.parity ^ (r.s == 0));
        } else if (warp == NUM_WG * 4 + 1) {
#pragma unroll
            for (int s = 0; s < STAGES; s++) {
                mbar_init_1(bars + BAR_FULL + 8 * s, 1);
                mbar_init_1(bars + BAR_EMPTY + 8 * s, NUM_WG * 4 * 2);
            }
            publish_barriers();
            cluster_arrive();
            TR(0, 61);
            cluster_wait();
            prefetch_map_1(&maps.out);
            uint32_t delay = 0;
            Ring r = {0, 0};
#pragma unroll 1
            for (uint32_t i = 0, id = cluster; id < num_tiles; i++, id += num_clusters, r.advance()) {
                mbar_wait(bars + BAR_FULL + 8 * r.s, r.parity);
                TR(7, i);
                const int late = (int)(timer_ns() - lds32(bars + STAMP_AT + 4 * r.s) - tune.CC_L0);
                if (i >= tune.CC_AT && late > 0) {
                    delay = min(delay + min((uint32_t)late * tune.CC_G >> 4, tune.CC_STEP), tune.CC_CAP);
                    sts32(bars + DELAY_AT, delay);
                }
            }
        } else if (warp == NUM_WG * 4 + 2) {
            sts32(bars + DELAY_AT, 0);
#pragma unroll
            for (int b = 0; b < STAGES; b++) {
#pragma unroll
                for (int w = 0; w < NUM_WG; w++) {
                    mbar_init_1(bars + BAR_OFREE + b * 32 + w * 8, 1);
                    mbar_init_1(bars + BAR_OFULL + b * 32 + w * 8, 4);
                }
            }
            publish_barriers();
            cluster_arrive();
            cluster_wait();
            const uint32_t mark = num_tiles / num_clusters - tune.SW_J;
            const int behind = cluster < num_tiles % num_clusters ? cluster : cluster - num_clusters;
            const int stage = (int)tune.SW_D1 - behind * (int)tune.SW_K;
            uint32_t due = t_entry + tune.ST_T0 + cluster * tune.ST_STAG - tune.ST_P1;
            uint32_t open = 0, t_end = 0, delay = 0;
            Ring o = {0, 0};
#pragma unroll 1
            for (uint32_t j = 0, id = cluster; id < num_tiles; j++, id += num_clusters, o.advance()) {
                const uint32_t obar = bars + o.s * 32;
                if (!mbar_test(obar + BAR_OFULL, o.parity)) {
                    hand_back<0>(open);
                    mbar_wait(obar + BAR_OFULL, o.parity);
                }
                if (j >= tune.ST_AT) {
                    const uint32_t period = j <= tune.ST_E1 ? tune.ST_P1 : j <= tune.ST_E2 ? tune.ST_P2 : tune.ST_P3;
                    const int over = (int)(due + period - t_end);
                    if (j <= mark || over <= 0) {
                        due += period;
                    } else {
                        const int t = over < (int)period ? over * (int)tune.ST_PT / (int)period : over - (int)period + (int)tune.ST_PT;
                        due = t_end + min(t, stage);
                    }
                    uint32_t now;
#pragma unroll 1
                    for (uint32_t spins = 0; spins < SPIN_LIMIT; spins++) {
                        const uint32_t more = uniform(lds32(bars + DELAY_AT)) - delay;
                        delay += more;
                        due += more;
                        t_end += more;
                        now = timer_ns();
                        if (reached(now, due)) break;
                        hand_back<0>(open);
                        __nanosleep(20);
                    }
                    if (reached(now - tune.ST_SLACK, due)) due = now - tune.ST_SLACK;
                    if (j == mark) t_end = due - cluster * tune.ST_STAG + tune.SW_D;
                }
                const uint32_t src = smem + SMEM_OUT + o.s * HALF_BYTES;
                if (mbar_test(obar + BAR_OFULL + 8, o.parity) && mbar_test(obar + BAR_OFULL + 16, o.parity)) {
                    TR(11, j);
#pragma unroll
                    for (int w = 0; w < NUM_WG; w++) tma_store_1(&maps.out, src + w * SLICE_BYTES, slice_channel(rank, w), id * TILE_PIX);
                    hand_back<3>(open);
                    stores_read_wait<2>();
                    TR(12, j);
                    mbar_arrive_1(obar + BAR_OFREE);
                    stores_read_wait<1>();
                    TR(13, j);
                    mbar_arrive_1(obar + BAR_OFREE + 8);
                    open = obar + BAR_OFREE + 16;
                } else {
#pragma unroll 1
                    for (uint32_t w = 0; w < NUM_WG; w++) {
                        if (!mbar_test(obar + BAR_OFULL + w * 8, o.parity)) {
                            hand_back<0>(open);
                            mbar_wait(obar + BAR_OFULL + w * 8, o.parity);
                        }
                        TR(11 + w, j);
                        tma_store_1(&maps.out, src + w * SLICE_BYTES, slice_channel(rank, w), id * TILE_PIX);
                        hand_back<1>(open);
                        open = obar + BAR_OFREE + w * 8;
                    }
                }
            }
            stores_read_wait<0>();
            TR(4, 62);
        } else {
            sts32(bars + ISSUED_AT, 0);
            cluster_arrive();
            uint32_t due = t_entry + tune.PM_T0 + (blockIdx.x & 3) * tune.PM_STAG;
            const uint32_t step = num_clusters / 2;
#pragma unroll 1
            for (uint32_t piece = 1;; piece++) {
                const uint32_t t = cluster + piece / 2 * num_clusters;
                if (t >= num_tiles) break;
                const bool last = t + tune.LEAD_T >= num_tiles;
                uint32_t now;
#pragma unroll 1
                for (uint32_t spins = 0; spins < 16384; spins++) {
                    const uint32_t issued = uniform(lds32(bars + ISSUED_AT));
                    now = timer_ns();
                    const int lead = max((int)(last ? tune.LEAD_C : tune.LEAD_B), (int)tune.LEAD_A - (max((int)issued - (int)tune.LEAD_F, 0) * (int)tune.LEAD_S >> 4));
                    if (reached(now, due)) {
                        if (cluster + piece * step <= issued + lead) break;
                        due = now;
                    }
                    __nanosleep(20);
                }
                if (reached(now - tune.PM_SLACK, due)) due = now - tune.PM_SLACK;
                due += piece < tune.PM_E1 ? tune.PM_DT1 : piece < tune.PM_E2 ? tune.PM_DT2 : last ? tune.PM_DT4 : tune.PM_DT3;
                const uint8_t* p = x_raw + (size_t)t * STAGE_BYTES + rank * HALF_BYTES + (piece % 2) * PIECE_BYTES + lane * 128;
#pragma unroll
                for (int k = 0; k < PIECE_BYTES / 4096; k++) prefetch_l2(p + k * 4096);
                if (piece % 2 == 0) TR(14, piece / 2);
            }
            cluster_wait();
        }
    }
}

typedef CUresult (*EncodeTiledFn)(CUtensorMap*, CUtensorMapDataType, cuuint32_t, void*, const cuuint64_t*,
                                  const cuuint64_t*, const cuuint32_t*, const cuuint32_t*, CUtensorMapInterleave,
                                  CUtensorMapSwizzle, CUtensorMapL2promotion, CUtensorMapFloatOOBfill);

}

extern "C" void kernel_launch(void* const* d_in, const int* in_sizes, int n_in, void* d_out, int out_size) {
    (void)n_in;
    (void)out_size;
    void* x = d_in[0];
    void* w = d_in[1];
    const uint16_t* b = (const uint16_t*)d_in[2];
    const int M = in_sizes[0] / C;
    const int num_tiles = M / TILE_PIX;

    static EncodeTiledFn encode = nullptr;
    static int sms = 0;
    if (!encode) {
        void* fn = nullptr;
        cudaDriverEntryPointQueryResult q;
        cudaGetDriverEntryPoint("cuTensorMapEncodeTiled", &fn, cudaEnableDefault, &q);
        encode = (EncodeTiledFn)fn;
        cudaDeviceGetAttribute(&sms, cudaDevAttrMultiProcessorCount, 0);
        cudaFuncSetAttribute(conv1x1_kernel, cudaFuncAttributeMaxDynamicSharedMemorySize, SMEM_TOTAL);
    }

    Maps maps;
    const cuuint32_t ones[4] = {1, 1, 1, 1};
    auto make = [&](CUtensorMap* map, int rank, void* base, const cuuint64_t* dims, const cuuint64_t* strides,
                    const cuuint32_t* box, CUtensorMapL2promotion promo) {
        encode(map, CU_TENSOR_MAP_DATA_TYPE_BFLOAT16, rank, base, dims, strides, box, ones, CU_TENSOR_MAP_INTERLEAVE_NONE,
               CU_TENSOR_MAP_SWIZZLE_128B, promo, CU_TENSOR_MAP_FLOAT_OOB_FILL_NONE);
    };
    {
        const cuuint64_t dims[4]    = {64, 8, 6, (cuuint64_t)(M / 8)};
        const cuuint64_t strides[3] = {C * 2, 128, 8 * C * 2};
        const cuuint32_t box[4]     = {64, 8, 6, TILE_PIX / 16};
        make(&maps.x, 4, x, dims, strides, box, CU_TENSOR_MAP_L2_PROMOTION_L2_128B);
    }
    {
        const cuuint64_t dims[3]    = {C, C / 2, 2};
        const cuuint64_t strides[2] = {C * 2, C * C};
        const cuuint32_t box[3]     = {64, C / 2, 2};
        make(&maps.w, 3, w, dims, strides, box, CU_TENSOR_MAP_L2_PROMOTION_L2_128B);
    }
    {
        const cuuint64_t dims[2]    = {C, (cuuint64_t)M};
        const cuuint64_t strides[1] = {C * 2};
        const cuuint32_t box[2]     = {64, TILE_PIX};
        make(&maps.out, 2, d_out, dims, strides, box, CU_TENSOR_MAP_L2_PROMOTION_NONE);
    }

    const Tune tune;
    int clusters = sms / 2;
    if (clusters > num_tiles) clusters = num_tiles;
    conv1x1_kernel<<<clusters * 2, THREADS, SMEM_TOTAL>>>((const uint8_t*)x, (const uint8_t*)w, b, (uint32_t)num_tiles,
                                                          (uint32_t)clusters, maps, tune);
}
```

```cpp
#include <cuda_runtime.h>
#include <cuda_bf16.h>
#include <cuda.h>
#include <stdint.h>

#define TUNABLES(F) \
    F(PM_T0, 350)        \
    F(PM_STAG, 120)      \
    F(PM_DT1, 400)       \
    F(PM_E1, 7) \
    F(PM_DT2, 475) \
    F(PM_E2, 23) \
    F(PM_DT3, 860) \
    F(PM_SLACK, 600)     \
    F(LEAD_A, 280)       \
    F(LEAD_F, 500)       \
    F(LEAD_S, 3)         \
    F(LEAD_B, 151)       \
    F(LEAD_T, 264)         \
    F(LEAD_C, 170)       \
    F(PM_DT4, 820)       \
    F(EF_TAIL, 500)      \
    F(ST_AT, 2)          \
    F(ST_T0, 6800)       \
    F(ST_S1, 2040)       \
    F(ST_N1, 528) \
    F(ST_S2, 1860) \
    F(ST_N2, 594) \
    F(ST_S3, 1970)       \
    F(ST_END, 605) \
    F(ST_S4, 1670)       \
    F(ST_N4, 80) \
    F(ST_S5, 1200) \
    F(ST_N5, 40) \
    F(ST_S6, 500) \
    F(CC_AT, 22)         \
    F(CC_L0, 1200)       \
    F(CC_G, 12)          \
    F(CC_STEP, 900)      \
    F(CC_CAP, 1250)

struct Tune {
#define F(n, v) uint32_t n = v;
    TUNABLES(F)
#undef F
};

#define TRV(slot, idx, v)
#define TR(slot, idx)
#define TRE(slot, idx)
#define TRACE_BYTES 0

namespace {

constexpr int C            = 384;
constexpr int TILE_PIX     = 64;
constexpr int STAGES       = 3;
constexpr int STAGE_BYTES  = TILE_PIX * C * 2;
constexpr int HALF_BYTES   = STAGE_BYTES / 2;
constexpr int PIECE_BYTES  = HALF_BYTES / 2;
constexpr int SLICE_BYTES  = TILE_PIX * 128;
constexpr int NUM_WG       = 3;
constexpr int THREADS      = (NUM_WG + 1) * 128;
constexpr int SMEM_OUT     = STAGES * STAGE_BYTES;
constexpr int SMEM_BAR     = SMEM_OUT + STAGES * HALF_BYTES;
constexpr int SMEM_TOTAL   = SMEM_BAR + 512 + TRACE_BYTES + 1024;
constexpr int HAND_AT      = 18;
constexpr int W_LINES      = C * C * 2 / 128;
constexpr int PRE_W        = 64;
#define PD0 0
#define PDT 330
constexpr int PRE_D0       = PD0;
constexpr int PRE_DT       = PDT;
constexpr uint32_t SPIN_LIMIT = 1u << 22;
constexpr int BAR_W     = 0;
constexpr int BAR_FULL  = 32;
constexpr int BAR_EMPTY = 64;
constexpr int BAR_OFREE = 96;
constexpr int BAR_OFULL = BAR_OFREE + 32 * STAGES;
constexpr int ISSUED_AT = BAR_OFULL + 32 * STAGES;
constexpr int DELAY_AT  = ISSUED_AT + 4;
constexpr int STAMP_AT  = DELAY_AT + 4;
constexpr int SINK_AT   = 384;

struct Maps {
    CUtensorMap w, x, out;
};

#define ELECT "{\n.reg .pred e;\nelect.sync _|e, 0xffffffff;\n@e "

__device__ __forceinline__ uint32_t smem_u32(const void* p) {
    return (uint32_t)__cvta_generic_to_shared(p);
}
__device__ __forceinline__ void mbar_init_1(uint32_t bar, uint32_t count) {
    asm volatile(ELECT "mbarrier.init.shared::cta.b64 [%0], %1;\n}" ::"r"(bar), "r"(count) : "memory");
}
__device__ __forceinline__ void mbar_expect_tx_1(uint32_t bar, uint32_t bytes) {
    asm volatile(ELECT "mbarrier.arrive.expect_tx.shared::cta.b64 _, [%0], %1;\n}" ::"r"(bar), "r"(bytes) : "memory");
}
__device__ __forceinline__ void mbar_arrive_1(uint32_t bar) {
    asm volatile(ELECT "mbarrier.arrive.shared::cta.b64 _, [%0];\n}" ::"r"(bar) : "memory");
}
__device__ __forceinline__ void mbar_wait(uint32_t bar, uint32_t parity) {
    uint32_t done;
    uint32_t spins = 0;
    do {
        asm volatile(
            "{\n.reg .pred p;\n"
            "mbarrier.try_wait.parity.shared::cta.b64 p, [%1], %2;\n"
            "selp.u32 %0, 1, 0, p;\n}"
            : "=r"(done) : "r"(bar), "r"(parity) : "memory");
    } while (!done && ++spins < SPIN_LIMIT);
    __syncwarp();
}
__device__ __forceinline__ bool mbar_test(uint32_t bar, uint32_t parity) {
    uint32_t done;
    asm volatile(
        "{\n.reg .pred p;\n"
        "mbarrier.test_wait.parity.shared::cta.b64 p, [%1], %2;\n"
        "selp.u32 %0, 1, 0, p;\n}"
        : "=r"(done) : "r"(bar), "r"(parity) : "memory");
    return __all_sync(0xffffffffu, done);
}
__device__ __forceinline__ void mbar_arrive_cta(uint32_t bar, uint32_t cta) {
    asm volatile(
        "{\n.reg .b32 ra;\n"
        "mapa.shared::cluster.u32 ra, %0, %1;\n"
        "mbarrier.arrive.shared::cluster.b64 _, [ra];\n}"
        ::"r"(bar), "r"(cta) : "memory");
}
__device__ __forceinline__ uint32_t lds32(uint32_t addr) {
    uint32_t v;
    asm volatile("ld.volatile.shared.b32 %0, [%1];" : "=r"(v) : "r"(addr) : "memory");
    return v;
}
__device__ __forceinline__ void sts32(uint32_t addr, uint32_t v) {
    asm volatile("st.volatile.shared.b32 [%0], %1;" ::"r"(addr), "r"(v) : "memory");
}
__device__ __forceinline__ uint32_t uniform(uint32_t v) {
    return __shfl_sync(0xffffffffu, v, 0);
}
__device__ __forceinline__ void tma_load_w_1(uint32_t dst, const CUtensorMap* map, uint32_t bar, int n) {
    asm volatile(
        ELECT "cp.async.bulk.tensor.3d.shared::cluster.global.mbarrier::complete_tx::bytes [%0], [%1, {%3, %4, %4}], [%2];\n}"
        ::"r"(dst), "l"(map), "r"(bar), "r"(n), "r"(0) : "memory");
}
__device__ __forceinline__ void tma_load_x_1(uint32_t dst, const CUtensorMap* map, uint32_t bar, int group) {
    asm volatile(
        ELECT "cp.async.bulk.tensor.4d.shared::cluster.global.mbarrier::complete_tx::bytes.multicast::cluster"
        " [%0], [%1, {%3, %3, %3, %4}], [%2], %5;\n}"
        ::"r"(dst), "l"(map), "r"(bar), "r"(0), "r"(group), "h"((uint16_t)3) : "memory");
}
__device__ __forceinline__ void tma_load_x_evict_first_1(uint32_t dst, const CUtensorMap* map, uint32_t bar, int group) {
    asm volatile(
        "{\n.reg .b64 pol;\n"
        "createpolicy.fractional.L2::evict_first.b64 pol, 1.0;\n"
        ELECT "cp.async.bulk.tensor.4d.shared::cluster.global.mbarrier::complete_tx::bytes.multicast::cluster.L2::cache_hint"
        " [%0], [%1, {%3, %3, %3, %4}], [%2], %5, pol;\n}\n}"
        ::"r"(dst), "l"(map), "r"(bar), "r"(0), "r"(group), "h"((uint16_t)3) : "memory");
}
__device__ __forceinline__ void tma_store_1(const CUtensorMap* map, uint32_t src, int ch, int pix) {
    asm volatile(
        ELECT "cp.async.bulk.tensor.2d.global.shared::cta.bulk_group [%0, {%2, %3}], [%1];\n}\n"
        "cp.async.bulk.commit_group;"
        ::"l"(map), "r"(src), "r"(ch), "r"(pix) : "memory");
}
template <int N>
__device__ __forceinline__ void stores_read_wait() {
    asm volatile("cp.async.bulk.wait_group.read %0;" ::"n"(N) : "memory");
}
__device__ __forceinline__ void prefetch_map_1(const CUtensorMap* map) {
    asm volatile(ELECT "prefetch.tensormap [%0];\n}" ::"l"(map) : "memory");
}
__device__ __forceinline__ void prefetch_l2(const void* p) {
    asm volatile("prefetch.global.L2 [%0];" ::"l"(p) : "memory");
}
__device__ __forceinline__ uint32_t timer_ns() {
    uint32_t t;
    asm volatile("mov.u32 %0, %%globaltimer_lo;" : "=r"(t)::"memory");
    return t;
}
__device__ __forceinline__ bool reached(uint32_t now, uint32_t t) {
    return (int32_t)(now - t) >= 0;
}
__device__ __forceinline__ void cluster_arrive() {
    asm volatile("barrier.cluster.arrive.relaxed.aligned;" ::: "memory");
}
__device__ __forceinline__ void cluster_wait() {
    asm volatile("barrier.cluster.wait.aligned;" ::: "memory");
}
__device__ __forceinline__ void publish_barriers() {
    asm volatile("fence.mbarrier_init.release.cluster;" ::: "memory");
    asm volatile("fence.proxy.async.shared::cta;" ::: "memory");
}

__device__ __forceinline__ void wgmma_rs_n64(float (&d)[32], const uint32_t* a, uint64_t desc, int scale_d) {
    asm volatile(
        "{\n.reg .pred p;\n"
        "setp.ne.b32 p, %37, 0;\n"
        "wgmma.mma_async.sync.aligned.m64n64k16.f32.bf16.bf16 "
        "{%0, %1, %2, %3, %4, %5, %6, %7, %8, %9, %10, %11, %12, %13, %14, %15, "
        "%16, %17, %18, %19, %20, %21, %22, %23, %24, %25, %26, %27, %28, %29, %30, %31}, "
        "{%32, %33, %34, %35}, %36, p, 1, 1, 0;\n}"
        : "+f"(d[0]), "+f"(d[1]), "+f"(d[2]), "+f"(d[3]), "+f"(d[4]), "+f"(d[5]), "+f"(d[6]), "+f"(d[7]),
          "+f"(d[8]), "+f"(d[9]), "+f"(d[10]), "+f"(d[11]), "+f"(d[12]), "+f"(d[13]), "+f"(d[14]), "+f"(d[15]),
          "+f"(d[16]), "+f"(d[17]), "+f"(d[18]), "+f"(d[19]), "+f"(d[20]), "+f"(d[21]), "+f"(d[22]), "+f"(d[23]),
          "+f"(d[24]), "+f"(d[25]), "+f"(d[26]), "+f"(d[27]), "+f"(d[28]), "+f"(d[29]), "+f"(d[30]), "+f"(d[31])
        : "r"(a[0]), "r"(a[1]), "r"(a[2]), "r"(a[3]), "l"(desc), "r"(scale_d));
}

__device__ __forceinline__ uint32_t pack_bias(float lo, float hi, uint32_t bias2) {
    uint32_t r;
    asm("{\n.reg .b32 t;\n"
        "cvt.rn.bf16x2.f32 t, %2, %1;\n"
        "add.rn.bf16x2 %0, t, %3;\n}"
        : "=r"(r) : "f"(lo), "f"(hi), "r"(bias2));
    return r;
}

__device__ __forceinline__ int slice_channel(uint32_t rank, int wg) {
    return (wg * 2 + rank) * 64;
}
__device__ __forceinline__ uint32_t w_stage(int wg) {
    return (wg + 1) * STAGE_BYTES + (wg == 2 ? HALF_BYTES : 0);
}

struct Ring {
    uint32_t s, parity;
    __device__ __forceinline__ void advance() {
        if (++s == STAGES) {
            s = 0;
            parity ^= 1;
        }
    }
};

__device__ __forceinline__ void write_out(uint32_t wg_bars, uint32_t st_addr, const Ring& r, const uint32_t (&v)[16]) {
    mbar_wait(wg_bars + BAR_OFREE + r.s * 32, r.parity ^ 1);
    const uint32_t dst = st_addr + r.s * HALF_BYTES;
#pragma unroll
    for (int j = 0; j < 4; j++) {
        asm volatile("stmatrix.sync.aligned.m8n8.x4.trans.shared.b16 [%0], {%1, %2, %3, %4};"
                     ::"r"(dst + j * 2048), "r"(v[4 * j]), "r"(v[4 * j + 1]), "r"(v[4 * j + 2]), "r"(v[4 * j + 3]) : "memory");
    }
    asm volatile("fence.proxy.async.shared::cta;" ::: "memory");
    __syncwarp();
    mbar_arrive_1(wg_bars + BAR_OFULL + r.s * 32);
}

template <int N>
__device__ __forceinline__ void hand_back(uint32_t& open) {
    if (open != 0) {
        stores_read_wait<N>();
        mbar_arrive_1(open);
        open = 0;
    }
}

__global__ void __cluster_dims__(2, 1, 1) __launch_bounds__(THREADS, 1)
conv1x1_kernel(const uint8_t* __restrict__ x_raw,
               const uint8_t* __restrict__ w_raw,
               const uint16_t* __restrict__ bias,
               uint32_t num_tiles,
               uint32_t num_clusters,
               const __grid_constant__ Maps maps,
               const __grid_constant__ Tune tune) {
    const uint32_t t_entry = timer_ns();
    extern __shared__ uint8_t smem_raw[];
    const uint32_t smem = (smem_u32(smem_raw) + 1023u) & ~1023u;
    const uint32_t bars = smem + SMEM_BAR;

    if (threadIdx.x < PRE_W) {
        prefetch_l2(w_raw + (blockIdx.x % (W_LINES / PRE_W) * PRE_W + threadIdx.x) * 128);
    } else if (threadIdx.x >= 96 && threadIdx.x < 128) {
        prefetch_map_1(&maps.w);
        prefetch_map_1(&maps.x);
    }
    if (threadIdx.x < NUM_WG * 128) cluster_arrive();
    if (threadIdx.x >= 128 && threadIdx.x < 128 + PIECE_BYTES / 128) {
        const uint8_t* p = x_raw + (size_t)blockIdx.x * HALF_BYTES + (threadIdx.x - 128) * 128;
        const uint32_t wait = PRE_D0 + ((threadIdx.x - 128) >> 5) * PRE_DT;
        const uint32_t c0 = (uint32_t)clock();
        while ((uint32_t)clock() - c0 < wait) {}
        asm volatile("cp.async.ca.shared.global.L2::128B [%0], [%1], 4;" ::"r"(bars + SINK_AT + (threadIdx.x & 31) * 4), "l"(p) : "memory");
    }
    if (threadIdx.x == 0) TRV(0, 63, t_entry);

    const int warp = uniform(threadIdx.x >> 5);
    const int lane = threadIdx.x & 31;
    const uint32_t rank    = blockIdx.x & 1;
    const uint32_t cluster = blockIdx.x >> 1;

    if (warp < NUM_WG * 4) {
        asm volatile("setmaxnreg.inc.sync.aligned.u32 160;");
        const int wg = warp >> 2;
        const int wq = warp & 3;
        const uint32_t bias_lo = bias[slice_channel(rank, wg) + wq * 16 + (lane >> 2)] * 0x10001u;
        const uint32_t bias_hi = bias[slice_channel(rank, wg) + wq * 16 + (lane >> 2) + 8] * 0x10001u;

        cluster_wait();
        TRE(1 + wg, 63);
        mbar_wait(bars + BAR_W + 8 * wg, 0);
        TRE(4 + wg, 63);
        uint32_t wreg[96];
        {
            const int r = lane & 7, m = lane >> 3;
            const uint32_t base = smem + w_stage(wg) + ((m >> 1) * 8 + r) * 128 + (((2 * wq + (m & 1)) ^ r) << 4);
#pragma unroll
            for (int ks = 0; ks < 24; ks++) {
                asm volatile("ldmatrix.sync.aligned.m8n8.x4.trans.shared.b16 {%0, %1, %2, %3}, [%4];"
                             : "=r"(wreg[ks * 4 + 0]), "=r"(wreg[ks * 4 + 1]), "=r"(wreg[ks * 4 + 2]), "=r"(wreg[ks * 4 + 3])
                             : "r"(base + ks * 2048) : "memory");
            }
        }
        uint32_t dep = 0;
#pragma unroll
        for (int ks = 0; ks < 24; ks++) dep ^= wreg[ks * 4];
        dep = uniform(dep & (num_tiles >> 31));
        if (lane < 6 && wg < 2) mbar_arrive_cta(bars + BAR_EMPTY + 8 * (wg + 1) + dep, lane & 1);
        asm volatile("cp.async.wait_all;" ::: "memory");
        TRE(1 + wg, 60);

        const uint32_t wg_bars = bars + wg * 8;
        const uint32_t st_addr = smem + SMEM_OUT + wg * SLICE_BYTES + ((lane >> 4) * 8 + (lane & 7)) * 128 +
                                 (((2 * wq + ((lane >> 3) & 1)) ^ (lane & 7)) << 4);
        const uint64_t desc_base =
            (uint64_t)((smem & 0x3FFFF) >> 4) | ((uint64_t)1 << 16) | ((uint64_t)(6144 >> 4) << 32) | ((uint64_t)1 << 62);
        const int next_turn = 4 + (wg + 1) % NUM_WG;

        float acc[32];
        uint32_t packed[16];
        Ring r = {0, dep}, o = r;
        bool held = false;
        for (uint32_t i = 0, id = cluster; id < num_tiles; i++, id += num_clusters, r.advance()) {
            mbar_wait(bars + BAR_FULL + 8 * r.s, r.parity);
            if ((i | wg) != 0) asm volatile("bar.sync %0, 256;" ::"r"(4 + wg) : "memory");
            TRE(1 + wg * 2, i);
            const uint64_t desc = desc_base + (uint64_t)(r.s * (STAGE_BYTES >> 4));
            asm volatile("wgmma.fence.sync.aligned;" ::: "memory");
#pragma unroll
            for (int ks = 0; ks < 24; ks++) {
                wgmma_rs_n64(acc, &wreg[ks * 4], desc + (uint64_t)((ks >> 2) * 64 + (ks & 3) * 2), ks != 0);
                if (ks + 1 == HAND_AT) asm volatile("bar.arrive %0, 256;" ::"r"(next_turn) : "memory");
            }
            asm volatile("wgmma.commit_group.sync.aligned;" ::: "memory");
            asm volatile("wgmma.wait_group.sync.aligned 0;" ::: "memory");
#pragma unroll
            for (int j = 0; j < 32; j++) asm volatile("" : "+f"(acc[j])::"memory");
            TRE(2 + wg * 2, i);
            if (lane < 2) mbar_arrive_cta(bars + BAR_EMPTY + 8 * r.s, lane);

            if (held) write_out(wg_bars, st_addr, o, packed);
            o = r;
#pragma unroll
            for (int j = 0; j < 16; j++) packed[j] = pack_bias(acc[2 * j], acc[2 * j + 1], j & 1 ? bias_hi : bias_lo);
            held = !mbar_test(wg_bars + BAR_OFREE + o.s * 32, o.parity ^ 1);
            if (!held) write_out(wg_bars, st_addr, o, packed);
            TRE(8 + wg, i);
        }
        if (held) write_out(wg_bars, st_addr, o, packed);
        if (wg == 0) asm volatile("bar.sync 4, 256;" ::: "memory");
        TRE(1 + wg, 62);
    } else {
        asm volatile("setmaxnreg.dec.sync.aligned.u32 32;");
        if (warp == NUM_WG * 4) {
#pragma unroll
            for (int j = 0; j < NUM_WG; j++) mbar_init_1(bars + BAR_W + 8 * j, 1);
            publish_barriers();
            cluster_arrive();
#pragma unroll
            for (int j = 0; j < NUM_WG; j++) {
                mbar_expect_tx_1(bars + BAR_W + 8 * j, STAGE_BYTES);
                tma_load_w_1(smem + w_stage(j), &maps.w, bars + BAR_W + 8 * j, slice_channel(rank, j));
                if (j == 0) TR(2, 61);
            }
            cluster_wait();
            TR(0, 0);
            mbar_expect_tx_1(bars + BAR_FULL, STAGE_BYTES);
            tma_load_x_1(smem + rank * HALF_BYTES, &maps.x, bars + BAR_FULL, cluster * 8 + rank * 4);
            Ring r = {1, 0};
#pragma unroll 1
            for (uint32_t i = 1, id = cluster + num_clusters; id < num_tiles; i++, id += num_clusters, r.advance()) {
                mbar_wait(bars + BAR_EMPTY + 8 * r.s, r.parity ^ (r.s == 0));
                sts32(bars + ISSUED_AT, id);
                sts32(bars + STAMP_AT + 4 * r.s, timer_ns());
                TR(0, i);
                TRV(15, i, id);
                const uint32_t full = bars + BAR_FULL + 8 * r.s;
                const uint32_t dst = smem + r.s * STAGE_BYTES + rank * HALF_BYTES;
                mbar_expect_tx_1(full, STAGE_BYTES);
                if (id + tune.EF_TAIL < num_tiles) tma_load_x_1(dst, &maps.x, full, id * 8 + rank * 4);
                else tma_load_x_evict_first_1(dst, &maps.x, full, id * 8 + rank * 4);
            }
#pragma unroll 1
            for (int k = 0; k < STAGES; k++, r.advance()) mbar_wait(bars + BAR_EMPTY + 8 * r.s, r.parity ^ (r.s == 0));
        } else if (warp == NUM_WG * 4 + 1) {
#pragma unroll
            for (int s = 0; s < STAGES; s++) {
                mbar_init_1(bars + BAR_FULL + 8 * s, 1);
                mbar_init_1(bars + BAR_EMPTY + 8 * s, NUM_WG * 4 * 2);
            }
            publish_barriers();
            cluster_arrive();
            TR(0, 61);
            cluster_wait();
            prefetch_map_1(&maps.out);
            uint32_t delay = 0;
            Ring r = {0, 0};
#pragma unroll 1
            for (uint32_t i = 0, id = cluster; id < num_tiles; i++, id += num_clusters, r.advance()) {
                mbar_wait(bars + BAR_FULL + 8 * r.s, r.parity);
                TR(7, i);
                const int late = (int)(timer_ns() - lds32(bars + STAMP_AT + 4 * r.s) - tune.CC_L0);
                if (i >= tune.CC_AT && late > 0) {
                    delay = min(delay + min((uint32_t)late * tune.CC_G >> 4, tune.CC_STEP), tune.CC_CAP);
                    sts32(bars + DELAY_AT, delay);
                }
            }
        } else if (warp == NUM_WG * 4 + 2) {
            sts32(bars + DELAY_AT, 0);
#pragma unroll
            for (int b = 0; b < STAGES; b++) {
#pragma unroll
                for (int w = 0; w < NUM_WG; w++) {
                    mbar_init_1(bars + BAR_OFREE + b * 32 + w * 8, 1);
                    mbar_init_1(bars + BAR_OFULL + b * 32 + w * 8, 4);
                }
            }
            publish_barriers();
            cluster_arrive();
            cluster_wait();
            const uint32_t first = tune.ST_AT * num_clusters;
            const uint32_t n3 = max((int)(num_tiles - first - tune.ST_N1 - tune.ST_N2 - tune.ST_END), 0);
            uint32_t open = 0;
            Ring o = {0, 0};
#pragma unroll 1
            for (uint32_t j = 0, id = cluster; id < num_tiles; j++, id += num_clusters, o.advance()) {
                const uint32_t obar = bars + o.s * 32;
                if (!mbar_test(obar + BAR_OFULL, o.parity)) {
                    hand_back<0>(open);
                    mbar_wait(obar + BAR_OFULL, o.parity);
                }
                if (id >= first) {
                    uint32_t rest = id - first, t = 0;
                    auto segment = [&](uint32_t ids, uint32_t per_round) {
                        const uint32_t n = min(rest, ids);
                        t += n * per_round;
                        rest -= n;
                    };
                    segment(tune.ST_N1, tune.ST_S1);
                    segment(tune.ST_N2, tune.ST_S2);
                    segment(n3, tune.ST_S3);
                    segment(tune.ST_N4, tune.ST_S4);
                    segment(tune.ST_N5, tune.ST_S5);
                    const uint32_t due = t_entry + tune.ST_T0 + (t + rest * tune.ST_S6) / num_clusters;
#pragma unroll 1
                    for (uint32_t spins = 0; spins < SPIN_LIMIT; spins++) {
                        const uint32_t delay = uniform(lds32(bars + DELAY_AT));
                        if (reached(timer_ns(), due + delay)) break;
                        hand_back<0>(open);
                        __nanosleep(20);
                    }
                }
                const uint32_t src = smem + SMEM_OUT + o.s * HALF_BYTES;
                if (mbar_test(obar + BAR_OFULL + 8, o.parity) && mbar_test(obar + BAR_OFULL + 16, o.parity)) {
                    TR(11, j);
#pragma unroll
                    for (int w = 0; w < NUM_WG; w++) tma_store_1(&maps.out, src + w * SLICE_BYTES, slice_channel(rank, w), id * TILE_PIX);
                    hand_back<3>(open);
                    stores_read_wait<2>();
                    TR(12, j);
                    mbar_arrive_1(obar + BAR_OFREE);
                    stores_read_wait<1>();
                    TR(13, j);
                    mbar_arrive_1(obar + BAR_OFREE + 8);
                    open = obar + BAR_OFREE + 16;
                } else {
#pragma unroll 1
                    for (uint32_t w = 0; w < NUM_WG; w++) {
                        if (!mbar_test(obar + BAR_OFULL + w * 8, o.parity)) {
                            hand_back<0>(open);
                            mbar_wait(obar + BAR_OFULL + w * 8, o.parity);
                        }
                        TR(11 + w, j);
                        tma_store_1(&maps.out, src + w * SLICE_BYTES, slice_channel(rank, w), id * TILE_PIX);
                        hand_back<1>(open);
                        open = obar + BAR_OFREE + w * 8;
                    }
                }
            }
            stores_read_wait<0>();
            TR(4, 62);
        } else {
            sts32(bars + ISSUED_AT, 0);
            cluster_arrive();
            uint32_t due = t_entry + tune.PM_T0 + (blockIdx.x & 3) * tune.PM_STAG;
            const uint32_t step = num_clusters / 2;
#pragma unroll 1
            for (uint32_t piece = 1;; piece++) {
                const uint32_t t = cluster + piece / 2 * num_clusters;
                if (t >= num_tiles) break;
                const bool last = t + tune.LEAD_T >= num_tiles;
                uint32_t now;
#pragma unroll 1
                for (uint32_t spins = 0; spins < 16384; spins++) {
                    const uint32_t issued = uniform(lds32(bars + ISSUED_AT));
                    now = timer_ns();
                    const int lead = max((int)(last ? tune.LEAD_C : tune.LEAD_B), (int)tune.LEAD_A - (max((int)issued - (int)tune.LEAD_F, 0) * (int)tune.LEAD_S >> 4));
                    if (reached(now, due)) {
                        if (cluster + piece * step <= issued + lead) break;
                        due = now;
                    }
                    __nanosleep(20);
                }
                if (reached(now - tune.PM_SLACK, due)) due = now - tune.PM_SLACK;
                due += piece < tune.PM_E1 ? tune.PM_DT1 : piece < tune.PM_E2 ? tune.PM_DT2 : last ? tune.PM_DT4 : tune.PM_DT3;
                const uint8_t* p = x_raw + (size_t)t * STAGE_BYTES + rank * HALF_BYTES + (piece % 2) * PIECE_BYTES + lane * 128;
#pragma unroll
                for (int k = 0; k < PIECE_BYTES / 4096; k++) prefetch_l2(p + k * 4096);
                if (piece % 2 == 0) TR(14, piece / 2);
            }
            cluster_wait();
        }
    }
}

typedef CUresult (*EncodeTiledFn)(CUtensorMap*, CUtensorMapDataType, cuuint32_t, void*, const cuuint64_t*,
                                  const cuuint64_t*, const cuuint32_t*, const cuuint32_t*, CUtensorMapInterleave,
                                  CUtensorMapSwizzle, CUtensorMapL2promotion, CUtensorMapFloatOOBfill);

}

extern "C" void kernel_launch(void* const* d_in, const int* in_sizes, int n_in, void* d_out, int out_size) {
    (void)n_in;
    (void)out_size;
    void* x = d_in[0];
    void* w = d_in[1];
    const uint16_t* b = (const uint16_t*)d_in[2];
    const int M = in_sizes[0] / C;
    const int num_tiles = M / TILE_PIX;

    static EncodeTiledFn encode = nullptr;
    static int sms = 0;
    if (!encode) {
        void* fn = nullptr;
        cudaDriverEntryPointQueryResult q;
        cudaGetDriverEntryPoint("cuTensorMapEncodeTiled", &fn, cudaEnableDefault, &q);
        encode = (EncodeTiledFn)fn;
        cudaDeviceGetAttribute(&sms, cudaDevAttrMultiProcessorCount, 0);
        cudaFuncSetAttribute(conv1x1_kernel, cudaFuncAttributeMaxDynamicSharedMemorySize, SMEM_TOTAL);
    }

    Maps maps;
    const cuuint32_t ones[4] = {1, 1, 1, 1};
    auto make = [&](CUtensorMap* map, int rank, void* base, const cuuint64_t* dims, const cuuint64_t* strides,
                    const cuuint32_t* box, CUtensorMapL2promotion promo) {
        encode(map, CU_TENSOR_MAP_DATA_TYPE_BFLOAT16, rank, base, dims, strides, box, ones, CU_TENSOR_MAP_INTERLEAVE_NONE,
               CU_TENSOR_MAP_SWIZZLE_128B, promo, CU_TENSOR_MAP_FLOAT_OOB_FILL_NONE);
    };
    {
        const cuuint64_t dims[4]    = {64, 8, 6, (cuuint64_t)(M / 8)};
        const cuuint64_t strides[3] = {C * 2, 128, 8 * C * 2};
        const cuuint32_t box[4]     = {64, 8, 6, TILE_PIX / 16};
        make(&maps.x, 4, x, dims, strides, box, CU_TENSOR_MAP_L2_PROMOTION_L2_128B);
    }
    {
        const cuuint64_t dims[3]    = {C, C / 2, 2};
        const cuuint64_t strides[2] = {C * 2, C * C};
        const cuuint32_t box[3]     = {64, C / 2, 2};
        make(&maps.w, 3, w, dims, strides, box, CU_TENSOR_MAP_L2_PROMOTION_L2_128B);
    }
    {
        const cuuint64_t dims[2]    = {C, (cuuint64_t)M};
        const cuuint64_t strides[1] = {C * 2};
        const cuuint32_t box[2]     = {64, TILE_PIX};
        make(&maps.out, 2, d_out, dims, strides, box, CU_TENSOR_MAP_L2_PROMOTION_NONE);
    }

    const Tune tune;
    int clusters = sms / 2;
    if (clusters > num_tiles) clusters = num_tiles;
    conv1x1_kernel<<<clusters * 2, THREADS, SMEM_TOTAL>>>((const uint8_t*)x, (const uint8_t*)w, b, (uint32_t)num_tiles,
                                                          (uint32_t)clusters, maps, tune);
}
```

```cpp
#include <cuda_runtime.h>
#include <cuda_bf16.h>
#include <cuda.h>
#include <stdint.h>

#define TUNABLES(F) \
    F(PM_T0, 350)        \
    F(PM_STAG, 120)      \
    F(PM_DT1, 400)       \
    F(PM_E1, 7) \
    F(PM_DT2, 475) \
    F(PM_E2, 23) \
    F(PM_DT3, 860) \
    F(PM_SLACK, 600)     \
    F(LEAD_A, 280)       \
    F(LEAD_F, 500)       \
    F(LEAD_S, 3)         \
    F(LEAD_B, 151)       \
    F(LEAD_T, 264)         \
    F(LEAD_C, 170)       \
    F(PM_DT4, 820)       \
    F(EF_TAIL, 500)      \
    F(ST_AT, 2)          \
    F(ST_T0, 6800)       \
    F(ST_S1, 2040)       \
    F(ST_N1, 528) \
    F(ST_S2, 1860) \
    F(ST_N2, 594) \
    F(ST_S3, 1970)       \
    F(ST_END, 605) \
    F(ST_S4, 1670)       \
    F(ST_N4, 80) \
    F(ST_S5, 1200) \
    F(ST_N5, 40) \
    F(ST_S6, 500) \
    F(CC_AT, 22)         \
    F(CC_L0, 1200)       \
    F(CC_G, 12)          \
    F(CC_STEP, 900)      \
    F(CC_CAP, 1300)

struct Tune {
#define F(n, v) uint32_t n = v;
    TUNABLES(F)
#undef F
};

#define TRV(slot, idx, v)
#define TR(slot, idx)
#define TRE(slot, idx)
#define TRACE_BYTES 0

namespace {

constexpr int C            = 384;
constexpr int TILE_PIX     = 64;
constexpr int STAGES       = 3;
constexpr int STAGE_BYTES  = TILE_PIX * C * 2;
constexpr int HALF_BYTES   = STAGE_BYTES / 2;
constexpr int PIECE_BYTES  = HALF_BYTES / 2;
constexpr int SLICE_BYTES  = TILE_PIX * 128;
constexpr int NUM_WG       = 3;
constexpr int THREADS      = (NUM_WG + 1) * 128;
constexpr int SMEM_OUT     = STAGES * STAGE_BYTES;
constexpr int SMEM_BAR     = SMEM_OUT + STAGES * HALF_BYTES;
constexpr int SMEM_TOTAL   = SMEM_BAR + 512 + TRACE_BYTES + 1024;
constexpr int HAND_AT      = 18;
constexpr int W_LINES      = C * C * 2 / 128;
constexpr int PRE_W        = 64;
constexpr int PRE_DT       = 330;
constexpr uint32_t SPIN_LIMIT = 1u << 22;
constexpr int BAR_W     = 0;
constexpr int BAR_FULL  = 32;
constexpr int BAR_EMPTY = 64;
constexpr int BAR_OFREE = 96;
constexpr int BAR_OFULL = BAR_OFREE + 32 * STAGES;
constexpr int ISSUED_AT = BAR_OFULL + 32 * STAGES;
constexpr int DELAY_AT  = ISSUED_AT + 4;
constexpr int STAMP_AT  = DELAY_AT + 4;
constexpr int SINK_AT   = 384;

struct Maps {
    CUtensorMap w, x, out;
};

#define ELECT "{\n.reg .pred e;\nelect.sync _|e, 0xffffffff;\n@e "

__device__ __forceinline__ uint32_t smem_u32(const void* p) {
    return (uint32_t)__cvta_generic_to_shared(p);
}
__device__ __forceinline__ void mbar_init_1(uint32_t bar, uint32_t count) {
    asm volatile(ELECT "mbarrier.init.shared::cta.b64 [%0], %1;\n}" ::"r"(bar), "r"(count) : "memory");
}
__device__ __forceinline__ void mbar_expect_tx_1(uint32_t bar, uint32_t bytes) {
    asm volatile(ELECT "mbarrier.arrive.expect_tx.shared::cta.b64 _, [%0], %1;\n}" ::"r"(bar), "r"(bytes) : "memory");
}
__device__ __forceinline__ void mbar_arrive_1(uint32_t bar) {
    asm volatile(ELECT "mbarrier.arrive.shared::cta.b64 _, [%0];\n}" ::"r"(bar) : "memory");
}
__device__ __forceinline__ void mbar_wait(uint32_t bar, uint32_t parity) {
    uint32_t done;
    uint32_t spins = 0;
    do {
        asm volatile(
            "{\n.reg .pred p;\n"
            "mbarrier.try_wait.parity.shared::cta.b64 p, [%1], %2;\n"
            "selp.u32 %0, 1, 0, p;\n}"
            : "=r"(done) : "r"(bar), "r"(parity) : "memory");
    } while (!done && ++spins < SPIN_LIMIT);
    __syncwarp();
}
__device__ __forceinline__ bool mbar_test(uint32_t bar, uint32_t parity) {
    uint32_t done;
    asm volatile(
        "{\n.reg .pred p;\n"
        "mbarrier.test_wait.parity.shared::cta.b64 p, [%1], %2;\n"
        "selp.u32 %0, 1, 0, p;\n}"
        : "=r"(done) : "r"(bar), "r"(parity) : "memory");
    return __all_sync(0xffffffffu, done);
}
__device__ __forceinline__ void mbar_arrive_cta(uint32_t bar, uint32_t cta) {
    asm volatile(
        "{\n.reg .b32 ra;\n"
        "mapa.shared::cluster.u32 ra, %0, %1;\n"
        "mbarrier.arrive.shared::cluster.b64 _, [ra];\n}"
        ::"r"(bar), "r"(cta) : "memory");
}
__device__ __forceinline__ uint32_t lds32(uint32_t addr) {
    uint32_t v;
    asm volatile("ld.volatile.shared.b32 %0, [%1];" : "=r"(v) : "r"(addr) : "memory");
    return v;
}
__device__ __forceinline__ void sts32(uint32_t addr, uint32_t v) {
    asm volatile("st.volatile.shared.b32 [%0], %1;" ::"r"(addr), "r"(v) : "memory");
}
__device__ __forceinline__ uint32_t uniform(uint32_t v) {
    return __shfl_sync(0xffffffffu, v, 0);
}
__device__ __forceinline__ void tma_load_w_1(uint32_t dst, const CUtensorMap* map, uint32_t bar, int n) {
    asm volatile(
        ELECT "cp.async.bulk.tensor.3d.shared::cluster.global.mbarrier::complete_tx::bytes [%0], [%1, {%3, %4, %4}], [%2];\n}"
        ::"r"(dst), "l"(map), "r"(bar), "r"(n), "r"(0) : "memory");
}
__device__ __forceinline__ void tma_load_x_1(uint32_t dst, const CUtensorMap* map, uint32_t bar, int group) {
    asm volatile(
        ELECT "cp.async.bulk.tensor.4d.shared::cluster.global.mbarrier::complete_tx::bytes.multicast::cluster"
        " [%0], [%1, {%3, %3, %3, %4}], [%2], %5;\n}"
        ::"r"(dst), "l"(map), "r"(bar), "r"(0), "r"(group), "h"((uint16_t)3) : "memory");
}
__device__ __forceinline__ void tma_load_x_evict_first_1(uint32_t dst, const CUtensorMap* map, uint32_t bar, int group) {
    asm volatile(
        "{\n.reg .b64 pol;\n"
        "createpolicy.fractional.L2::evict_first.b64 pol, 1.0;\n"
        ELECT "cp.async.bulk.tensor.4d.shared::cluster.global.mbarrier::complete_tx::bytes.multicast::cluster.L2::cache_hint"
        " [%0], [%1, {%3, %3, %3, %4}], [%2], %5, pol;\n}\n}"
        ::"r"(dst), "l"(map), "r"(bar), "r"(0), "r"(group), "h"((uint16_t)3) : "memory");
}
__device__ __forceinline__ void tma_store_1(const CUtensorMap* map, uint32_t src, int ch, int pix) {
    asm volatile(
        ELECT "cp.async.bulk.tensor.2d.global.shared::cta.bulk_group [%0, {%2, %3}], [%1];\n}\n"
        "cp.async.bulk.commit_group;"
        ::"l"(map), "r"(src), "r"(ch), "r"(pix) : "memory");
}
template <int N>
__device__ __forceinline__ void stores_read_wait() {
    asm volatile("cp.async.bulk.wait_group.read %0;" ::"n"(N) : "memory");
}
__device__ __forceinline__ void prefetch_map_1(const CUtensorMap* map) {
    asm volatile(ELECT "prefetch.tensormap [%0];\n}" ::"l"(map) : "memory");
}
__device__ __forceinline__ void prefetch_l2(const void* p) {
    asm volatile("prefetch.global.L2 [%0];" ::"l"(p) : "memory");
}
__device__ __forceinline__ uint32_t timer_ns() {
    uint32_t t;
    asm volatile("mov.u32 %0, %%globaltimer_lo;" : "=r"(t)::"memory");
    return t;
}
__device__ __forceinline__ bool reached(uint32_t now, uint32_t t) {
    return (int32_t)(now - t) >= 0;
}
__device__ __forceinline__ void cluster_arrive() {
    asm volatile("barrier.cluster.arrive.relaxed.aligned;" ::: "memory");
}
__device__ __forceinline__ void cluster_wait() {
    asm volatile("barrier.cluster.wait.aligned;" ::: "memory");
}
__device__ __forceinline__ void publish_barriers() {
    asm volatile("fence.mbarrier_init.release.cluster;" ::: "memory");
    asm volatile("fence.proxy.async.shared::cta;" ::: "memory");
}

__device__ __forceinline__ void wgmma_rs_n64(float (&d)[32], const uint32_t* a, uint64_t desc, int scale_d) {
    asm volatile(
        "{\n.reg .pred p;\n"
        "setp.ne.b32 p, %37, 0;\n"
        "wgmma.mma_async.sync.aligned.m64n64k16.f32.bf16.bf16 "
        "{%0, %1, %2, %3, %4, %5, %6, %7, %8, %9, %10, %11, %12, %13, %14, %15, "
        "%16, %17, %18, %19, %20, %21, %22, %23, %24, %25, %26, %27, %28, %29, %30, %31}, "
        "{%32, %33, %34, %35}, %36, p, 1, 1, 0;\n}"
        : "+f"(d[0]), "+f"(d[1]), "+f"(d[2]), "+f"(d[3]), "+f"(d[4]), "+f"(d[5]), "+f"(d[6]), "+f"(d[7]),
          "+f"(d[8]), "+f"(d[9]), "+f"(d[10]), "+f"(d[11]), "+f"(d[12]), "+f"(d[13]), "+f"(d[14]), "+f"(d[15]),
          "+f"(d[16]), "+f"(d[17]), "+f"(d[18]), "+f"(d[19]), "+f"(d[20]), "+f"(d[21]), "+f"(d[22]), "+f"(d[23]),
          "+f"(d[24]), "+f"(d[25]), "+f"(d[26]), "+f"(d[27]), "+f"(d[28]), "+f"(d[29]), "+f"(d[30]), "+f"(d[31])
        : "r"(a[0]), "r"(a[1]), "r"(a[2]), "r"(a[3]), "l"(desc), "r"(scale_d));
}

__device__ __forceinline__ uint32_t pack_bias(float lo, float hi, uint32_t bias2) {
    uint32_t r;
    asm("{\n.reg .b32 t;\n"
        "cvt.rn.bf16x2.f32 t, %2, %1;\n"
        "add.rn.bf16x2 %0, t, %3;\n}"
        : "=r"(r) : "f"(lo), "f"(hi), "r"(bias2));
    return r;
}

__device__ __forceinline__ int slice_channel(uint32_t rank, int wg) {
    return (wg * 2 + rank) * 64;
}
__device__ __forceinline__ uint32_t w_stage(int wg) {
    return (wg + 1) * STAGE_BYTES + (wg == 2 ? HALF_BYTES : 0);
}

struct Ring {
    uint32_t s, parity;
    __device__ __forceinline__ void advance() {
        if (++s == STAGES) {
            s = 0;
            parity ^= 1;
        }
    }
};

__device__ __forceinline__ void write_out(uint32_t wg_bars, uint32_t st_addr, const Ring& r, const uint32_t (&v)[16]) {
    mbar_wait(wg_bars + BAR_OFREE + r.s * 32, r.parity ^ 1);
    const uint32_t dst = st_addr + r.s * HALF_BYTES;
#pragma unroll
    for (int j = 0; j < 4; j++) {
        asm volatile("stmatrix.sync.aligned.m8n8.x4.trans.shared.b16 [%0], {%1, %2, %3, %4};"
                     ::"r"(dst + j * 2048), "r"(v[4 * j]), "r"(v[4 * j + 1]), "r"(v[4 * j + 2]), "r"(v[4 * j + 3]) : "memory");
    }
    asm volatile("fence.proxy.async.shared::cta;" ::: "memory");
    __syncwarp();
    mbar_arrive_1(wg_bars + BAR_OFULL + r.s * 32);
}

template <int N>
__device__ __forceinline__ void hand_back(uint32_t& open) {
    if (open != 0) {
        stores_read_wait<N>();
        mbar_arrive_1(open);
        open = 0;
    }
}

__global__ void __cluster_dims__(2, 1, 1) __launch_bounds__(THREADS, 1)
conv1x1_kernel(const uint8_t* __restrict__ x_raw,
               const uint8_t* __restrict__ w_raw,
               const uint16_t* __restrict__ bias,
               uint32_t num_tiles,
               uint32_t num_clusters,
               const __grid_constant__ Maps maps,
               const __grid_constant__ Tune tune) {
    const uint32_t t_entry = timer_ns();
    extern __shared__ uint8_t smem_raw[];
    const uint32_t smem = (smem_u32(smem_raw) + 1023u) & ~1023u;
    const uint32_t bars = smem + SMEM_BAR;

    if (threadIdx.x < PRE_W) {
        prefetch_l2(w_raw + (blockIdx.x % (W_LINES / PRE_W) * PRE_W + threadIdx.x) * 128);
    } else if (threadIdx.x >= 96 && threadIdx.x < 128) {
        prefetch_map_1(&maps.w);
        prefetch_map_1(&maps.x);
    }
    if (threadIdx.x < NUM_WG * 128) cluster_arrive();
    if (threadIdx.x >= 128 && threadIdx.x < 128 + PIECE_BYTES / 128) {
        const uint8_t* p = x_raw + (size_t)blockIdx.x * HALF_BYTES + (threadIdx.x - 128) * 128;
        const uint32_t wait = ((threadIdx.x - 128) >> 5) * PRE_DT;
        const uint32_t c0 = (uint32_t)clock();
        while ((uint32_t)clock() - c0 < wait) {}
        asm volatile("cp.async.ca.shared.global.L2::128B [%0], [%1], 4;" ::"r"(bars + SINK_AT + (threadIdx.x & 31) * 4), "l"(p) : "memory");
    }
    if (threadIdx.x == 0) TRV(0, 63, t_entry);

    const int warp = uniform(threadIdx.x >> 5);
    const int lane = threadIdx.x & 31;
    const uint32_t rank    = blockIdx.x & 1;
    const uint32_t cluster = blockIdx.x >> 1;

    if (warp < NUM_WG * 4) {
        asm volatile("setmaxnreg.inc.sync.aligned.u32 160;");
        const int wg = warp >> 2;
        const int wq = warp & 3;
        const uint32_t bias_lo = bias[slice_channel(rank, wg) + wq * 16 + (lane >> 2)] * 0x10001u;
        const uint32_t bias_hi = bias[slice_channel(rank, wg) + wq * 16 + (lane >> 2) + 8] * 0x10001u;

        cluster_wait();
        TRE(1 + wg, 63);
        mbar_wait(bars + BAR_W + 8 * wg, 0);
        TRE(4 + wg, 63);
        uint32_t wreg[96];
        {
            const int r = lane & 7, m = lane >> 3;
            const uint32_t base = smem + w_stage(wg) + ((m >> 1) * 8 + r) * 128 + (((2 * wq + (m & 1)) ^ r) << 4);
#pragma unroll
            for (int ks = 0; ks < 24; ks++) {
                asm volatile("ldmatrix.sync.aligned.m8n8.x4.trans.shared.b16 {%0, %1, %2, %3}, [%4];"
                             : "=r"(wreg[ks * 4 + 0]), "=r"(wreg[ks * 4 + 1]), "=r"(wreg[ks * 4 + 2]), "=r"(wreg[ks * 4 + 3])
                             : "r"(base + ks * 2048) : "memory");
            }
        }
        uint32_t dep = 0;
#pragma unroll
        for (int ks = 0; ks < 24; ks++) dep ^= wreg[ks * 4];
        dep = uniform(dep & (num_tiles >> 31));
        if (lane < 6 && wg < 2) mbar_arrive_cta(bars + BAR_EMPTY + 8 * (wg + 1) + dep, lane & 1);
        asm volatile("cp.async.wait_all;" ::: "memory");
        TRE(1 + wg, 60);

        const uint32_t wg_bars = bars + wg * 8;
        const uint32_t st_addr = smem + SMEM_OUT + wg * SLICE_BYTES + ((lane >> 4) * 8 + (lane & 7)) * 128 +
                                 (((2 * wq + ((lane >> 3) & 1)) ^ (lane & 7)) << 4);
        const uint64_t desc_base =
            (uint64_t)((smem & 0x3FFFF) >> 4) | ((uint64_t)1 << 16) | ((uint64_t)(6144 >> 4) << 32) | ((uint64_t)1 << 62);
        const int next_turn = 4 + (wg + 1) % NUM_WG;

        float acc[32];
        uint32_t packed[16];
        Ring r = {0, dep}, o = r;
        bool held = false;
        for (uint32_t i = 0, id = cluster; id < num_tiles; i++, id += num_clusters, r.advance()) {
            mbar_wait(bars + BAR_FULL + 8 * r.s, r.parity);
            if ((i | wg) != 0) asm volatile("bar.sync %0, 256;" ::"r"(4 + wg) : "memory");
            TRE(1 + wg * 2, i);
            const uint64_t desc = desc_base + (uint64_t)(r.s * (STAGE_BYTES >> 4));
            asm volatile("wgmma.fence.sync.aligned;" ::: "memory");
#pragma unroll
            for (int ks = 0; ks < 24; ks++) {
                wgmma_rs_n64(acc, &wreg[ks * 4], desc + (uint64_t)((ks >> 2) * 64 + (ks & 3) * 2), ks != 0);
                if (ks + 1 == HAND_AT) asm volatile("bar.arrive %0, 256;" ::"r"(next_turn) : "memory");
            }
            asm volatile("wgmma.commit_group.sync.aligned;" ::: "memory");
            asm volatile("wgmma.wait_group.sync.aligned 0;" ::: "memory");
#pragma unroll
            for (int j = 0; j < 32; j++) asm volatile("" : "+f"(acc[j])::"memory");
            TRE(2 + wg * 2, i);
            if (lane < 2) mbar_arrive_cta(bars + BAR_EMPTY + 8 * r.s, lane);

            if (held) write_out(wg_bars, st_addr, o, packed);
            o = r;
#pragma unroll
            for (int j = 0; j < 16; j++) packed[j] = pack_bias(acc[2 * j], acc[2 * j + 1], j & 1 ? bias_hi : bias_lo);
            held = !mbar_test(wg_bars + BAR_OFREE + o.s * 32, o.parity ^ 1);
            if (!held) write_out(wg_bars, st_addr, o, packed);
            TRE(8 + wg, i);
        }
        if (held) write_out(wg_bars, st_addr, o, packed);
        if (wg == 0) asm volatile("bar.sync 4, 256;" ::: "memory");
        TRE(1 + wg, 62);
    } else {
        asm volatile("setmaxnreg.dec.sync.aligned.u32 32;");
        if (warp == NUM_WG * 4) {
#pragma unroll
            for (int j = 0; j < NUM_WG; j++) mbar_init_1(bars + BAR_W + 8 * j, 1);
            publish_barriers();
            cluster_arrive();
#pragma unroll
            for (int j = 0; j < NUM_WG; j++) {
                mbar_expect_tx_1(bars + BAR_W + 8 * j, STAGE_BYTES);
                tma_load_w_1(smem + w_stage(j), &maps.w, bars + BAR_W + 8 * j, slice_channel(rank, j));
                if (j == 0) TR(2, 61);
            }
            cluster_wait();
            TR(0, 0);
            mbar_expect_tx_1(bars + BAR_FULL, STAGE_BYTES);
            tma_load_x_1(smem + rank * HALF_BYTES, &maps.x, bars + BAR_FULL, cluster * 8 + rank * 4);
            Ring r = {1, 0};
#pragma unroll 1
            for (uint32_t i = 1, id = cluster + num_clusters; id < num_tiles; i++, id += num_clusters, r.advance()) {
                mbar_wait(bars + BAR_EMPTY + 8 * r.s, r.parity ^ (r.s == 0));
                sts32(bars + ISSUED_AT, id);
                sts32(bars + STAMP_AT + 4 * r.s, timer_ns());
                TR(0, i);
                TRV(15, i, id);
                const uint32_t full = bars + BAR_FULL + 8 * r.s;
                const uint32_t dst = smem + r.s * STAGE_BYTES + rank * HALF_BYTES;
                mbar_expect_tx_1(full, STAGE_BYTES);
                if (id + tune.EF_TAIL < num_tiles) tma_load_x_1(dst, &maps.x, full, id * 8 + rank * 4);
                else tma_load_x_evict_first_1(dst, &maps.x, full, id * 8 + rank * 4);
            }
#pragma unroll 1
            for (int k = 0; k < STAGES; k++, r.advance()) mbar_wait(bars + BAR_EMPTY + 8 * r.s, r.parity ^ (r.s == 0));
        } else if (warp == NUM_WG * 4 + 1) {
#pragma unroll
            for (int s = 0; s < STAGES; s++) {
                mbar_init_1(bars + BAR_FULL + 8 * s, 1);
                mbar_init_1(bars + BAR_EMPTY + 8 * s, NUM_WG * 4 * 2);
            }
            publish_barriers();
            cluster_arrive();
            TR(0, 61);
            cluster_wait();
            prefetch_map_1(&maps.out);
            uint32_t delay = 0;
            Ring r = {0, 0};
#pragma unroll 1
            for (uint32_t i = 0, id = cluster; id < num_tiles; i++, id += num_clusters, r.advance()) {
                mbar_wait(bars + BAR_FULL + 8 * r.s, r.parity);
                TR(7, i);
                const int late = (int)(timer_ns() - lds32(bars + STAMP_AT + 4 * r.s) - tune.CC_L0);
                if (i >= tune.CC_AT && late > 0) {
                    delay = min(delay + min((uint32_t)late * tune.CC_G >> 4, tune.CC_STEP), tune.CC_CAP);
                    sts32(bars + DELAY_AT, delay);
                }
            }
        } else if (warp == NUM_WG * 4 + 2) {
            sts32(bars + DELAY_AT, 0);
#pragma unroll
            for (int b = 0; b < STAGES; b++) {
#pragma unroll
                for (int w = 0; w < NUM_WG; w++) {
                    mbar_init_1(bars + BAR_OFREE + b * 32 + w * 8, 1);
                    mbar_init_1(bars + BAR_OFULL + b * 32 + w * 8, 4);
                }
            }
            publish_barriers();
            cluster_arrive();
            cluster_wait();
            const uint32_t first = tune.ST_AT * num_clusters;
            const uint32_t n3 = max((int)(num_tiles - first - tune.ST_N1 - tune.ST_N2 - tune.ST_END), 0);
            uint32_t open = 0;
            Ring o = {0, 0};
#pragma unroll 1
            for (uint32_t j = 0, id = cluster; id < num_tiles; j++, id += num_clusters, o.advance()) {
                const uint32_t obar = bars + o.s * 32;
                if (!mbar_test(obar + BAR_OFULL, o.parity)) {
                    hand_back<0>(open);
                    mbar_wait(obar + BAR_OFULL, o.parity);
                }
                if (id >= first) {
                    uint32_t rest = id - first, t = 0;
                    auto segment = [&](uint32_t ids, uint32_t per_round) {
                        const uint32_t n = min(rest, ids);
                        t += n * per_round;
                        rest -= n;
                    };
                    segment(tune.ST_N1, tune.ST_S1);
                    segment(tune.ST_N2, tune.ST_S2);
                    segment(n3, tune.ST_S3);
                    segment(tune.ST_N4, tune.ST_S4);
                    segment(tune.ST_N5, tune.ST_S5);
                    const uint32_t due = t_entry + tune.ST_T0 + (t + rest * tune.ST_S6) / num_clusters;
#pragma unroll 1
                    for (uint32_t spins = 0; spins < SPIN_LIMIT; spins++) {
                        const uint32_t delay = uniform(lds32(bars + DELAY_AT));
                        if (reached(timer_ns(), due + delay)) break;
                        hand_back<0>(open);
                        __nanosleep(20);
                    }
                }
                const uint32_t src = smem + SMEM_OUT + o.s * HALF_BYTES;
                if (mbar_test(obar + BAR_OFULL + 8, o.parity) && mbar_test(obar + BAR_OFULL + 16, o.parity)) {
                    TR(11, j);
#pragma unroll
                    for (int w = 0; w < NUM_WG; w++) tma_store_1(&maps.out, src + w * SLICE_BYTES, slice_channel(rank, w), id * TILE_PIX);
                    hand_back<3>(open);
                    stores_read_wait<2>();
                    TR(12, j);
                    mbar_arrive_1(obar + BAR_OFREE);
                    stores_read_wait<1>();
                    TR(13, j);
                    mbar_arrive_1(obar + BAR_OFREE + 8);
                    open = obar + BAR_OFREE + 16;
                } else {
#pragma unroll 1
                    for (uint32_t w = 0; w < NUM_WG; w++) {
                        if (!mbar_test(obar + BAR_OFULL + w * 8, o.parity)) {
                            hand_back<0>(open);
                            mbar_wait(obar + BAR_OFULL + w * 8, o.parity);
                        }
                        TR(11 + w, j);
                        tma_store_1(&maps.out, src + w * SLICE_BYTES, slice_channel(rank, w), id * TILE_PIX);
                        hand_back<1>(open);
                        open = obar + BAR_OFREE + w * 8;
                    }
                }
            }
            stores_read_wait<0>();
            TR(4, 62);
            TRV(6, 62, lds32(bars + DELAY_AT));
        } else {
            sts32(bars + ISSUED_AT, 0);
            cluster_arrive();
            uint32_t due = t_entry + tune.PM_T0 + (blockIdx.x & 3) * tune.PM_STAG;
            const uint32_t step = num_clusters / 2;
#pragma unroll 1
            for (uint32_t piece = 1;; piece++) {
                const uint32_t t = cluster + piece / 2 * num_clusters;
                if (t >= num_tiles) break;
                const bool last = t + tune.LEAD_T >= num_tiles;
                uint32_t now;
#pragma unroll 1
                for (uint32_t spins = 0; spins < 16384; spins++) {
                    const uint32_t issued = uniform(lds32(bars + ISSUED_AT));
                    now = timer_ns();
                    const int lead = max((int)(last ? tune.LEAD_C : tune.LEAD_B), (int)tune.LEAD_A - (max((int)issued - (int)tune.LEAD_F, 0) * (int)tune.LEAD_S >> 4));
                    if (reached(now, due)) {
                        if (cluster + piece * step <= issued + lead) break;
                        due = now;
                    }
                    __nanosleep(20);
                }
                if (reached(now - tune.PM_SLACK, due)) due = now - tune.PM_SLACK;
                due += piece < tune.PM_E1 ? tune.PM_DT1 : piece < tune.PM_E2 ? tune.PM_DT2 : last ? tune.PM_DT4 : tune.PM_DT3;
                const uint8_t* p = x_raw + (size_t)t * STAGE_BYTES + rank * HALF_BYTES + (piece % 2) * PIECE_BYTES + lane * 128;
#pragma unroll
                for (int k = 0; k < PIECE_BYTES / 4096; k++) prefetch_l2(p + k * 4096);
                if (piece % 2 == 0) TR(14, piece / 2);
            }
            cluster_wait();
        }
    }
}

typedef CUresult (*EncodeTiledFn)(CUtensorMap*, CUtensorMapDataType, cuuint32_t, void*, const cuuint64_t*,
                                  const cuuint64_t*, const cuuint32_t*, const cuuint32_t*, CUtensorMapInterleave,
                                  CUtensorMapSwizzle, CUtensorMapL2promotion, CUtensorMapFloatOOBfill);

}

extern "C" void kernel_launch(void* const* d_in, const int* in_sizes, int n_in, void* d_out, int out_size) {
    (void)n_in;
    (void)out_size;
    void* x = d_in[0];
    void* w = d_in[1];
    const uint16_t* b = (const uint16_t*)d_in[2];
    const int M = in_sizes[0] / C;
    const int num_tiles = M / TILE_PIX;

    static EncodeTiledFn encode = nullptr;
    static int sms = 0;
    if (!encode) {
        void* fn = nullptr;
        cudaDriverEntryPointQueryResult q;
        cudaGetDriverEntryPoint("cuTensorMapEncodeTiled", &fn, cudaEnableDefault, &q);
        encode = (EncodeTiledFn)fn;
        cudaDeviceGetAttribute(&sms, cudaDevAttrMultiProcessorCount, 0);
        cudaFuncSetAttribute(conv1x1_kernel, cudaFuncAttributeMaxDynamicSharedMemorySize, SMEM_TOTAL);
    }

    Maps maps;
    const cuuint32_t ones[4] = {1, 1, 1, 1};
    auto make = [&](CUtensorMap* map, int rank, void* base, const cuuint64_t* dims, const cuuint64_t* strides,
                    const cuuint32_t* box, CUtensorMapL2promotion promo) {
        encode(map, CU_TENSOR_MAP_DATA_TYPE_BFLOAT16, rank, base, dims, strides, box, ones, CU_TENSOR_MAP_INTERLEAVE_NONE,
               CU_TENSOR_MAP_SWIZZLE_128B, promo, CU_TENSOR_MAP_FLOAT_OOB_FILL_NONE);
    };
    {
        const cuuint64_t dims[4]    = {64, 8, 6, (cuuint64_t)(M / 8)};
        const cuuint64_t strides[3] = {C * 2, 128, 8 * C * 2};
        const cuuint32_t box[4]     = {64, 8, 6, TILE_PIX / 16};
        make(&maps.x, 4, x, dims, strides, box, CU_TENSOR_MAP_L2_PROMOTION_L2_128B);
    }
    {
        const cuuint64_t dims[3]    = {C, C / 2, 2};
        const cuuint64_t strides[2] = {C * 2, C * C};
        const cuuint32_t box[3]     = {64, C / 2, 2};
        make(&maps.w, 3, w, dims, strides, box, CU_TENSOR_MAP_L2_PROMOTION_L2_128B);
    }
    {
        const cuuint64_t dims[2]    = {C, (cuuint64_t)M};
        const cuuint64_t strides[1] = {C * 2};
        const cuuint32_t box[2]     = {64, TILE_PIX};
        make(&maps.out, 2, d_out, dims, strides, box, CU_TENSOR_MAP_L2_PROMOTION_NONE);
    }

    const Tune tune;
    int clusters = sms / 2;
    if (clusters > num_tiles) clusters = num_tiles;
    conv1x1_kernel<<<clusters * 2, THREADS, SMEM_TOTAL>>>((const uint8_t*)x, (const uint8_t*)w, b, (uint32_t)num_tiles,
                                                          (uint32_t)clusters, maps, tune);
}
```

```cpp
#include <cuda_runtime.h>
#include <cuda_bf16.h>
#include <cuda.h>
#include <stdint.h>

#define TUNABLES(F) \
    F(PM_T0, 350)        \
    F(PM_STAG, 30)      \
    F(PM_DT1, 415)       \
    F(PM_E1, 7) \
    F(PM_DT2, 475) \
    F(PM_E2, 23) \
    F(PM_DT3, 860) \
    F(PM_SLACK, 500)     \
    F(LEAD_A, 269)       \
    F(LEAD_F, 550)       \
    F(LEAD_S, 3)         \
    F(LEAD_B, 151)       \
    F(LEAD_T, 264)         \
    F(LEAD_C, 170)       \
    F(PM_DT4, 700)       \
    F(EF_TAIL, 500)      \
    F(ST_AT, 2)          \
    F(ST_T0, 6770)       \
    F(ST_S1, 2040)       \
    F(ST_N1, 448) \
    F(ST_S2, 1860) \
    F(ST_N2, 594) \
    F(ST_S3, 1970)       \
    F(ST_END, 613) \
    F(ST_S4, 1500)       \
    F(ST_N4, 100) \
    F(ST_S5, 1100) \
    F(ST_N5, 100) \
    F(ST_S6, 962) \
    F(ST_N7, 22)          \
    F(ST_S7, 0) \
    F(CC_AT, 22)         \
    F(CC_L0, 1300)       \
    F(CC_G, 14)          \
    F(CC_STEP, 1100)      \
    F(CC_CAP, 1350)

struct Tune {
#define F(n, v) uint32_t n = v;
    TUNABLES(F)
#undef F
};

#define TRV(slot, idx, v)
#define TR(slot, idx)
#define TRE(slot, idx)
#define TRACE_BYTES 0

namespace {

constexpr int C            = 384;
constexpr int TILE_PIX     = 64;
constexpr int STAGES       = 3;
constexpr int STAGE_BYTES  = TILE_PIX * C * 2;
constexpr int HALF_BYTES   = STAGE_BYTES / 2;
constexpr int PIECE_BYTES  = HALF_BYTES / 2;
constexpr int SLICE_BYTES  = TILE_PIX * 128;
constexpr int NUM_WG       = 3;
constexpr int THREADS      = (NUM_WG + 1) * 128;
constexpr int SMEM_OUT     = STAGES * STAGE_BYTES;
constexpr int SMEM_BAR     = SMEM_OUT + STAGES * HALF_BYTES;
constexpr int SMEM_TOTAL   = SMEM_BAR + 512 + TRACE_BYTES + 1024;
constexpr int HAND_AT      = 18;
constexpr int W_LINES      = C * C * 2 / 128;
constexpr int PRE_W        = 64;
constexpr int PRE_DT       = 330;
constexpr uint32_t SPIN_LIMIT = 1u << 22;
constexpr int BAR_W     = 0;
constexpr int BAR_FULL  = 32;
constexpr int BAR_EMPTY = 64;
constexpr int BAR_OFREE = 96;
constexpr int BAR_OFULL = BAR_OFREE + 32 * STAGES;
constexpr int ISSUED_AT = BAR_OFULL + 32 * STAGES;
constexpr int DELAY_AT  = ISSUED_AT + 4;
constexpr int STAMP_AT  = DELAY_AT + 4;
constexpr int SINK_AT   = 384;

struct Maps {
    CUtensorMap w, x, out;
};

#define ELECT "{\n.reg .pred e;\nelect.sync _|e, 0xffffffff;\n@e "

__device__ __forceinline__ uint32_t smem_u32(const void* p) {
    return (uint32_t)__cvta_generic_to_shared(p);
}
__device__ __forceinline__ void mbar_init_1(uint32_t bar, uint32_t count) {
    asm volatile(ELECT "mbarrier.init.shared::cta.b64 [%0], %1;\n}" ::"r"(bar), "r"(count) : "memory");
}
__device__ __forceinline__ void mbar_expect_tx_1(uint32_t bar, uint32_t bytes) {
    asm volatile(ELECT "mbarrier.arrive.expect_tx.shared::cta.b64 _, [%0], %1;\n}" ::"r"(bar), "r"(bytes) : "memory");
}
__device__ __forceinline__ void mbar_arrive_1(uint32_t bar) {
    asm volatile(ELECT "mbarrier.arrive.shared::cta.b64 _, [%0];\n}" ::"r"(bar) : "memory");
}
__device__ __forceinline__ void mbar_wait(uint32_t bar, uint32_t parity) {
    uint32_t done;
    uint32_t spins = 0;
    do {
        asm volatile(
            "{\n.reg .pred p;\n"
            "mbarrier.try_wait.parity.shared::cta.b64 p, [%1], %2;\n"
            "selp.u32 %0, 1, 0, p;\n}"
            : "=r"(done) : "r"(bar), "r"(parity) : "memory");
    } while (!done && ++spins < SPIN_LIMIT);
    __syncwarp();
}
__device__ __forceinline__ bool mbar_test(uint32_t bar, uint32_t parity) {
    uint32_t done;
    asm volatile(
        "{\n.reg .pred p;\n"
        "mbarrier.test_wait.parity.shared::cta.b64 p, [%1], %2;\n"
        "selp.u32 %0, 1, 0, p;\n}"
        : "=r"(done) : "r"(bar), "r"(parity) : "memory");
    return __all_sync(0xffffffffu, done);
}
__device__ __forceinline__ void mbar_arrive_cta(uint32_t bar, uint32_t cta) {
    asm volatile(
        "{\n.reg .b32 ra;\n"
        "mapa.shared::cluster.u32 ra, %0, %1;\n"
        "mbarrier.arrive.shared::cluster.b64 _, [ra];\n}"
        ::"r"(bar), "r"(cta) : "memory");
}
__device__ __forceinline__ uint32_t lds32(uint32_t addr) {
    uint32_t v;
    asm volatile("ld.volatile.shared.b32 %0, [%1];" : "=r"(v) : "r"(addr) : "memory");
    return v;
}
__device__ __forceinline__ void sts32(uint32_t addr, uint32_t v) {
    asm volatile("st.volatile.shared.b32 [%0], %1;" ::"r"(addr), "r"(v) : "memory");
}
__device__ __forceinline__ uint32_t uniform(uint32_t v) {
    return __shfl_sync(0xffffffffu, v, 0);
}
__device__ __forceinline__ void tma_load_w_1(uint32_t dst, const CUtensorMap* map, uint32_t bar, int n) {
    asm volatile(
        ELECT "cp.async.bulk.tensor.3d.shared::cluster.global.mbarrier::complete_tx::bytes [%0], [%1, {%3, %4, %4}], [%2];\n}"
        ::"r"(dst), "l"(map), "r"(bar), "r"(n), "r"(0) : "memory");
}
__device__ __forceinline__ void tma_load_x_1(uint32_t dst, const CUtensorMap* map, uint32_t bar, int group) {
    asm volatile(
        ELECT "cp.async.bulk.tensor.4d.shared::cluster.global.mbarrier::complete_tx::bytes.multicast::cluster"
        " [%0], [%1, {%3, %3, %3, %4}], [%2], %5;\n}"
        ::"r"(dst), "l"(map), "r"(bar), "r"(0), "r"(group), "h"((uint16_t)3) : "memory");
}
__device__ __forceinline__ void tma_load_x_evict_first_1(uint32_t dst, const CUtensorMap* map, uint32_t bar, int group) {
    asm volatile(
        "{\n.reg .b64 pol;\n"
        "createpolicy.fractional.L2::evict_first.b64 pol, 1.0;\n"
        ELECT "cp.async.bulk.tensor.4d.shared::cluster.global.mbarrier::complete_tx::bytes.multicast::cluster.L2::cache_hint"
        " [%0], [%1, {%3, %3, %3, %4}], [%2], %5, pol;\n}\n}"
        ::"r"(dst), "l"(map), "r"(bar), "r"(0), "r"(group), "h"((uint16_t)3) : "memory");
}
__device__ __forceinline__ void tma_store_1(const CUtensorMap* map, uint32_t src, int ch, int pix) {
    asm volatile(
        ELECT "cp.async.bulk.tensor.2d.global.shared::cta.bulk_group [%0, {%2, %3}], [%1];\n}\n"
        "cp.async.bulk.commit_group;"
        ::"l"(map), "r"(src), "r"(ch), "r"(pix) : "memory");
}
template <int N>
__device__ __forceinline__ void stores_read_wait() {
    asm volatile("cp.async.bulk.wait_group.read %0;" ::"n"(N) : "memory");
}
__device__ __forceinline__ void prefetch_map_1(const CUtensorMap* map) {
    asm volatile(ELECT "prefetch.tensormap [%0];\n}" ::"l"(map) : "memory");
}
__device__ __forceinline__ void prefetch_l2(const void* p) {
    asm volatile("prefetch.global.L2 [%0];" ::"l"(p) : "memory");
}
__device__ __forceinline__ uint32_t timer_ns() {
    uint32_t t;
    asm volatile("mov.u32 %0, %%globaltimer_lo;" : "=r"(t)::"memory");
    return t;
}
__device__ __forceinline__ bool reached(uint32_t now, uint32_t t) {
    return (int32_t)(now - t) >= 0;
}
__device__ __forceinline__ void cluster_arrive() {
    asm volatile("barrier.cluster.arrive.relaxed.aligned;" ::: "memory");
}
__device__ __forceinline__ void cluster_wait() {
    asm volatile("barrier.cluster.wait.aligned;" ::: "memory");
}
__device__ __forceinline__ void publish_barriers() {
    asm volatile("fence.mbarrier_init.release.cluster;" ::: "memory");
    asm volatile("fence.proxy.async.shared::cta;" ::: "memory");
}

__device__ __forceinline__ void wgmma_rs_n64(float (&d)[32], const uint32_t* a, uint64_t desc, int scale_d) {
    asm volatile(
        "{\n.reg .pred p;\n"
        "setp.ne.b32 p, %37, 0;\n"
        "wgmma.mma_async.sync.aligned.m64n64k16.f32.bf16.bf16 "
        "{%0, %1, %2, %3, %4, %5, %6, %7, %8, %9, %10, %11, %12, %13, %14, %15, "
        "%16, %17, %18, %19, %20, %21, %22, %23, %24, %25, %26, %27, %28, %29, %30, %31}, "
        "{%32, %33, %34, %35}, %36, p, 1, 1, 0;\n}"
        : "+f"(d[0]), "+f"(d[1]), "+f"(d[2]), "+f"(d[3]), "+f"(d[4]), "+f"(d[5]), "+f"(d[6]), "+f"(d[7]),
          "+f"(d[8]), "+f"(d[9]), "+f"(d[10]), "+f"(d[11]), "+f"(d[12]), "+f"(d[13]), "+f"(d[14]), "+f"(d[15]),
          "+f"(d[16]), "+f"(d[17]), "+f"(d[18]), "+f"(d[19]), "+f"(d[20]), "+f"(d[21]), "+f"(d[22]), "+f"(d[23]),
          "+f"(d[24]), "+f"(d[25]), "+f"(d[26]), "+f"(d[27]), "+f"(d[28]), "+f"(d[29]), "+f"(d[30]), "+f"(d[31])
        : "r"(a[0]), "r"(a[1]), "r"(a[2]), "r"(a[3]), "l"(desc), "r"(scale_d));
}

__device__ __forceinline__ uint32_t pack_bias(float lo, float hi, uint32_t bias2) {
    uint32_t r;
    asm("{\n.reg .b32 t;\n"
        "cvt.rn.bf16x2.f32 t, %2, %1;\n"
        "add.rn.bf16x2 %0, t, %3;\n}"
        : "=r"(r) : "f"(lo), "f"(hi), "r"(bias2));
    return r;
}

__device__ __forceinline__ int slice_channel(uint32_t rank, int wg) {
    return (wg * 2 + rank) * 64;
}
__device__ __forceinline__ uint32_t w_stage(int wg) {
    return (wg + 1) * STAGE_BYTES + (wg == 2 ? HALF_BYTES : 0);
}

struct Ring {
    uint32_t s, parity;
    __device__ __forceinline__ void advance() {
        if (++s == STAGES) {
            s = 0;
            parity ^= 1;
        }
    }
};

__device__ __forceinline__ void write_out(uint32_t wg_bars, uint32_t st_addr, const Ring& r, const uint32_t (&v)[16]) {
    mbar_wait(wg_bars + BAR_OFREE + r.s * 32, r.parity ^ 1);
    const uint32_t dst = st_addr + r.s * HALF_BYTES;
#pragma unroll
    for (int j = 0; j < 4; j++) {
        asm volatile("stmatrix.sync.aligned.m8n8.x4.trans.shared.b16 [%0], {%1, %2, %3, %4};"
                     ::"r"(dst + j * 2048), "r"(v[4 * j]), "r"(v[4 * j + 1]), "r"(v[4 * j + 2]), "r"(v[4 * j + 3]) : "memory");
    }
    asm volatile("fence.proxy.async.shared::cta;" ::: "memory");
    __syncwarp();
    mbar_arrive_1(wg_bars + BAR_OFULL + r.s * 32);
}

template <int N>
__device__ __forceinline__ void hand_back(uint32_t& open) {
    if (open != 0) {
        stores_read_wait<N>();
        mbar_arrive_1(open);
        open = 0;
    }
}

__global__ void __cluster_dims__(2, 1, 1) __launch_bounds__(THREADS, 1)
conv1x1_kernel(const uint8_t* __restrict__ x_raw,
               const uint8_t* __restrict__ w_raw,
               const uint16_t* __restrict__ bias,
               uint32_t num_tiles,
               uint32_t num_clusters,
               const __grid_constant__ Maps maps,
               const __grid_constant__ Tune tune) {
    const uint32_t t_entry = timer_ns();
    extern __shared__ uint8_t smem_raw[];
    const uint32_t smem = (smem_u32(smem_raw) + 1023u) & ~1023u;
    const uint32_t bars = smem + SMEM_BAR;

    if (threadIdx.x < PRE_W) {
        prefetch_l2(w_raw + (blockIdx.x % (W_LINES / PRE_W) * PRE_W + threadIdx.x) * 128);
    } else if (threadIdx.x >= 96 && threadIdx.x < 128) {
        prefetch_map_1(&maps.w);
        prefetch_map_1(&maps.x);
    }
    if (threadIdx.x < NUM_WG * 128) cluster_arrive();
    if (threadIdx.x >= 128 && threadIdx.x < 128 + PIECE_BYTES / 128) {
        const uint8_t* p = x_raw + (size_t)blockIdx.x * HALF_BYTES + (threadIdx.x - 128) * 128;
        const uint32_t wait = ((threadIdx.x - 128) >> 5) * PRE_DT;
        const uint32_t c0 = (uint32_t)clock();
        while ((uint32_t)clock() - c0 < wait) {}
        asm volatile("cp.async.ca.shared.global.L2::128B [%0], [%1], 4;" ::"r"(bars + SINK_AT + (threadIdx.x & 31) * 4), "l"(p) : "memory");
    }
    if (threadIdx.x == 0) TRV(0, 63, t_entry);

    const int warp = uniform(threadIdx.x >> 5);
    const int lane = threadIdx.x & 31;
    const uint32_t rank    = blockIdx.x & 1;
    const uint32_t cluster = blockIdx.x >> 1;

    if (warp < NUM_WG * 4) {
        asm volatile("setmaxnreg.inc.sync.aligned.u32 160;");
        const int wg = warp >> 2;
        const int wq = warp & 3;
        const uint32_t bias_lo = bias[slice_channel(rank, wg) + wq * 16 + (lane >> 2)] * 0x10001u;
        const uint32_t bias_hi = bias[slice_channel(rank, wg) + wq * 16 + (lane >> 2) + 8] * 0x10001u;

        cluster_wait();
        TRE(1 + wg, 63);
        mbar_wait(bars + BAR_W + 8 * wg, 0);
        TRE(4 + wg, 63);
        uint32_t wreg[96];
        {
            const int r = lane & 7, m = lane >> 3;
            const uint32_t base = smem + w_stage(wg) + ((m >> 1) * 8 + r) * 128 + (((2 * wq + (m & 1)) ^ r) << 4);
#pragma unroll
            for (int ks = 0; ks < 24; ks++) {
                asm volatile("ldmatrix.sync.aligned.m8n8.x4.trans.shared.b16 {%0, %1, %2, %3}, [%4];"
                             : "=r"(wreg[ks * 4 + 0]), "=r"(wreg[ks * 4 + 1]), "=r"(wreg[ks * 4 + 2]), "=r"(wreg[ks * 4 + 3])
                             : "r"(base + ks * 2048) : "memory");
            }
        }
        uint32_t dep = 0;
#pragma unroll
        for (int ks = 0; ks < 24; ks++) dep ^= wreg[ks * 4];
        dep = uniform(dep & (num_tiles >> 31));
        if (lane < 6 && wg < 2) mbar_arrive_cta(bars + BAR_EMPTY + 8 * (wg + 1) + dep, lane & 1);
        asm volatile("cp.async.wait_all;" ::: "memory");
        TRE(1 + wg, 60);

        const uint32_t wg_bars = bars + wg * 8;
        const uint32_t st_addr = smem + SMEM_OUT + wg * SLICE_BYTES + ((lane >> 4) * 8 + (lane & 7)) * 128 +
                                 (((2 * wq + ((lane >> 3) & 1)) ^ (lane & 7)) << 4);
        const uint64_t desc_base =
            (uint64_t)((smem & 0x3FFFF) >> 4) | ((uint64_t)1 << 16) | ((uint64_t)(6144 >> 4) << 32) | ((uint64_t)1 << 62);
        const int next_turn = 4 + (wg + 1) % NUM_WG;

        float acc[32];
        uint32_t packed[16];
        Ring r = {0, dep}, o = r;
        bool held = false;
        for (uint32_t i = 0, id = cluster; id < num_tiles; i++, id += num_clusters, r.advance()) {
            mbar_wait(bars + BAR_FULL + 8 * r.s, r.parity);
            if ((i | wg) != 0) asm volatile("bar.sync %0, 256;" ::"r"(4 + wg) : "memory");
            TRE(1 + wg * 2, i);
            const uint64_t desc = desc_base + (uint64_t)(r.s * (STAGE_BYTES >> 4));
            asm volatile("wgmma.fence.sync.aligned;" ::: "memory");
#pragma unroll
            for (int ks = 0; ks < 24; ks++) {
                wgmma_rs_n64(acc, &wreg[ks * 4], desc + (uint64_t)((ks >> 2) * 64 + (ks & 3) * 2), ks != 0);
                if (ks + 1 == HAND_AT) asm volatile("bar.arrive %0, 256;" ::"r"(next_turn) : "memory");
            }
            asm volatile("wgmma.commit_group.sync.aligned;" ::: "memory");
            asm volatile("wgmma.wait_group.sync.aligned 0;" ::: "memory");
#pragma unroll
            for (int j = 0; j < 32; j++) asm volatile("" : "+f"(acc[j])::"memory");
            TRE(2 + wg * 2, i);
            if (lane < 2) mbar_arrive_cta(bars + BAR_EMPTY + 8 * r.s, lane);

            if (held) write_out(wg_bars, st_addr, o, packed);
            o = r;
#pragma unroll
            for (int j = 0; j < 16; j++) packed[j] = pack_bias(acc[2 * j], acc[2 * j + 1], j & 1 ? bias_hi : bias_lo);
            held = !mbar_test(wg_bars + BAR_OFREE + o.s * 32, o.parity ^ 1);
            if (!held) write_out(wg_bars, st_addr, o, packed);
            TRE(8 + wg, i);
        }
        if (held) write_out(wg_bars, st_addr, o, packed);
        if (wg == 0) asm volatile("bar.sync 4, 256;" ::: "memory");
        TRE(1 + wg, 62);
    } else {
        asm volatile("setmaxnreg.dec.sync.aligned.u32 32;");
        if (warp == NUM_WG * 4) {
#pragma unroll
            for (int j = 0; j < NUM_WG; j++) mbar_init_1(bars + BAR_W + 8 * j, 1);
            publish_barriers();
            cluster_arrive();
#pragma unroll
            for (int j = 0; j < NUM_WG; j++) {
                mbar_expect_tx_1(bars + BAR_W + 8 * j, STAGE_BYTES);
                tma_load_w_1(smem + w_stage(j), &maps.w, bars + BAR_W + 8 * j, slice_channel(rank, j));
                if (j == 0) TR(2, 61);
            }
            cluster_wait();
            TR(0, 0);
            mbar_expect_tx_1(bars + BAR_FULL, STAGE_BYTES);
            tma_load_x_1(smem + rank * HALF_BYTES, &maps.x, bars + BAR_FULL, cluster * 8 + rank * 4);
            Ring r = {1, 0};
#pragma unroll 1
            for (uint32_t i = 1, id = cluster + num_clusters; id < num_tiles; i++, id += num_clusters, r.advance()) {
                mbar_wait(bars + BAR_EMPTY + 8 * r.s, r.parity ^ (r.s == 0));
                sts32(bars + ISSUED_AT, id);
                sts32(bars + STAMP_AT + 4 * r.s, timer_ns());
                TR(0, i);
                TRV(15, i, id);
                const uint32_t full = bars + BAR_FULL + 8 * r.s;
                const uint32_t dst = smem + r.s * STAGE_BYTES + rank * HALF_BYTES;
                mbar_expect_tx_1(full, STAGE_BYTES);
                if (id + tune.EF_TAIL < num_tiles) tma_load_x_1(dst, &maps.x, full, id * 8 + rank * 4);
                else tma_load_x_evict_first_1(dst, &maps.x, full, id * 8 + rank * 4);
            }
#pragma unroll 1
            for (int k = 0; k < STAGES; k++, r.advance()) mbar_wait(bars + BAR_EMPTY + 8 * r.s, r.parity ^ (r.s == 0));
        } else if (warp == NUM_WG * 4 + 1) {
#pragma unroll
            for (int s = 0; s < STAGES; s++) {
                mbar_init_1(bars + BAR_FULL + 8 * s, 1);
                mbar_init_1(bars + BAR_EMPTY + 8 * s, NUM_WG * 4 * 2);
            }
            publish_barriers();
            cluster_arrive();
            TR(0, 61);
            cluster_wait();
            prefetch_map_1(&maps.out);
            uint32_t delay = 0;
            Ring r = {0, 0};
#pragma unroll 1
            for (uint32_t i = 0, id = cluster; id < num_tiles; i++, id += num_clusters, r.advance()) {
                mbar_wait(bars + BAR_FULL + 8 * r.s, r.parity);
                TR(7, i);
                const int late = (int)(timer_ns() - lds32(bars + STAMP_AT + 4 * r.s) - tune.CC_L0);
                if (i >= tune.CC_AT && late > 0) {
                    delay = min(delay + min((uint32_t)late * tune.CC_G >> 4, tune.CC_STEP), tune.CC_CAP);
                    sts32(bars + DELAY_AT, delay);
                }
            }
        } else if (warp == NUM_WG * 4 + 2) {
            sts32(bars + DELAY_AT, 0);
#pragma unroll
            for (int b = 0; b < STAGES; b++) {
#pragma unroll
                for (int w = 0; w < NUM_WG; w++) {
                    mbar_init_1(bars + BAR_OFREE + b * 32 + w * 8, 1);
                    mbar_init_1(bars + BAR_OFULL + b * 32 + w * 8, 4);
                }
            }
            publish_barriers();
            cluster_arrive();
            cluster_wait();
            const uint32_t first = tune.ST_AT * num_clusters;
            const uint32_t n3 = max((int)(num_tiles - first - tune.ST_N1 - tune.ST_N2 - tune.ST_END), 0);
            uint32_t open = 0;
            Ring o = {0, 0};
#pragma unroll 1
            for (uint32_t j = 0, id = cluster; id < num_tiles; j++, id += num_clusters, o.advance()) {
                const uint32_t obar = bars + o.s * 32;
                if (!mbar_test(obar + BAR_OFULL, o.parity)) {
                    hand_back<0>(open);
                    mbar_wait(obar + BAR_OFULL, o.parity);
                }
                if (id >= first) {
                    uint32_t rest = id - first, t = 0;
                    auto segment = [&](uint32_t ids, uint32_t per_round) {
                        const uint32_t n = min(rest, ids);
                        t += n * per_round;
                        rest -= n;
                    };
                    segment(tune.ST_N1, tune.ST_S1);
                    segment(tune.ST_N2, tune.ST_S2);
                    segment(n3, tune.ST_S3);
                    segment(tune.ST_N4, tune.ST_S4);
                    segment(tune.ST_N5, tune.ST_S5);
                    segment(tune.ST_END - tune.ST_N4 - tune.ST_N5 - tune.ST_N7, tune.ST_S6);
                    const uint32_t due = t_entry + tune.ST_T0 + (t + rest * tune.ST_S7) / num_clusters;
#pragma unroll 1
                    for (uint32_t spins = 0; spins < SPIN_LIMIT; spins++) {
                        const uint32_t delay = uniform(lds32(bars + DELAY_AT));
                        if (reached(timer_ns(), due + delay)) break;
                        hand_back<0>(open);
                        __nanosleep(20);
                    }
                }
                const uint32_t src = smem + SMEM_OUT + o.s * HALF_BYTES;
                if (mbar_test(obar + BAR_OFULL + 8, o.parity) && mbar_test(obar + BAR_OFULL + 16, o.parity)) {
                    TR(11, j);
#pragma unroll
                    for (int w = 0; w < NUM_WG; w++) tma_store_1(&maps.out, src + w * SLICE_BYTES, slice_channel(rank, w), id * TILE_PIX);
                    hand_back<3>(open);
                    stores_read_wait<2>();
                    TR(12, j);
                    mbar_arrive_1(obar + BAR_OFREE);
                    stores_read_wait<1>();
                    TR(13, j);
                    mbar_arrive_1(obar + BAR_OFREE + 8);
                    open = obar + BAR_OFREE + 16;
                } else {
#pragma unroll 1
                    for (uint32_t w = 0; w < NUM_WG; w++) {
                        if (!mbar_test(obar + BAR_OFULL + w * 8, o.parity)) {
                            hand_back<0>(open);
                            mbar_wait(obar + BAR_OFULL + w * 8, o.parity);
                        }
                        TR(11 + w, j);
                        tma_store_1(&maps.out, src + w * SLICE_BYTES, slice_channel(rank, w), id * TILE_PIX);
                        hand_back<1>(open);
                        open = obar + BAR_OFREE + w * 8;
                    }
                }
            }
            stores_read_wait<0>();
            TR(4, 62);
            TRV(6, 62, lds32(bars + DELAY_AT));
        } else {
            sts32(bars + ISSUED_AT, 0);
            cluster_arrive();
            uint32_t due = t_entry + tune.PM_T0 + (blockIdx.x & 3) * tune.PM_STAG;
            const uint32_t step = num_clusters / 2;
#pragma unroll 1
            for (uint32_t piece = 1;; piece++) {
                const uint32_t t = cluster + piece / 2 * num_clusters;
                if (t >= num_tiles) break;
                const bool last = t + tune.LEAD_T >= num_tiles;
                uint32_t now;
#pragma unroll 1
                for (uint32_t spins = 0; spins < 16384; spins++) {
                    const uint32_t issued = uniform(lds32(bars + ISSUED_AT));
                    now = timer_ns();
                    const int lead = max((int)(last ? tune.LEAD_C : tune.LEAD_B), (int)tune.LEAD_A - (max((int)issued - (int)tune.LEAD_F, 0) * (int)tune.LEAD_S >> 4));
                    if (reached(now, due)) {
                        if (cluster + piece * step <= issued + lead) break;
                        due = now;
                    }
                    __nanosleep(20);
                }
                if (reached(now - tune.PM_SLACK, due)) due = now - tune.PM_SLACK;
                due += piece < tune.PM_E1 ? tune.PM_DT1 : piece < tune.PM_E2 ? tune.PM_DT2 : last ? tune.PM_DT4 : tune.PM_DT3;
                const uint8_t* p = x_raw + (size_t)t * STAGE_BYTES + rank * HALF_BYTES + (piece % 2) * PIECE_BYTES + lane * 128;
#pragma unroll
                for (int k = 0; k < PIECE_BYTES / 4096; k++) prefetch_l2(p + k * 4096);
                if (piece % 2 == 0) TR(14, piece / 2);
            }
            cluster_wait();
        }
    }
}

typedef CUresult (*EncodeTiledFn)(CUtensorMap*, CUtensorMapDataType, cuuint32_t, void*, const cuuint64_t*,
                                  const cuuint64_t*, const cuuint32_t*, const cuuint32_t*, CUtensorMapInterleave,
                                  CUtensorMapSwizzle, CUtensorMapL2promotion, CUtensorMapFloatOOBfill);

}

extern "C" void kernel_launch(void* const* d_in, const int* in_sizes, int n_in, void* d_out, int out_size) {
    (void)n_in;
    (void)out_size;
    void* x = d_in[0];
    void* w = d_in[1];
    const uint16_t* b = (const uint16_t*)d_in[2];
    const int M = in_sizes[0] / C;
    const int num_tiles = M / TILE_PIX;

    static EncodeTiledFn encode = nullptr;
    static int sms = 0;
    if (!encode) {
        void* fn = nullptr;
        cudaDriverEntryPointQueryResult q;
        cudaGetDriverEntryPoint("cuTensorMapEncodeTiled", &fn, cudaEnableDefault, &q);
        encode = (EncodeTiledFn)fn;
        cudaDeviceGetAttribute(&sms, cudaDevAttrMultiProcessorCount, 0);
        cudaFuncSetAttribute(conv1x1_kernel, cudaFuncAttributeMaxDynamicSharedMemorySize, SMEM_TOTAL);
    }

    Maps maps;
    const cuuint32_t ones[4] = {1, 1, 1, 1};
    auto make = [&](CUtensorMap* map, int rank, void* base, const cuuint64_t* dims, const cuuint64_t* strides,
                    const cuuint32_t* box, CUtensorMapL2promotion promo) {
        encode(map, CU_TENSOR_MAP_DATA_TYPE_BFLOAT16, rank, base, dims, strides, box, ones, CU_TENSOR_MAP_INTERLEAVE_NONE,
               CU_TENSOR_MAP_SWIZZLE_128B, promo, CU_TENSOR_MAP_FLOAT_OOB_FILL_NONE);
    };
    {
        const cuuint64_t dims[4]    = {64, 8, 6, (cuuint64_t)(M / 8)};
        const cuuint64_t strides[3] = {C * 2, 128, 8 * C * 2};
        const cuuint32_t box[4]     = {64, 8, 6, TILE_PIX / 16};
        make(&maps.x, 4, x, dims, strides, box, CU_TENSOR_MAP_L2_PROMOTION_L2_128B);
    }
    {
        const cuuint64_t dims[3]    = {C, C / 2, 2};
        const cuuint64_t strides[2] = {C * 2, C * C};
        const cuuint32_t box[3]     = {64, C / 2, 2};
        make(&maps.w, 3, w, dims, strides, box, CU_TENSOR_MAP_L2_PROMOTION_L2_128B);
    }
    {
        const cuuint64_t dims[2]    = {C, (cuuint64_t)M};
        const cuuint64_t strides[1] = {C * 2};
        const cuuint32_t box[2]     = {64, TILE_PIX};
        make(&maps.out, 2, d_out, dims, strides, box, CU_TENSOR_MAP_L2_PROMOTION_NONE);
    }

    const Tune tune;
    int clusters = sms / 2;
    if (clusters > num_tiles) clusters = num_tiles;
    conv1x1_kernel<<<clusters * 2, THREADS, SMEM_TOTAL>>>((const uint8_t*)x, (const uint8_t*)w, b, (uint32_t)num_tiles,
                                                          (uint32_t)clusters, maps, tune);
}
```

```cpp
#include <cuda_runtime.h>
#include <cuda_bf16.h>
#include <cuda.h>
#include <stdint.h>

#define TUNABLES(F) \
    F(PM_T0, 350)        \
    F(PM_STAG, 30)      \
    F(PM_DT1, 415)       \
    F(PM_E1, 7) \
    F(PM_DT2, 475) \
    F(PM_E2, 23) \
    F(PM_DT3, 860) \
    F(PM_SLACK, 500)     \
    F(LEAD_A, 269)       \
    F(LEAD_F, 550)       \
    F(LEAD_S, 3)         \
    F(LEAD_B, 151)       \
    F(LEAD_T, 264)         \
    F(LEAD_C, 170)       \
    F(PM_DT4, 700)       \
    F(EF_TAIL, 500)      \
    F(ST_AT, 2)          \
    F(ST_T0, 6830)       \
    F(ST_S1, 2040)       \
    F(ST_N1, 448) \
    F(ST_S2, 1860) \
    F(ST_N2, 594) \
    F(ST_S3, 1970)       \
    F(ST_END, 613) \
    F(ST_S4, 1500)       \
    F(ST_N4, 100) \
    F(ST_S5, 1100) \
    F(ST_N5, 100) \
    F(ST_S6, 962) \
    F(ST_N7, 22)          \
    F(CC_AT, 22)         \
    F(CC_L0, 1300)       \
    F(CC_G, 14)          \
    F(CC_STEP, 1100)      \
    F(CC_CAP, 1350)

struct Tune {
#define F(n, v) uint32_t n = v;
    TUNABLES(F)
#undef F
};

#define TRV(slot, idx, v)
#define TR(slot, idx)
#define TRE(slot, idx)
#define TRACE_BYTES 0

namespace {

constexpr int C            = 384;
constexpr int TILE_PIX     = 64;
constexpr int STAGES       = 3;
constexpr int STAGE_BYTES  = TILE_PIX * C * 2;
constexpr int HALF_BYTES   = STAGE_BYTES / 2;
constexpr int PIECE_BYTES  = HALF_BYTES / 2;
constexpr int SLICE_BYTES  = TILE_PIX * 128;
constexpr int NUM_WG       = 3;
constexpr int THREADS      = (NUM_WG + 1) * 128;
constexpr int SMEM_OUT     = STAGES * STAGE_BYTES;
constexpr int SMEM_BAR     = SMEM_OUT + STAGES * HALF_BYTES;
constexpr int SMEM_TOTAL   = SMEM_BAR + 512 + TRACE_BYTES + 1024;
constexpr int HAND_AT      = 18;
constexpr int W_LINES      = C * C * 2 / 128;
constexpr int PRE_W        = 64;
constexpr int PRE_DT       = 330;
constexpr uint32_t SPIN_LIMIT = 1u << 22;
constexpr int BAR_W     = 0;
constexpr int BAR_FULL  = 32;
constexpr int BAR_EMPTY = 64;
constexpr int BAR_OFREE = 96;
constexpr int BAR_OFULL = BAR_OFREE + 32 * STAGES;
constexpr int ISSUED_AT = BAR_OFULL + 32 * STAGES;
constexpr int DELAY_AT  = ISSUED_AT + 4;
constexpr int STAMP_AT  = DELAY_AT + 4;
constexpr int SINK_AT   = 384;

struct Maps {
    CUtensorMap w, x, out;
};

#define ELECT "{\n.reg .pred e;\nelect.sync _|e, 0xffffffff;\n@e "

__device__ __forceinline__ uint32_t smem_u32(const void* p) {
    return (uint32_t)__cvta_generic_to_shared(p);
}
__device__ __forceinline__ void mbar_init_1(uint32_t bar, uint32_t count) {
    asm volatile(ELECT "mbarrier.init.shared::cta.b64 [%0], %1;\n}" ::"r"(bar), "r"(count) : "memory");
}
__device__ __forceinline__ void mbar_expect_tx_1(uint32_t bar, uint32_t bytes) {
    asm volatile(ELECT "mbarrier.arrive.expect_tx.shared::cta.b64 _, [%0], %1;\n}" ::"r"(bar), "r"(bytes) : "memory");
}
__device__ __forceinline__ void mbar_arrive_1(uint32_t bar) {
    asm volatile(ELECT "mbarrier.arrive.shared::cta.b64 _, [%0];\n}" ::"r"(bar) : "memory");
}
__device__ __forceinline__ void mbar_wait(uint32_t bar, uint32_t parity) {
    uint32_t done;
    uint32_t spins = 0;
    do {
        asm volatile(
            "{\n.reg .pred p;\n"
            "mbarrier.try_wait.parity.shared::cta.b64 p, [%1], %2;\n"
            "selp.u32 %0, 1, 0, p;\n}"
            : "=r"(done) : "r"(bar), "r"(parity) : "memory");
    } while (!done && ++spins < SPIN_LIMIT);
    __syncwarp();
}
__device__ __forceinline__ bool mbar_test(uint32_t bar, uint32_t parity) {
    uint32_t done;
    asm volatile(
        "{\n.reg .pred p;\n"
        "mbarrier.test_wait.parity.shared::cta.b64 p, [%1], %2;\n"
        "selp.u32 %0, 1, 0, p;\n}"
        : "=r"(done) : "r"(bar), "r"(parity) : "memory");
    return __all_sync(0xffffffffu, done);
}
__device__ __forceinline__ void mbar_arrive_cta(uint32_t bar, uint32_t cta) {
    asm volatile(
        "{\n.reg .b32 ra;\n"
        "mapa.shared::cluster.u32 ra, %0, %1;\n"
        "mbarrier.arrive.shared::cluster.b64 _, [ra];\n}"
        ::"r"(bar), "r"(cta) : "memory");
}
__device__ __forceinline__ uint32_t lds32(uint32_t addr) {
    uint32_t v;
    asm volatile("ld.volatile.shared.b32 %0, [%1];" : "=r"(v) : "r"(addr) : "memory");
    return v;
}
__device__ __forceinline__ void sts32(uint32_t addr, uint32_t v) {
    asm volatile("st.volatile.shared.b32 [%0], %1;" ::"r"(addr), "r"(v) : "memory");
}
__device__ __forceinline__ uint32_t uniform(uint32_t v) {
    return __shfl_sync(0xffffffffu, v, 0);
}
__device__ __forceinline__ void tma_load_w_1(uint32_t dst, const CUtensorMap* map, uint32_t bar, int n) {
    asm volatile(
        ELECT "cp.async.bulk.tensor.3d.shared::cluster.global.mbarrier::complete_tx::bytes [%0], [%1, {%3, %4, %4}], [%2];\n}"
        ::"r"(dst), "l"(map), "r"(bar), "r"(n), "r"(0) : "memory");
}
__device__ __forceinline__ void tma_load_x_1(uint32_t dst, const CUtensorMap* map, uint32_t bar, int group) {
    asm volatile(
        ELECT "cp.async.bulk.tensor.4d.shared::cluster.global.mbarrier::complete_tx::bytes.multicast::cluster"
        " [%0], [%1, {%3, %3, %3, %4}], [%2], %5;\n}"
        ::"r"(dst), "l"(map), "r"(bar), "r"(0), "r"(group), "h"((uint16_t)3) : "memory");
}
__device__ __forceinline__ void tma_load_x_evict_first_1(uint32_t dst, const CUtensorMap* map, uint32_t bar, int group) {
    asm volatile(
        "{\n.reg .b64 pol;\n"
        "createpolicy.fractional.L2::evict_first.b64 pol, 1.0;\n"
        ELECT "cp.async.bulk.tensor.4d.shared::cluster.global.mbarrier::complete_tx::bytes.multicast::cluster.L2::cache_hint"
        " [%0], [%1, {%3, %3, %3, %4}], [%2], %5, pol;\n}\n}"
        ::"r"(dst), "l"(map), "r"(bar), "r"(0), "r"(group), "h"((uint16_t)3) : "memory");
}
__device__ __forceinline__ void tma_store_1(const CUtensorMap* map, uint32_t src, int ch, int pix) {
    asm volatile(
        ELECT "cp.async.bulk.tensor.2d.global.shared::cta.bulk_group [%0, {%2, %3}], [%1];\n}\n"
        "cp.async.bulk.commit_group;"
        ::"l"(map), "r"(src), "r"(ch), "r"(pix) : "memory");
}
template <int N>
__device__ __forceinline__ void stores_read_wait() {
    asm volatile("cp.async.bulk.wait_group.read %0;" ::"n"(N) : "memory");
}
__device__ __forceinline__ void prefetch_map_1(const CUtensorMap* map) {
    asm volatile(ELECT "prefetch.tensormap [%0];\n}" ::"l"(map) : "memory");
}
__device__ __forceinline__ void prefetch_l2(const void* p) {
    asm volatile("prefetch.global.L2 [%0];" ::"l"(p) : "memory");
}
__device__ __forceinline__ uint32_t timer_ns() {
    uint32_t t;
    asm volatile("mov.u32 %0, %%globaltimer_lo;" : "=r"(t)::"memory");
    return t;
}
__device__ __forceinline__ bool reached(uint32_t now, uint32_t t) {
    return (int32_t)(now - t) >= 0;
}
__device__ __forceinline__ void cluster_arrive() {
    asm volatile("barrier.cluster.arrive.relaxed.aligned;" ::: "memory");
}
__device__ __forceinline__ void cluster_wait() {
    asm volatile("barrier.cluster.wait.aligned;" ::: "memory");
}
__device__ __forceinline__ void publish_barriers() {
    asm volatile("fence.mbarrier_init.release.cluster;" ::: "memory");
    asm volatile("fence.proxy.async.shared::cta;" ::: "memory");
}

__device__ __forceinline__ void wgmma_rs_n64(float (&d)[32], const uint32_t* a, uint64_t desc, int scale_d) {
    asm volatile(
        "{\n.reg .pred p;\n"
        "setp.ne.b32 p, %37, 0;\n"
        "wgmma.mma_async.sync.aligned.m64n64k16.f32.bf16.bf16 "
        "{%0, %1, %2, %3, %4, %5, %6, %7, %8, %9, %10, %11, %12, %13, %14, %15, "
        "%16, %17, %18, %19, %20, %21, %22, %23, %24, %25, %26, %27, %28, %29, %30, %31}, "
        "{%32, %33, %34, %35}, %36, p, 1, 1, 0;\n}"
        : "+f"(d[0]), "+f"(d[1]), "+f"(d[2]), "+f"(d[3]), "+f"(d[4]), "+f"(d[5]), "+f"(d[6]), "+f"(d[7]),
          "+f"(d[8]), "+f"(d[9]), "+f"(d[10]), "+f"(d[11]), "+f"(d[12]), "+f"(d[13]), "+f"(d[14]), "+f"(d[15]),
          "+f"(d[16]), "+f"(d[17]), "+f"(d[18]), "+f"(d[19]), "+f"(d[20]), "+f"(d[21]), "+f"(d[22]), "+f"(d[23]),
          "+f"(d[24]), "+f"(d[25]), "+f"(d[26]), "+f"(d[27]), "+f"(d[28]), "+f"(d[29]), "+f"(d[30]), "+f"(d[31])
        : "r"(a[0]), "r"(a[1]), "r"(a[2]), "r"(a[3]), "l"(desc), "r"(scale_d));
}

__device__ __forceinline__ uint32_t pack_bias(float lo, float hi, uint32_t bias2) {
    uint32_t r;
    asm("{\n.reg .b32 t;\n"
        "cvt.rn.bf16x2.f32 t, %2, %1;\n"
        "add.rn.bf16x2 %0, t, %3;\n}"
        : "=r"(r) : "f"(lo), "f"(hi), "r"(bias2));
    return r;
}

__device__ __forceinline__ int slice_channel(uint32_t rank, int wg) {
    return (wg * 2 + rank) * 64;
}
__device__ __forceinline__ uint32_t w_stage(int wg) {
    return (wg + 1) * STAGE_BYTES + (wg == 2 ? HALF_BYTES : 0);
}

struct Ring {
    uint32_t s, parity;
    __device__ __forceinline__ void advance() {
        if (++s == STAGES) {
            s = 0;
            parity ^= 1;
        }
    }
};

__device__ __forceinline__ void write_out(uint32_t wg_bars, uint32_t st_addr, const Ring& r, const uint32_t (&v)[16]) {
    mbar_wait(wg_bars + BAR_OFREE + r.s * 32, r.parity ^ 1);
    const uint32_t dst = st_addr + r.s * HALF_BYTES;
#pragma unroll
    for (int j = 0; j < 4; j++) {
        asm volatile("stmatrix.sync.aligned.m8n8.x4.trans.shared.b16 [%0], {%1, %2, %3, %4};"
                     ::"r"(dst + j * 2048), "r"(v[4 * j]), "r"(v[4 * j + 1]), "r"(v[4 * j + 2]), "r"(v[4 * j + 3]) : "memory");
    }
    asm volatile("fence.proxy.async.shared::cta;" ::: "memory");
    __syncwarp();
    mbar_arrive_1(wg_bars + BAR_OFULL + r.s * 32);
}

template <int N>
__device__ __forceinline__ void hand_back(uint32_t& open) {
    if (open != 0) {
        stores_read_wait<N>();
        mbar_arrive_1(open);
        open = 0;
    }
}

__global__ void __cluster_dims__(2, 1, 1) __launch_bounds__(THREADS, 1)
conv1x1_kernel(const uint8_t* __restrict__ x_raw,
               const uint8_t* __restrict__ w_raw,
               const uint16_t* __restrict__ bias,
               uint32_t num_tiles,
               uint32_t num_clusters,
               const __grid_constant__ Maps maps,
               const __grid_constant__ Tune tune) {
    const uint32_t t_entry = timer_ns();
    extern __shared__ uint8_t smem_raw[];
    const uint32_t smem = (smem_u32(smem_raw) + 1023u) & ~1023u;
    const uint32_t bars = smem + SMEM_BAR;

    if (threadIdx.x < PRE_W) {
        prefetch_l2(w_raw + (blockIdx.x % (W_LINES / PRE_W) * PRE_W + threadIdx.x) * 128);
    } else if (threadIdx.x >= 96 && threadIdx.x < 128) {
        prefetch_map_1(&maps.w);
        prefetch_map_1(&maps.x);
    }
    if (threadIdx.x < NUM_WG * 128) cluster_arrive();
    if (threadIdx.x >= 128 && threadIdx.x < 128 + PIECE_BYTES / 128) {
        const uint8_t* p = x_raw + (size_t)blockIdx.x * HALF_BYTES + (threadIdx.x - 128) * 128;
        const uint32_t wait = ((threadIdx.x - 128) >> 5) * PRE_DT;
        const uint32_t c0 = (uint32_t)clock();
        while ((uint32_t)clock() - c0 < wait) {}
        asm volatile("cp.async.ca.shared.global.L2::128B [%0], [%1], 4;" ::"r"(bars + SINK_AT + (threadIdx.x & 31) * 4), "l"(p) : "memory");
    }
    if (threadIdx.x == 0) TRV(0, 63, t_entry);

    const int warp = uniform(threadIdx.x >> 5);
    const int lane = threadIdx.x & 31;
    const uint32_t rank    = blockIdx.x & 1;
    const uint32_t cluster = blockIdx.x >> 1;

    if (warp < NUM_WG * 4) {
        asm volatile("setmaxnreg.inc.sync.aligned.u32 160;");
        const int wg = warp >> 2;
        const int wq = warp & 3;
        const uint32_t bias_lo = bias[slice_channel(rank, wg) + wq * 16 + (lane >> 2)] * 0x10001u;
        const uint32_t bias_hi = bias[slice_channel(rank, wg) + wq * 16 + (lane >> 2) + 8] * 0x10001u;

        cluster_wait();
        TRE(1 + wg, 63);
        mbar_wait(bars + BAR_W + 8 * wg, 0);
        TRE(4 + wg, 63);
        uint32_t wreg[96];
        {
            const int r = lane & 7, m = lane >> 3;
            const uint32_t base = smem + w_stage(wg) + ((m >> 1) * 8 + r) * 128 + (((2 * wq + (m & 1)) ^ r) << 4);
#pragma unroll
            for (int ks = 0; ks < 24; ks++) {
                asm volatile("ldmatrix.sync.aligned.m8n8.x4.trans.shared.b16 {%0, %1, %2, %3}, [%4];"
                             : "=r"(wreg[ks * 4 + 0]), "=r"(wreg[ks * 4 + 1]), "=r"(wreg[ks * 4 + 2]), "=r"(wreg[ks * 4 + 3])
                             : "r"(base + ks * 2048) : "memory");
            }
        }
        uint32_t dep = 0;
#pragma unroll
        for (int ks = 0; ks < 24; ks++) dep ^= wreg[ks * 4];
        dep = uniform(dep & (num_tiles >> 31));
        if (lane < 6 && wg < 2) mbar_arrive_cta(bars + BAR_EMPTY + 8 * (wg + 1) + dep, lane & 1);
        asm volatile("cp.async.wait_all;" ::: "memory");
        TRE(1 + wg, 60);

        const uint32_t wg_bars = bars + wg * 8;
        const uint32_t st_addr = smem + SMEM_OUT + wg * SLICE_BYTES + ((lane >> 4) * 8 + (lane & 7)) * 128 +
                                 (((2 * wq + ((lane >> 3) & 1)) ^ (lane & 7)) << 4);
        const uint64_t desc_base =
            (uint64_t)((smem & 0x3FFFF) >> 4) | ((uint64_t)1 << 16) | ((uint64_t)(6144 >> 4) << 32) | ((uint64_t)1 << 62);
        const int next_turn = 4 + (wg + 1) % NUM_WG;

        float acc[32];
        uint32_t packed[16];
        Ring r = {0, dep}, o = r;
        bool held = false;
        for (uint32_t i = 0, id = cluster; id < num_tiles; i++, id += num_clusters, r.advance()) {
            mbar_wait(bars + BAR_FULL + 8 * r.s, r.parity);
            if ((i | wg) != 0) asm volatile("bar.sync %0, 256;" ::"r"(4 + wg) : "memory");
            TRE(1 + wg * 2, i);
            const uint64_t desc = desc_base + (uint64_t)(r.s * (STAGE_BYTES >> 4));
            asm volatile("wgmma.fence.sync.aligned;" ::: "memory");
#pragma unroll
            for (int ks = 0; ks < 24; ks++) {
                wgmma_rs_n64(acc, &wreg[ks * 4], desc + (uint64_t)((ks >> 2) * 64 + (ks & 3) * 2), ks != 0);
                if (ks + 1 == HAND_AT) asm volatile("bar.arrive %0, 256;" ::"r"(next_turn) : "memory");
            }
            asm volatile("wgmma.commit_group.sync.aligned;" ::: "memory");
            asm volatile("wgmma.wait_group.sync.aligned 0;" ::: "memory");
#pragma unroll
            for (int j = 0; j < 32; j++) asm volatile("" : "+f"(acc[j])::"memory");
            TRE(2 + wg * 2, i);
            if (lane < 2) mbar_arrive_cta(bars + BAR_EMPTY + 8 * r.s, lane);

            if (held) write_out(wg_bars, st_addr, o, packed);
            o = r;
#pragma unroll
            for (int j = 0; j < 16; j++) packed[j] = pack_bias(acc[2 * j], acc[2 * j + 1], j & 1 ? bias_hi : bias_lo);
            held = !mbar_test(wg_bars + BAR_OFREE + o.s * 32, o.parity ^ 1);
            if (!held) write_out(wg_bars, st_addr, o, packed);
            TRE(8 + wg, i);
        }
        if (held) write_out(wg_bars, st_addr, o, packed);
        if (wg == 0) asm volatile("bar.sync 4, 256;" ::: "memory");
        TRE(1 + wg, 62);
    } else {
        asm volatile("setmaxnreg.dec.sync.aligned.u32 32;");
        if (warp == NUM_WG * 4) {
#pragma unroll
            for (int j = 0; j < NUM_WG; j++) mbar_init_1(bars + BAR_W + 8 * j, 1);
            publish_barriers();
            cluster_arrive();
#pragma unroll
            for (int j = 0; j < NUM_WG; j++) {
                mbar_expect_tx_1(bars + BAR_W + 8 * j, STAGE_BYTES);
                tma_load_w_1(smem + w_stage(j), &maps.w, bars + BAR_W + 8 * j, slice_channel(rank, j));
                if (j == 0) TR(2, 61);
            }
            cluster_wait();
            TR(0, 0);
            mbar_expect_tx_1(bars + BAR_FULL, STAGE_BYTES);
            tma_load_x_1(smem + rank * HALF_BYTES, &maps.x, bars + BAR_FULL, cluster * 8 + rank * 4);
            Ring r = {1, 0};
#pragma unroll 1
            for (uint32_t i = 1, id = cluster + num_clusters; id < num_tiles; i++, id += num_clusters, r.advance()) {
                mbar_wait(bars + BAR_EMPTY + 8 * r.s, r.parity ^ (r.s == 0));
                sts32(bars + ISSUED_AT, id);
                sts32(bars + STAMP_AT + 4 * r.s, timer_ns());
                TR(0, i);
                TRV(15, i, id);
                const uint32_t full = bars + BAR_FULL + 8 * r.s;
                const uint32_t dst = smem + r.s * STAGE_BYTES + rank * HALF_BYTES;
                mbar_expect_tx_1(full, STAGE_BYTES);
                if (id + tune.EF_TAIL < num_tiles) tma_load_x_1(dst, &maps.x, full, id * 8 + rank * 4);
                else tma_load_x_evict_first_1(dst, &maps.x, full, id * 8 + rank * 4);
            }
#pragma unroll 1
            for (int k = 0; k < STAGES; k++, r.advance()) mbar_wait(bars + BAR_EMPTY + 8 * r.s, r.parity ^ (r.s == 0));
        } else if (warp == NUM_WG * 4 + 1) {
#pragma unroll
            for (int s = 0; s < STAGES; s++) {
                mbar_init_1(bars + BAR_FULL + 8 * s, 1);
                mbar_init_1(bars + BAR_EMPTY + 8 * s, NUM_WG * 4 * 2);
            }
            publish_barriers();
            cluster_arrive();
            TR(0, 61);
            cluster_wait();
            prefetch_map_1(&maps.out);
            uint32_t delay = 0;
            Ring r = {0, 0};
#pragma unroll 1
            for (uint32_t i = 0, id = cluster; id < num_tiles; i++, id += num_clusters, r.advance()) {
                mbar_wait(bars + BAR_FULL + 8 * r.s, r.parity);
                TR(7, i);
                const int late = (int)(timer_ns() - lds32(bars + STAMP_AT + 4 * r.s) - tune.CC_L0);
                if (i >= tune.CC_AT && late > 0) {
                    delay = min(delay + min((uint32_t)late * tune.CC_G >> 4, tune.CC_STEP), tune.CC_CAP);
                    sts32(bars + DELAY_AT, delay);
                }
            }
        } else if (warp == NUM_WG * 4 + 2) {
            sts32(bars + DELAY_AT, 0);
#pragma unroll
            for (int b = 0; b < STAGES; b++) {
#pragma unroll
                for (int w = 0; w < NUM_WG; w++) {
                    mbar_init_1(bars + BAR_OFREE + b * 32 + w * 8, 1);
                    mbar_init_1(bars + BAR_OFULL + b * 32 + w * 8, 4);
                }
            }
            publish_barriers();
            cluster_arrive();
            cluster_wait();
            const uint32_t first = tune.ST_AT * num_clusters;
            const uint32_t n3 = max((int)(num_tiles - first - tune.ST_N1 - tune.ST_N2 - tune.ST_END), 0);
            auto release_time = [&](uint32_t id) {
                if (id < first) return t_entry;
                uint32_t rest = id - first, t = 0;
                auto segment = [&](uint32_t ids, uint32_t per_round) {
                    const uint32_t n = min(rest, ids);
                    t += n * per_round;
                    rest -= n;
                };
                segment(tune.ST_N1, tune.ST_S1);
                segment(tune.ST_N2, tune.ST_S2);
                segment(n3, tune.ST_S3);
                segment(tune.ST_N4, tune.ST_S4);
                segment(tune.ST_N5, tune.ST_S5);
                segment(tune.ST_END - tune.ST_N4 - tune.ST_N5 - tune.ST_N7, tune.ST_S6);
                return t_entry + tune.ST_T0 + t / num_clusters;
            };
            const uint32_t lane_full = bars + BAR_OFULL + min(lane, NUM_WG - 1) * 8;
            uint32_t open = 0, due = release_time(cluster);
            Ring o = {0, 0};
#pragma unroll 1
            for (uint32_t j = 0, id = cluster; id < num_tiles; j++, id += num_clusters, o.advance()) {
                const uint32_t obar = bars + o.s * 32;
                const uint32_t src = smem + SMEM_OUT + o.s * HALF_BYTES;
                bool whole;
#pragma unroll 1
                for (uint32_t spins = 0; spins < SPIN_LIMIT; spins++) {
                    const uint32_t delay = lds32(bars + DELAY_AT);
                    whole = mbar_test(lane_full + o.s * 32, o.parity);
                    if (reached(timer_ns(), due + uniform(delay))) break;
                    hand_back<0>(open);
                    __nanosleep(20);
                }
                if (whole) {
                    TR(11, j);
#pragma unroll
                    for (int w = 0; w < NUM_WG; w++) tma_store_1(&maps.out, src + w * SLICE_BYTES, slice_channel(rank, w), id * TILE_PIX);
                    due = release_time(id + num_clusters);
                    hand_back<3>(open);
                    stores_read_wait<2>();
                    TR(12, j);
                    mbar_arrive_1(obar + BAR_OFREE);
                    stores_read_wait<1>();
                    TR(13, j);
                    mbar_arrive_1(obar + BAR_OFREE + 8);
                    open = obar + BAR_OFREE + 16;
                } else {
#pragma unroll 1
                    for (uint32_t w = 0; w < NUM_WG; w++) {
                        if (!mbar_test(obar + BAR_OFULL + w * 8, o.parity)) {
                            hand_back<0>(open);
                            mbar_wait(obar + BAR_OFULL + w * 8, o.parity);
                        }
                        TR(11 + w, j);
                        tma_store_1(&maps.out, src + w * SLICE_BYTES, slice_channel(rank, w), id * TILE_PIX);
                        hand_back<1>(open);
                        open = obar + BAR_OFREE + w * 8;
                    }
                    due = release_time(id + num_clusters);
                }
            }
            stores_read_wait<0>();
            TR(4, 62);
            TRV(6, 62, lds32(bars + DELAY_AT));
        } else {
            sts32(bars + ISSUED_AT, 0);
            cluster_arrive();
            uint32_t due = t_entry + tune.PM_T0 + (blockIdx.x & 3) * tune.PM_STAG;
            const uint32_t step = num_clusters / 2;
#pragma unroll 1
            for (uint32_t piece = 1;; piece++) {
                const uint32_t t = cluster + piece / 2 * num_clusters;
                if (t >= num_tiles) break;
                const bool last = t + tune.LEAD_T >= num_tiles;
                uint32_t now;
#pragma unroll 1
                for (uint32_t spins = 0; spins < 16384; spins++) {
                    const uint32_t issued = uniform(lds32(bars + ISSUED_AT));
                    now = timer_ns();
                    const int lead = max((int)(last ? tune.LEAD_C : tune.LEAD_B), (int)tune.LEAD_A - (max((int)issued - (int)tune.LEAD_F, 0) * (int)tune.LEAD_S >> 4));
                    if (reached(now, due)) {
                        if (cluster + piece * step <= issued + lead) break;
                        due = now;
                    }
                    __nanosleep(20);
                }
                if (reached(now - tune.PM_SLACK, due)) due = now - tune.PM_SLACK;
                due += piece < tune.PM_E1 ? tune.PM_DT1 : piece < tune.PM_E2 ? tune.PM_DT2 : last ? tune.PM_DT4 : tune.PM_DT3;
                const uint8_t* p = x_raw + (size_t)t * STAGE_BYTES + rank * HALF_BYTES + (piece % 2) * PIECE_BYTES + lane * 128;
#pragma unroll
                for (int k = 0; k < PIECE_BYTES / 4096; k++) prefetch_l2(p + k * 4096);
                if (piece % 2 == 0) TR(14, piece / 2);
            }
            cluster_wait();
        }
    }
}

typedef CUresult (*EncodeTiledFn)(CUtensorMap*, CUtensorMapDataType, cuuint32_t, void*, const cuuint64_t*,
                                  const cuuint64_t*, const cuuint32_t*, const cuuint32_t*, CUtensorMapInterleave,
                                  CUtensorMapSwizzle, CUtensorMapL2promotion, CUtensorMapFloatOOBfill);

}

extern "C" void kernel_launch(void* const* d_in, const int* in_sizes, int n_in, void* d_out, int out_size) {
    (void)n_in;
    (void)out_size;
    void* x = d_in[0];
    void* w = d_in[1];
    const uint16_t* b = (const uint16_t*)d_in[2];
    const int M = in_sizes[0] / C;
    const int num_tiles = M / TILE_PIX;

    static EncodeTiledFn encode = nullptr;
    static int sms = 0;
    if (!encode) {
        void* fn = nullptr;
        cudaDriverEntryPointQueryResult q;
        cudaGetDriverEntryPoint("cuTensorMapEncodeTiled", &fn, cudaEnableDefault, &q);
        encode = (EncodeTiledFn)fn;
        cudaDeviceGetAttribute(&sms, cudaDevAttrMultiProcessorCount, 0);
        cudaFuncSetAttribute(conv1x1_kernel, cudaFuncAttributeMaxDynamicSharedMemorySize, SMEM_TOTAL);
    }

    Maps maps;
    const cuuint32_t ones[4] = {1, 1, 1, 1};
    auto make = [&](CUtensorMap* map, int rank, void* base, const cuuint64_t* dims, const cuuint64_t* strides,
                    const cuuint32_t* box, CUtensorMapL2promotion promo) {
        encode(map, CU_TENSOR_MAP_DATA_TYPE_BFLOAT16, rank, base, dims, strides, box, ones, CU_TENSOR_MAP_INTERLEAVE_NONE,
               CU_TENSOR_MAP_SWIZZLE_128B, promo, CU_TENSOR_MAP_FLOAT_OOB_FILL_NONE);
    };
    {
        const cuuint64_t dims[4]    = {64, 8, 6, (cuuint64_t)(M / 8)};
        const cuuint64_t strides[3] = {C * 2, 128, 8 * C * 2};
        const cuuint32_t box[4]     = {64, 8, 6, TILE_PIX / 16};
        make(&maps.x, 4, x, dims, strides, box, CU_TENSOR_MAP_L2_PROMOTION_L2_128B);
    }
    {
        const cuuint64_t dims[3]    = {C, C / 2, 2};
        const cuuint64_t strides[2] = {C * 2, C * C};
        const cuuint32_t box[3]     = {64, C / 2, 2};
        make(&maps.w, 3, w, dims, strides, box, CU_TENSOR_MAP_L2_PROMOTION_L2_128B);
    }
    {
        const cuuint64_t dims[2]    = {C, (cuuint64_t)M};
        const cuuint64_t strides[1] = {C * 2};
        const cuuint32_t box[2]     = {64, TILE_PIX};
        make(&maps.out, 2, d_out, dims, strides, box, CU_TENSOR_MAP_L2_PROMOTION_NONE);
    }

    const Tune tune;
    int clusters = sms / 2;
    if (clusters > num_tiles) clusters = num_tiles;
    conv1x1_kernel<<<clusters * 2, THREADS, SMEM_TOTAL>>>((const uint8_t*)x, (const uint8_t*)w, b, (uint32_t)num_tiles,
                                                          (uint32_t)clusters, maps, tune);
}
```

```cpp
#include <cuda_runtime.h>
#include <cuda_bf16.h>
#include <cuda.h>
#include <stdint.h>

#define TUNABLES(F) \
    F(PM_T0, 350)        \
    F(PM_STAG, 30)       \
    F(PM_DT1, 415)       \
    F(PM_E1, 7) \
    F(PM_DT2, 475) \
    F(PM_E2, 23) \
    F(PM_DT3, 860) \
    F(PM_SLACK, 500)     \
    F(LEAD_A, 269)       \
    F(LEAD_F, 550)       \
    F(LEAD_S, 3)         \
    F(LEAD_B, 151)       \
    F(LEAD_T, 264)       \
    F(LEAD_C, 170)       \
    F(PM_DT4, 700)       \
    F(EF_TAIL, 500)      \
    F(ST_AT, 2)          \
    F(ST_T0, 6830)       \
    F(ST_S1, 2040)       \
    F(ST_N1, 448) \
    F(ST_S2, 1860) \
    F(ST_N2, 594) \
    F(ST_S3, 1970)       \
    F(ST_END, 613) \
    F(ST_S4, 1500)       \
    F(ST_N4, 100) \
    F(ST_S5, 1100) \
    F(ST_N5, 100) \
    F(ST_S6, 962) \
    F(ST_N7, 22)         \
    F(CC_AT, 22)         \
    F(CC_L0, 1300)       \
    F(CC_G, 14)          \
    F(CC_STEP, 1100)     \
    F(CC_CAP, 1350)

struct Tune {
#define F(n, v) uint32_t n = v;
    TUNABLES(F)
#undef F
};

#define TRV(slot, idx, v)
#define TR(slot, idx)
#define TRE(slot, idx)
#define TRACE_BYTES 0

namespace {

constexpr int C            = 384;
constexpr int TILE_PIX     = 64;
constexpr int STAGES       = 3;
constexpr int STAGE_BYTES  = TILE_PIX * C * 2;
constexpr int HALF_BYTES   = STAGE_BYTES / 2;
constexpr int PIECE_BYTES  = HALF_BYTES / 2;
constexpr int SLICE_BYTES  = TILE_PIX * 128;
constexpr int NUM_WG       = 3;
constexpr int THREADS      = (NUM_WG + 1) * 128;
constexpr int SMEM_OUT     = STAGES * STAGE_BYTES;
constexpr int SMEM_BAR     = SMEM_OUT + STAGES * HALF_BYTES;
constexpr int SMEM_TOTAL   = SMEM_BAR + 512 + TRACE_BYTES + 1024;
constexpr int HAND_AT      = 18;
constexpr int W_LINES      = C * C * 2 / 128;
constexpr int PRE_W        = 64;
constexpr int PRE_DT       = 330;
constexpr uint32_t SPIN_LIMIT = 1u << 22;
constexpr int BAR_W     = 0;
constexpr int BAR_FULL  = 32;
constexpr int BAR_EMPTY = 64;
constexpr int BAR_OFREE = 96;
constexpr int BAR_OFULL = BAR_OFREE + 32 * STAGES;
constexpr int ISSUED_AT = BAR_OFULL + 32 * STAGES;
constexpr int DELAY_AT  = ISSUED_AT + 4;
constexpr int STAMP_AT  = DELAY_AT + 4;
constexpr int SINK_AT   = 384;

struct Maps {
    CUtensorMap w, x, out;
};

#define ELECT "{\n.reg .pred e;\nelect.sync _|e, 0xffffffff;\n@e "

__device__ __forceinline__ uint32_t smem_u32(const void* p) {
    return (uint32_t)__cvta_generic_to_shared(p);
}
__device__ __forceinline__ void mbar_init_1(uint32_t bar, uint32_t count) {
    asm volatile(ELECT "mbarrier.init.shared::cta.b64 [%0], %1;\n}" ::"r"(bar), "r"(count) : "memory");
}
__device__ __forceinline__ void mbar_expect_tx_1(uint32_t bar, uint32_t bytes) {
    asm volatile(ELECT "mbarrier.arrive.expect_tx.shared::cta.b64 _, [%0], %1;\n}" ::"r"(bar), "r"(bytes) : "memory");
}
__device__ __forceinline__ void mbar_arrive_1(uint32_t bar) {
    asm volatile(ELECT "mbarrier.arrive.shared::cta.b64 _, [%0];\n}" ::"r"(bar) : "memory");
}
__device__ __forceinline__ void mbar_wait(uint32_t bar, uint32_t parity) {
    uint32_t done;
    uint32_t spins = 0;
    do {
        asm volatile(
            "{\n.reg .pred p;\n"
            "mbarrier.try_wait.parity.shared::cta.b64 p, [%1], %2;\n"
            "selp.u32 %0, 1, 0, p;\n}"
            : "=r"(done) : "r"(bar), "r"(parity) : "memory");
    } while (!done && ++spins < SPIN_LIMIT);
    __syncwarp();
}
__device__ __forceinline__ bool mbar_test(uint32_t bar, uint32_t parity) {
    uint32_t done;
    asm volatile(
        "{\n.reg .pred p;\n"
        "mbarrier.test_wait.parity.shared::cta.b64 p, [%1], %2;\n"
        "selp.u32 %0, 1, 0, p;\n}"
        : "=r"(done) : "r"(bar), "r"(parity) : "memory");
    return __all_sync(0xffffffffu, done);
}
__device__ __forceinline__ void mbar_arrive_cta(uint32_t bar, uint32_t cta) {
    asm volatile(
        "{\n.reg .b32 ra;\n"
        "mapa.shared::cluster.u32 ra, %0, %1;\n"
        "mbarrier.arrive.shared::cluster.b64 _, [ra];\n}"
        ::"r"(bar), "r"(cta) : "memory");
}
__device__ __forceinline__ uint32_t lds32(uint32_t addr) {
    uint32_t v;
    asm volatile("ld.volatile.shared.b32 %0, [%1];" : "=r"(v) : "r"(addr) : "memory");
    return v;
}
__device__ __forceinline__ void sts32(uint32_t addr, uint32_t v) {
    asm volatile("st.volatile.shared.b32 [%0], %1;" ::"r"(addr), "r"(v) : "memory");
}
__device__ __forceinline__ uint32_t uniform(uint32_t v) {
    return __shfl_sync(0xffffffffu, v, 0);
}
__device__ __forceinline__ void tma_load_w_1(uint32_t dst, const CUtensorMap* map, uint32_t bar, int n) {
    asm volatile(
        ELECT "cp.async.bulk.tensor.3d.shared::cluster.global.mbarrier::complete_tx::bytes [%0], [%1, {%3, %4, %4}], [%2];\n}"
        ::"r"(dst), "l"(map), "r"(bar), "r"(n), "r"(0) : "memory");
}
__device__ __forceinline__ void tma_load_x_1(uint32_t dst, const CUtensorMap* map, uint32_t bar, int group) {
    asm volatile(
        ELECT "cp.async.bulk.tensor.4d.shared::cluster.global.mbarrier::complete_tx::bytes.multicast::cluster"
        " [%0], [%1, {%3, %3, %3, %4}], [%2], %5;\n}"
        ::"r"(dst), "l"(map), "r"(bar), "r"(0), "r"(group), "h"((uint16_t)3) : "memory");
}
__device__ __forceinline__ void tma_load_x_evict_first_1(uint32_t dst, const CUtensorMap* map, uint32_t bar, int group) {
    asm volatile(
        "{\n.reg .b64 pol;\n"
        "createpolicy.fractional.L2::evict_first.b64 pol, 1.0;\n"
        ELECT "cp.async.bulk.tensor.4d.shared::cluster.global.mbarrier::complete_tx::bytes.multicast::cluster.L2::cache_hint"
        " [%0], [%1, {%3, %3, %3, %4}], [%2], %5, pol;\n}\n}"
        ::"r"(dst), "l"(map), "r"(bar), "r"(0), "r"(group), "h"((uint16_t)3) : "memory");
}
__device__ __forceinline__ void tma_store_1(const CUtensorMap* map, uint32_t src, int ch, int pix) {
    asm volatile(
        ELECT "cp.async.bulk.tensor.2d.global.shared::cta.bulk_group [%0, {%2, %3}], [%1];\n}\n"
        "cp.async.bulk.commit_group;"
        ::"l"(map), "r"(src), "r"(ch), "r"(pix) : "memory");
}
template <int N>
__device__ __forceinline__ void stores_read_wait() {
    asm volatile("cp.async.bulk.wait_group.read %0;" ::"n"(N) : "memory");
}
__device__ __forceinline__ void prefetch_map_1(const CUtensorMap* map) {
    asm volatile(ELECT "prefetch.tensormap [%0];\n}" ::"l"(map) : "memory");
}
__device__ __forceinline__ void prefetch_l2(const void* p) {
    asm volatile("prefetch.global.L2 [%0];" ::"l"(p) : "memory");
}
__device__ __forceinline__ uint32_t timer_ns() {
    uint32_t t;
    asm volatile("mov.u32 %0, %%globaltimer_lo;" : "=r"(t)::"memory");
    return t;
}
__device__ __forceinline__ bool reached(uint32_t now, uint32_t t) {
    return (int32_t)(now - t) >= 0;
}
__device__ __forceinline__ void cluster_arrive() {
    asm volatile("barrier.cluster.arrive.relaxed.aligned;" ::: "memory");
}
__device__ __forceinline__ void cluster_wait() {
    asm volatile("barrier.cluster.wait.aligned;" ::: "memory");
}
__device__ __forceinline__ void publish_barriers() {
    asm volatile("fence.mbarrier_init.release.cluster;" ::: "memory");
    asm volatile("fence.proxy.async.shared::cta;" ::: "memory");
}

__device__ __forceinline__ void wgmma_rs_n64(float (&d)[32], const uint32_t* a, uint64_t desc, int scale_d) {
    asm volatile(
        "{\n.reg .pred p;\n"
        "setp.ne.b32 p, %37, 0;\n"
        "wgmma.mma_async.sync.aligned.m64n64k16.f32.bf16.bf16 "
        "{%0, %1, %2, %3, %4, %5, %6, %7, %8, %9, %10, %11, %12, %13, %14, %15, "
        "%16, %17, %18, %19, %20, %21, %22, %23, %24, %25, %26, %27, %28, %29, %30, %31}, "
        "{%32, %33, %34, %35}, %36, p, 1, 1, 0;\n}"
        : "+f"(d[0]), "+f"(d[1]), "+f"(d[2]), "+f"(d[3]), "+f"(d[4]), "+f"(d[5]), "+f"(d[6]), "+f"(d[7]),
          "+f"(d[8]), "+f"(d[9]), "+f"(d[10]), "+f"(d[11]), "+f"(d[12]), "+f"(d[13]), "+f"(d[14]), "+f"(d[15]),
          "+f"(d[16]), "+f"(d[17]), "+f"(d[18]), "+f"(d[19]), "+f"(d[20]), "+f"(d[21]), "+f"(d[22]), "+f"(d[23]),
          "+f"(d[24]), "+f"(d[25]), "+f"(d[26]), "+f"(d[27]), "+f"(d[28]), "+f"(d[29]), "+f"(d[30]), "+f"(d[31])
        : "r"(a[0]), "r"(a[1]), "r"(a[2]), "r"(a[3]), "l"(desc), "r"(scale_d));
}

__device__ __forceinline__ uint32_t pack_bias(float lo, float hi, uint32_t bias2) {
    uint32_t r;
    asm("{\n.reg .b32 t;\n"
        "cvt.rn.bf16x2.f32 t, %2, %1;\n"
        "add.rn.bf16x2 %0, t, %3;\n}"
        : "=r"(r) : "f"(lo), "f"(hi), "r"(bias2));
    return r;
}

__device__ __forceinline__ int slice_channel(uint32_t rank, int wg) {
    return (wg * 2 + rank) * 64;
}
__device__ __forceinline__ uint32_t w_stage(int wg) {
    return (wg + 1) * STAGE_BYTES + (wg == 2 ? HALF_BYTES : 0);
}

struct Ring {
    uint32_t s, parity;
    __device__ __forceinline__ void advance() {
        if (++s == STAGES) {
            s = 0;
            parity ^= 1;
        }
    }
};

__device__ __forceinline__ void write_out(uint32_t wg_bars, uint32_t st_addr, const Ring& r, const uint32_t (&v)[16]) {
    mbar_wait(wg_bars + BAR_OFREE + r.s * 32, r.parity ^ 1);
    const uint32_t dst = st_addr + r.s * HALF_BYTES;
#pragma unroll
    for (int j = 0; j < 4; j++) {
        asm volatile("stmatrix.sync.aligned.m8n8.x4.trans.shared.b16 [%0], {%1, %2, %3, %4};"
                     ::"r"(dst + j * 2048), "r"(v[4 * j]), "r"(v[4 * j + 1]), "r"(v[4 * j + 2]), "r"(v[4 * j + 3]) : "memory");
    }
    asm volatile("fence.proxy.async.shared::cta;" ::: "memory");
    __syncwarp();
    mbar_arrive_1(wg_bars + BAR_OFULL + r.s * 32);
}

template <int N>
__device__ __forceinline__ void hand_back(uint32_t& open) {
    if (open != 0) {
        stores_read_wait<N>();
        mbar_arrive_1(open);
        open = 0;
    }
}

__global__ void __cluster_dims__(2, 1, 1) __launch_bounds__(THREADS, 1)
conv1x1_kernel(const uint8_t* __restrict__ x_raw,
               const uint8_t* __restrict__ w_raw,
               const uint16_t* __restrict__ bias,
               uint32_t num_tiles,
               uint32_t num_clusters,
               const __grid_constant__ Maps maps,
               const __grid_constant__ Tune tune) {
    const uint32_t t_entry = timer_ns();
    extern __shared__ uint8_t smem_raw[];
    const uint32_t smem = (smem_u32(smem_raw) + 1023u) & ~1023u;
    const uint32_t bars = smem + SMEM_BAR;

    if (threadIdx.x < PRE_W) {
        prefetch_l2(w_raw + (blockIdx.x % (W_LINES / PRE_W) * PRE_W + threadIdx.x) * 128);
    } else if (threadIdx.x >= 96 && threadIdx.x < 128) {
        prefetch_map_1(&maps.w);
        prefetch_map_1(&maps.x);
    }
    if (threadIdx.x < NUM_WG * 128) cluster_arrive();
    if (threadIdx.x >= 128 && threadIdx.x < 128 + PIECE_BYTES / 128) {
        const uint8_t* p = x_raw + (size_t)blockIdx.x * HALF_BYTES + (threadIdx.x - 128) * 128;
        const uint32_t wait = ((threadIdx.x - 128) >> 5) * PRE_DT;
        const uint32_t c0 = (uint32_t)clock();
        while ((uint32_t)clock() - c0 < wait) {}
        asm volatile("cp.async.ca.shared.global.L2::128B [%0], [%1], 4;" ::"r"(bars + SINK_AT + (threadIdx.x & 31) * 4), "l"(p) : "memory");
    }
    if (threadIdx.x == 0) TRV(0, 63, t_entry);

    const int warp = uniform(threadIdx.x >> 5);
    const int lane = threadIdx.x & 31;
    const uint32_t rank    = blockIdx.x & 1;
    const uint32_t cluster = blockIdx.x >> 1;

    if (warp < NUM_WG * 4) {
        asm volatile("setmaxnreg.inc.sync.aligned.u32 160;");
        const int wg = warp >> 2;
        const int wq = warp & 3;
        const uint32_t bias_lo = bias[slice_channel(rank, wg) + wq * 16 + (lane >> 2)] * 0x10001u;
        const uint32_t bias_hi = bias[slice_channel(rank, wg) + wq * 16 + (lane >> 2) + 8] * 0x10001u;

        cluster_wait();
        TRE(1 + wg, 63);
        mbar_wait(bars + BAR_W + 8 * wg, 0);
        TRE(4 + wg, 63);
        uint32_t wreg[96];
        {
            const int r = lane & 7, m = lane >> 3;
            const uint32_t base = smem + w_stage(wg) + ((m >> 1) * 8 + r) * 128 + (((2 * wq + (m & 1)) ^ r) << 4);
#pragma unroll
            for (int ks = 0; ks < 24; ks++) {
                asm volatile("ldmatrix.sync.aligned.m8n8.x4.trans.shared.b16 {%0, %1, %2, %3}, [%4];"
                             : "=r"(wreg[ks * 4 + 0]), "=r"(wreg[ks * 4 + 1]), "=r"(wreg[ks * 4 + 2]), "=r"(wreg[ks * 4 + 3])
                             : "r"(base + ks * 2048) : "memory");
            }
        }
        uint32_t dep = 0;
#pragma unroll
        for (int ks = 0; ks < 24; ks++) dep ^= wreg[ks * 4];
        dep = uniform(dep & (num_tiles >> 31));
        if (lane < 6 && wg < 2) mbar_arrive_cta(bars + BAR_EMPTY + 8 * (wg + 1) + dep, lane & 1);
        asm volatile("cp.async.wait_all;" ::: "memory");
        TRE(1 + wg, 60);

        const uint32_t wg_bars = bars + wg * 8;
        const uint32_t st_addr = smem + SMEM_OUT + wg * SLICE_BYTES + ((lane >> 4) * 8 + (lane & 7)) * 128 +
                                 (((2 * wq + ((lane >> 3) & 1)) ^ (lane & 7)) << 4);
        const uint64_t desc_base =
            (uint64_t)((smem & 0x3FFFF) >> 4) | ((uint64_t)1 << 16) | ((uint64_t)(6144 >> 4) << 32) | ((uint64_t)1 << 62);
        const int next_turn = 4 + (wg + 1) % NUM_WG;

        float acc[32];
        uint32_t packed[16];
        Ring r = {0, dep}, o = r;
        bool held = false;
        for (uint32_t i = 0, id = cluster; id < num_tiles; i++, id += num_clusters, r.advance()) {
            mbar_wait(bars + BAR_FULL + 8 * r.s, r.parity);
            if ((i | wg) != 0) asm volatile("bar.sync %0, 256;" ::"r"(4 + wg) : "memory");
            TRE(1 + wg * 2, i);
            const uint64_t desc = desc_base + (uint64_t)(r.s * (STAGE_BYTES >> 4));
            asm volatile("wgmma.fence.sync.aligned;" ::: "memory");
#pragma unroll
            for (int ks = 0; ks < 24; ks++) {
                wgmma_rs_n64(acc, &wreg[ks * 4], desc + (uint64_t)((ks >> 2) * 64 + (ks & 3) * 2), ks != 0);
                if (ks + 1 == HAND_AT) asm volatile("bar.arrive %0, 256;" ::"r"(next_turn) : "memory");
            }
            asm volatile("wgmma.commit_group.sync.aligned;" ::: "memory");
            asm volatile("wgmma.wait_group.sync.aligned 0;" ::: "memory");
#pragma unroll
            for (int j = 0; j < 32; j++) asm volatile("" : "+f"(acc[j])::"memory");
            TRE(2 + wg * 2, i);
            if (lane < 2) mbar_arrive_cta(bars + BAR_EMPTY + 8 * r.s, lane);

            if (held) write_out(wg_bars, st_addr, o, packed);
            o = r;
#pragma unroll
            for (int j = 0; j < 16; j++) packed[j] = pack_bias(acc[2 * j], acc[2 * j + 1], j & 1 ? bias_hi : bias_lo);
            held = !mbar_test(wg_bars + BAR_OFREE + o.s * 32, o.parity ^ 1);
            if (!held) write_out(wg_bars, st_addr, o, packed);
            TRE(8 + wg, i);
        }
        if (held) write_out(wg_bars, st_addr, o, packed);
        if (wg == 0) asm volatile("bar.sync 4, 256;" ::: "memory");
        TRE(1 + wg, 62);
    } else {
        asm volatile("setmaxnreg.dec.sync.aligned.u32 32;");
        if (warp == NUM_WG * 4) {
#pragma unroll
            for (int j = 0; j < NUM_WG; j++) mbar_init_1(bars + BAR_W + 8 * j, 1);
            publish_barriers();
            cluster_arrive();
#pragma unroll
            for (int j = 0; j < NUM_WG; j++) {
                mbar_expect_tx_1(bars + BAR_W + 8 * j, STAGE_BYTES);
                tma_load_w_1(smem + w_stage(j), &maps.w, bars + BAR_W + 8 * j, slice_channel(rank, j));
                if (j == 0) TR(2, 61);
            }
            cluster_wait();
            TR(0, 0);
            mbar_expect_tx_1(bars + BAR_FULL, STAGE_BYTES);
            tma_load_x_1(smem + rank * HALF_BYTES, &maps.x, bars + BAR_FULL, cluster * 8 + rank * 4);
            Ring r = {1, 0};
#pragma unroll 1
            for (uint32_t i = 1, id = cluster + num_clusters; id < num_tiles; i++, id += num_clusters, r.advance()) {
                mbar_wait(bars + BAR_EMPTY + 8 * r.s, r.parity ^ (r.s == 0));
                sts32(bars + ISSUED_AT, id);
                sts32(bars + STAMP_AT + 4 * r.s, timer_ns());
                TR(0, i);
                TRV(15, i, id);
                const uint32_t full = bars + BAR_FULL + 8 * r.s;
                const uint32_t dst = smem + r.s * STAGE_BYTES + rank * HALF_BYTES;
                mbar_expect_tx_1(full, STAGE_BYTES);
                if (id + tune.EF_TAIL < num_tiles) tma_load_x_1(dst, &maps.x, full, id * 8 + rank * 4);
                else tma_load_x_evict_first_1(dst, &maps.x, full, id * 8 + rank * 4);
            }
#pragma unroll 1
            for (int k = 0; k < STAGES; k++, r.advance()) mbar_wait(bars + BAR_EMPTY + 8 * r.s, r.parity ^ (r.s == 0));
        } else if (warp == NUM_WG * 4 + 1) {
#pragma unroll
            for (int s = 0; s < STAGES; s++) {
                mbar_init_1(bars + BAR_FULL + 8 * s, 1);
                mbar_init_1(bars + BAR_EMPTY + 8 * s, NUM_WG * 4 * 2);
            }
            publish_barriers();
            cluster_arrive();
            TR(0, 61);
            cluster_wait();
            prefetch_map_1(&maps.out);
            uint32_t delay = 0;
            Ring r = {0, 0};
#pragma unroll 1
            for (uint32_t i = 0, id = cluster; id < num_tiles; i++, id += num_clusters, r.advance()) {
                mbar_wait(bars + BAR_FULL + 8 * r.s, r.parity);
                TR(7, i);
                const int late = (int)(timer_ns() - lds32(bars + STAMP_AT + 4 * r.s) - tune.CC_L0);
                if (i >= tune.CC_AT && late > 0) {
                    delay = min(delay + min((uint32_t)late * tune.CC_G >> 4, tune.CC_STEP), tune.CC_CAP);
                    sts32(bars + DELAY_AT, delay);
                }
            }
        } else if (warp == NUM_WG * 4 + 2) {
            sts32(bars + DELAY_AT, 0);
#pragma unroll
            for (int b = 0; b < STAGES; b++) {
#pragma unroll
                for (int w = 0; w < NUM_WG; w++) {
                    mbar_init_1(bars + BAR_OFREE + b * 32 + w * 8, 1);
                    mbar_init_1(bars + BAR_OFULL + b * 32 + w * 8, 4);
                }
            }
            publish_barriers();
            cluster_arrive();
            cluster_wait();
            const uint32_t first = tune.ST_AT * num_clusters;
            const uint32_t n3 = max((int)(num_tiles - first - tune.ST_N1 - tune.ST_N2 - tune.ST_END), 0);
            auto release_time = [&](uint32_t id) {
                if (id < first) return t_entry;
                uint32_t rest = id - first, t = 0;
                auto segment = [&](uint32_t ids, uint32_t per_round) {
                    const uint32_t n = min(rest, ids);
                    t += n * per_round;
                    rest -= n;
                };
                segment(tune.ST_N1, tune.ST_S1);
                segment(tune.ST_N2, tune.ST_S2);
                segment(n3, tune.ST_S3);
                segment(tune.ST_N4, tune.ST_S4);
                segment(tune.ST_N5, tune.ST_S5);
                segment(tune.ST_END - tune.ST_N4 - tune.ST_N5 - tune.ST_N7, tune.ST_S6);
                return t_entry + tune.ST_T0 + t / num_clusters;
            };
            const uint32_t lane_full = bars + BAR_OFULL + min(lane, NUM_WG - 1) * 8;
            uint32_t open = 0, due = release_time(cluster);
            Ring o = {0, 0};
#pragma unroll 1
            for (uint32_t j = 0, id = cluster; id < num_tiles; j++, id += num_clusters, o.advance()) {
                const uint32_t obar = bars + o.s * 32;
                const uint32_t src = smem + SMEM_OUT + o.s * HALF_BYTES;
                bool whole;
#pragma unroll 1
                for (uint32_t spins = 0; spins < SPIN_LIMIT; spins++) {
                    const uint32_t delay = lds32(bars + DELAY_AT);
                    whole = mbar_test(lane_full + o.s * 32, o.parity);
                    if (reached(timer_ns(), due + uniform(delay))) break;
                    hand_back<0>(open);
                    __nanosleep(20);
                }
                if (whole) {
                    TR(11, j);
#pragma unroll
                    for (int w = 0; w < NUM_WG; w++) tma_store_1(&maps.out, src + w * SLICE_BYTES, slice_channel(rank, w), id * TILE_PIX);
                    due = release_time(id + num_clusters);
                    hand_back<3>(open);
                    stores_read_wait<2>();
                    TR(12, j);
                    mbar_arrive_1(obar + BAR_OFREE);
                    stores_read_wait<1>();
                    TR(13, j);
                    mbar_arrive_1(obar + BAR_OFREE + 8);
                    open = obar + BAR_OFREE + 16;
                } else {
#pragma unroll 1
                    for (uint32_t w = 0; w < NUM_WG; w++) {
                        if (!mbar_test(obar + BAR_OFULL + w * 8, o.parity)) {
                            hand_back<0>(open);
                            mbar_wait(obar + BAR_OFULL + w * 8, o.parity);
                        }
                        TR(11 + w, j);
                        tma_store_1(&maps.out, src + w * SLICE_BYTES, slice_channel(rank, w), id * TILE_PIX);
                        hand_back<1>(open);
                        open = obar + BAR_OFREE + w * 8;
                    }
                    due = release_time(id + num_clusters);
                }
            }
            stores_read_wait<0>();
            TR(4, 62);
            TRV(6, 62, lds32(bars + DELAY_AT));
        } else {
            sts32(bars + ISSUED_AT, 0);
            cluster_arrive();
            uint32_t due = t_entry + tune.PM_T0 + (blockIdx.x & 3) * tune.PM_STAG;
            const uint32_t step = num_clusters / 2;
#pragma unroll 1
            for (uint32_t piece = 1;; piece++) {
                const uint32_t t = cluster + piece / 2 * num_clusters;
                if (t >= num_tiles) break;
                const bool last = t + tune.LEAD_T >= num_tiles;
                uint32_t now;
#pragma unroll 1
                for (uint32_t spins = 0; spins < 16384; spins++) {
                    const uint32_t issued = uniform(lds32(bars + ISSUED_AT));
                    now = timer_ns();
                    const int lead = max((int)(last ? tune.LEAD_C : tune.LEAD_B), (int)tune.LEAD_A - (max((int)issued - (int)tune.LEAD_F, 0) * (int)tune.LEAD_S >> 4));
                    if (reached(now, due)) {
                        if (cluster + piece * step <= issued + lead) break;
                        due = now;
                    }
                    __nanosleep(20);
                }
                if (reached(now - tune.PM_SLACK, due)) due = now - tune.PM_SLACK;
                due += piece < tune.PM_E1 ? tune.PM_DT1 : piece < tune.PM_E2 ? tune.PM_DT2 : last ? tune.PM_DT4 : tune.PM_DT3;
                const uint8_t* p = x_raw + (size_t)t * STAGE_BYTES + rank * HALF_BYTES + (piece % 2) * PIECE_BYTES + lane * 128;
#pragma unroll
                for (int k = 0; k < PIECE_BYTES / 4096; k++) prefetch_l2(p + k * 4096);
                if (piece % 2 == 0) TR(14, piece / 2);
            }
            cluster_wait();
        }
    }
}

typedef CUresult (*EncodeTiledFn)(CUtensorMap*, CUtensorMapDataType, cuuint32_t, void*, const cuuint64_t*,
                                  const cuuint64_t*, const cuuint32_t*, const cuuint32_t*, CUtensorMapInterleave,
                                  CUtensorMapSwizzle, CUtensorMapL2promotion, CUtensorMapFloatOOBfill);

}

extern "C" void kernel_launch(void* const* d_in, const int* in_sizes, int n_in, void* d_out, int out_size) {
    (void)n_in;
    (void)out_size;
    void* x = d_in[0];
    void* w = d_in[1];
    const uint16_t* b = (const uint16_t*)d_in[2];
    const int M = in_sizes[0] / C;
    const int num_tiles = M / TILE_PIX;

    static EncodeTiledFn encode = nullptr;
    static int sms = 0;
    if (!encode) {
        void* fn = nullptr;
        cudaDriverEntryPointQueryResult q;
        cudaGetDriverEntryPoint("cuTensorMapEncodeTiled", &fn, cudaEnableDefault, &q);
        encode = (EncodeTiledFn)fn;
        cudaDeviceGetAttribute(&sms, cudaDevAttrMultiProcessorCount, 0);
        cudaFuncSetAttribute(conv1x1_kernel, cudaFuncAttributeMaxDynamicSharedMemorySize, SMEM_TOTAL);
    }

    Maps maps;
    const cuuint32_t ones[4] = {1, 1, 1, 1};
    auto make = [&](CUtensorMap* map, int rank, void* base, const cuuint64_t* dims, const cuuint64_t* strides,
                    const cuuint32_t* box, CUtensorMapL2promotion promo) {
        encode(map, CU_TENSOR_MAP_DATA_TYPE_BFLOAT16, rank, base, dims, strides, box, ones, CU_TENSOR_MAP_INTERLEAVE_NONE,
               CU_TENSOR_MAP_SWIZZLE_128B, promo, CU_TENSOR_MAP_FLOAT_OOB_FILL_NONE);
    };
    {
        const cuuint64_t dims[4]    = {64, 8, 6, (cuuint64_t)(M / 8)};
        const cuuint64_t strides[3] = {C * 2, 128, 8 * C * 2};
        const cuuint32_t box[4]     = {64, 8, 6, TILE_PIX / 16};
        make(&maps.x, 4, x, dims, strides, box, CU_TENSOR_MAP_L2_PROMOTION_L2_128B);
    }
    {
        const cuuint64_t dims[3]    = {C, C / 2, 2};
        const cuuint64_t strides[2] = {C * 2, C * C};
        const cuuint32_t box[3]     = {64, C / 2, 2};
        make(&maps.w, 3, w, dims, strides, box, CU_TENSOR_MAP_L2_PROMOTION_L2_128B);
    }
    {
        const cuuint64_t dims[2]    = {C, (cuuint64_t)M};
        const cuuint64_t strides[1] = {C * 2};
        const cuuint32_t box[2]     = {64, TILE_PIX};
        make(&maps.out, 2, d_out, dims, strides, box, CU_TENSOR_MAP_L2_PROMOTION_NONE);
    }

    const Tune tune;
    int clusters = sms / 2;
    if (clusters > num_tiles) clusters = num_tiles;
    conv1x1_kernel<<<clusters * 2, THREADS, SMEM_TOTAL>>>((const uint8_t*)x, (const uint8_t*)w, b, (uint32_t)num_tiles,
                                                          (uint32_t)clusters, maps, tune);
}
```

```cpp
#include <cuda_runtime.h>
#include <cuda_bf16.h>
#include <cuda.h>
#include <stdint.h>

#define TUNABLES(F) \
    F(PM_T0, 350)        \
    F(PM_STAG, 90)       \
    F(PM_DT1, 415)       \
    F(PM_E1, 7) \
    F(PM_DT2, 475) \
    F(PM_E2, 23) \
    F(PM_DT3, 860) \
    F(PM_SLACK, 500)     \
    F(LEAD_A, 269)       \
    F(LEAD_F, 550)       \
    F(LEAD_S, 3)         \
    F(LEAD_B, 151)       \
    F(LEAD_T, 264)       \
    F(LEAD_C, 170)       \
    F(PM_DT4, 700)       \
    F(EF_TAIL, 500)      \
    F(ST_AT, 2)          \
    F(ST_T0, 6830)       \
    F(ST_S1, 2040)       \
    F(ST_N1, 448) \
    F(ST_S2, 1860) \
    F(ST_N2, 594) \
    F(ST_S3, 1970)       \
    F(ST_END, 613) \
    F(ST_S4, 1500)       \
    F(ST_N4, 100) \
    F(ST_S5, 1100) \
    F(ST_N5, 85) \
    F(ST_S6, 950) \
    F(ST_N7, 22)         \
    F(SE_TAIL, 400)      \
    F(CC_AT, 22)         \
    F(CC_L0, 1300)       \
    F(CC_CAP, 1330)

struct Tune {
#define F(n, v) uint32_t n = v;
    TUNABLES(F)
#undef F
};

#define TRV(slot, idx, v)
#define TR(slot, idx)
#define TRE(slot, idx)
#define TRACE_BYTES 0

namespace {

constexpr int C            = 384;
constexpr int TILE_PIX     = 64;
constexpr int STAGES       = 3;
constexpr int STAGE_BYTES  = TILE_PIX * C * 2;
constexpr int HALF_BYTES   = STAGE_BYTES / 2;
constexpr int PIECE_BYTES  = HALF_BYTES / 2;
constexpr int SLICE_BYTES  = TILE_PIX * 128;
constexpr int NUM_WG       = 3;
constexpr int THREADS      = (NUM_WG + 1) * 128;
constexpr int SMEM_OUT     = STAGES * STAGE_BYTES;
constexpr int SMEM_BAR     = SMEM_OUT + STAGES * HALF_BYTES;
constexpr int SMEM_TOTAL   = SMEM_BAR + 512 + TRACE_BYTES + 1024;
constexpr int HAND_AT      = 18;
constexpr int W_LINES      = C * C * 2 / 128;
constexpr int PRE_W        = 64;
constexpr int PRE_DT       = 330;
constexpr uint32_t SPIN_LIMIT = 1u << 22;
constexpr int BAR_W     = 0;
constexpr int BAR_FULL  = 32;
constexpr int BAR_EMPTY = 64;
constexpr int BAR_OFREE = 96;
constexpr int BAR_OFULL = BAR_OFREE + 32 * STAGES;
constexpr int ISSUED_AT = BAR_OFULL + 32 * STAGES;
constexpr int DELAY_AT  = ISSUED_AT + 4;
constexpr int STAMP_AT  = DELAY_AT + 4;
constexpr int SINK_AT   = 384;

struct Maps {
    CUtensorMap w, x, out;
};

#define ELECT "{\n.reg .pred e;\nelect.sync _|e, 0xffffffff;\n@e "

__device__ __forceinline__ uint32_t smem_u32(const void* p) {
    return (uint32_t)__cvta_generic_to_shared(p);
}
__device__ __forceinline__ void mbar_init_1(uint32_t bar, uint32_t count) {
    asm volatile(ELECT "mbarrier.init.shared::cta.b64 [%0], %1;\n}" ::"r"(bar), "r"(count) : "memory");
}
__device__ __forceinline__ void mbar_expect_tx_1(uint32_t bar, uint32_t bytes) {
    asm volatile(ELECT "mbarrier.arrive.expect_tx.shared::cta.b64 _, [%0], %1;\n}" ::"r"(bar), "r"(bytes) : "memory");
}
__device__ __forceinline__ void mbar_arrive_1(uint32_t bar) {
    asm volatile(ELECT "mbarrier.arrive.shared::cta.b64 _, [%0];\n}" ::"r"(bar) : "memory");
}
__device__ __forceinline__ void mbar_wait(uint32_t bar, uint32_t parity) {
    uint32_t done;
    uint32_t spins = 0;
    do {
        asm volatile(
            "{\n.reg .pred p;\n"
            "mbarrier.try_wait.parity.shared::cta.b64 p, [%1], %2;\n"
            "selp.u32 %0, 1, 0, p;\n}"
            : "=r"(done) : "r"(bar), "r"(parity) : "memory");
    } while (!done && ++spins < SPIN_LIMIT);
    __syncwarp();
}
__device__ __forceinline__ bool mbar_test(uint32_t bar, uint32_t parity) {
    uint32_t done;
    asm volatile(
        "{\n.reg .pred p;\n"
        "mbarrier.test_wait.parity.shared::cta.b64 p, [%1], %2;\n"
        "selp.u32 %0, 1, 0, p;\n}"
        : "=r"(done) : "r"(bar), "r"(parity) : "memory");
    return __all_sync(0xffffffffu, done);
}
__device__ __forceinline__ void mbar_arrive_cta(uint32_t bar, uint32_t cta) {
    asm volatile(
        "{\n.reg .b32 ra;\n"
        "mapa.shared::cluster.u32 ra, %0, %1;\n"
        "mbarrier.arrive.shared::cluster.b64 _, [ra];\n}"
        ::"r"(bar), "r"(cta) : "memory");
}
__device__ __forceinline__ uint32_t lds32(uint32_t addr) {
    uint32_t v;
    asm volatile("ld.volatile.shared.b32 %0, [%1];" : "=r"(v) : "r"(addr) : "memory");
    return v;
}
__device__ __forceinline__ void sts32(uint32_t addr, uint32_t v) {
    asm volatile("st.volatile.shared.b32 [%0], %1;" ::"r"(addr), "r"(v) : "memory");
}
__device__ __forceinline__ uint32_t uniform(uint32_t v) {
    return __shfl_sync(0xffffffffu, v, 0);
}
__device__ __forceinline__ void tma_load_w_1(uint32_t dst, const CUtensorMap* map, uint32_t bar, int n) {
    asm volatile(
        ELECT "cp.async.bulk.tensor.3d.shared::cluster.global.mbarrier::complete_tx::bytes [%0], [%1, {%3, %4, %4}], [%2];\n}"
        ::"r"(dst), "l"(map), "r"(bar), "r"(n), "r"(0) : "memory");
}
__device__ __forceinline__ void tma_load_x_1(uint32_t dst, const CUtensorMap* map, uint32_t bar, int group) {
    asm volatile(
        ELECT "cp.async.bulk.tensor.4d.shared::cluster.global.mbarrier::complete_tx::bytes.multicast::cluster"
        " [%0], [%1, {%3, %3, %3, %4}], [%2], %5;\n}"
        ::"r"(dst), "l"(map), "r"(bar), "r"(0), "r"(group), "h"((uint16_t)3) : "memory");
}
__device__ __forceinline__ void tma_load_x_evict_first_1(uint32_t dst, const CUtensorMap* map, uint32_t bar, int group) {
    asm volatile(
        "{\n.reg .b64 pol;\n"
        "createpolicy.fractional.L2::evict_first.b64 pol, 1.0;\n"
        ELECT "cp.async.bulk.tensor.4d.shared::cluster.global.mbarrier::complete_tx::bytes.multicast::cluster.L2::cache_hint"
        " [%0], [%1, {%3, %3, %3, %4}], [%2], %5, pol;\n}\n}"
        ::"r"(dst), "l"(map), "r"(bar), "r"(0), "r"(group), "h"((uint16_t)3) : "memory");
}
__device__ __forceinline__ void tma_store_1(const CUtensorMap* map, uint32_t src, int ch, int pix) {
    asm volatile(
        ELECT "cp.async.bulk.tensor.2d.global.shared::cta.bulk_group [%0, {%2, %3}], [%1];\n}\n"
        "cp.async.bulk.commit_group;"
        ::"l"(map), "r"(src), "r"(ch), "r"(pix) : "memory");
}
__device__ __forceinline__ void tma_store_evict_first_1(const CUtensorMap* map, uint32_t src, int ch, int pix) {
    asm volatile(
        "{\n.reg .b64 pol;\n"
        "createpolicy.fractional.L2::evict_first.b64 pol, 1.0;\n"
        ELECT "cp.async.bulk.tensor.2d.global.shared::cta.bulk_group.L2::cache_hint [%0, {%2, %3}], [%1], pol;\n}\n}\n"
        "cp.async.bulk.commit_group;"
        ::"l"(map), "r"(src), "r"(ch), "r"(pix) : "memory");
}
template <int N>
__device__ __forceinline__ void stores_read_wait() {
    asm volatile("cp.async.bulk.wait_group.read %0;" ::"n"(N) : "memory");
}
__device__ __forceinline__ void prefetch_map_1(const CUtensorMap* map) {
    asm volatile(ELECT "prefetch.tensormap [%0];\n}" ::"l"(map) : "memory");
}
__device__ __forceinline__ void prefetch_l2(const void* p) {
    asm volatile("prefetch.global.L2 [%0];" ::"l"(p) : "memory");
}
__device__ __forceinline__ uint32_t timer_ns() {
    uint32_t t;
    asm volatile("mov.u32 %0, %%globaltimer_lo;" : "=r"(t)::"memory");
    return t;
}
__device__ __forceinline__ bool reached(uint32_t now, uint32_t t) {
    return (int32_t)(now - t) >= 0;
}
__device__ __forceinline__ void cluster_arrive() {
    asm volatile("barrier.cluster.arrive.relaxed.aligned;" ::: "memory");
}
__device__ __forceinline__ void cluster_wait() {
    asm volatile("barrier.cluster.wait.aligned;" ::: "memory");
}
__device__ __forceinline__ void publish_barriers() {
    asm volatile("fence.mbarrier_init.release.cluster;" ::: "memory");
    asm volatile("fence.proxy.async.shared::cta;" ::: "memory");
}

__device__ __forceinline__ void wgmma_rs_n64(float (&d)[32], const uint32_t* a, uint64_t desc, int scale_d) {
    asm volatile(
        "{\n.reg .pred p;\n"
        "setp.ne.b32 p, %37, 0;\n"
        "wgmma.mma_async.sync.aligned.m64n64k16.f32.bf16.bf16 "
        "{%0, %1, %2, %3, %4, %5, %6, %7, %8, %9, %10, %11, %12, %13, %14, %15, "
        "%16, %17, %18, %19, %20, %21, %22, %23, %24, %25, %26, %27, %28, %29, %30, %31}, "
        "{%32, %33, %34, %35}, %36, p, 1, 1, 0;\n}"
        : "+f"(d[0]), "+f"(d[1]), "+f"(d[2]), "+f"(d[3]), "+f"(d[4]), "+f"(d[5]), "+f"(d[6]), "+f"(d[7]),
          "+f"(d[8]), "+f"(d[9]), "+f"(d[10]), "+f"(d[11]), "+f"(d[12]), "+f"(d[13]), "+f"(d[14]), "+f"(d[15]),
          "+f"(d[16]), "+f"(d[17]), "+f"(d[18]), "+f"(d[19]), "+f"(d[20]), "+f"(d[21]), "+f"(d[22]), "+f"(d[23]),
          "+f"(d[24]), "+f"(d[25]), "+f"(d[26]), "+f"(d[27]), "+f"(d[28]), "+f"(d[29]), "+f"(d[30]), "+f"(d[31])
        : "r"(a[0]), "r"(a[1]), "r"(a[2]), "r"(a[3]), "l"(desc), "r"(scale_d));
}

__device__ __forceinline__ uint32_t pack_bias(float lo, float hi, uint32_t bias2) {
    uint32_t r;
    asm("{\n.reg .b32 t;\n"
        "cvt.rn.bf16x2.f32 t, %2, %1;\n"
        "add.rn.bf16x2 %0, t, %3;\n}"
        : "=r"(r) : "f"(lo), "f"(hi), "r"(bias2));
    return r;
}

__device__ __forceinline__ int slice_channel(uint32_t rank, int wg) {
    return (wg * 2 + rank) * 64;
}
__device__ __forceinline__ uint32_t w_stage(int wg) {
    return (wg + 1) * STAGE_BYTES + (wg == 2 ? HALF_BYTES : 0);
}

struct Ring {
    uint32_t s, parity;
    __device__ __forceinline__ void advance() {
        if (++s == STAGES) {
            s = 0;
            parity ^= 1;
        }
    }
};

__device__ __forceinline__ void write_out(uint32_t wg_bars, uint32_t st_addr, const Ring& r, const uint32_t (&v)[16]) {
    mbar_wait(wg_bars + BAR_OFREE + r.s * 32, r.parity ^ 1);
    const uint32_t dst = st_addr + r.s * HALF_BYTES;
#pragma unroll
    for (int j = 0; j < 4; j++) {
        asm volatile("stmatrix.sync.aligned.m8n8.x4.trans.shared.b16 [%0], {%1, %2, %3, %4};"
                     ::"r"(dst + j * 2048), "r"(v[4 * j]), "r"(v[4 * j + 1]), "r"(v[4 * j + 2]), "r"(v[4 * j + 3]) : "memory");
    }
    asm volatile("fence.proxy.async.shared::cta;" ::: "memory");
    __syncwarp();
    mbar_arrive_1(wg_bars + BAR_OFULL + r.s * 32);
}

template <int N>
__device__ __forceinline__ void hand_back(uint32_t& open) {
    if (open != 0) {
        stores_read_wait<N>();
        mbar_arrive_1(open);
        open = 0;
    }
}

__global__ void __cluster_dims__(2, 1, 1) __launch_bounds__(THREADS, 1)
conv1x1_kernel(const uint8_t* __restrict__ x_raw,
               const uint8_t* __restrict__ w_raw,
               const uint16_t* __restrict__ bias,
               uint32_t num_tiles,
               uint32_t num_clusters,
               const __grid_constant__ Maps maps,
               const __grid_constant__ Tune tune) {
    const uint32_t t_entry = timer_ns();
    extern __shared__ uint8_t smem_raw[];
    const uint32_t smem = (smem_u32(smem_raw) + 1023u) & ~1023u;
    const uint32_t bars = smem + SMEM_BAR;

    if (threadIdx.x < PRE_W) {
        prefetch_l2(w_raw + (blockIdx.x % (W_LINES / PRE_W) * PRE_W + threadIdx.x) * 128);
    } else if (threadIdx.x >= 96 && threadIdx.x < 128) {
        prefetch_map_1(&maps.w);
        prefetch_map_1(&maps.x);
    }
    if (threadIdx.x < NUM_WG * 128) cluster_arrive();
    if (threadIdx.x >= 128 && threadIdx.x < 128 + PIECE_BYTES / 128) {
        const uint8_t* p = x_raw + (size_t)blockIdx.x * HALF_BYTES + (threadIdx.x - 128) * 128;
        const uint32_t wait = ((threadIdx.x - 128) >> 5) * PRE_DT;
        const uint32_t c0 = (uint32_t)clock();
        while ((uint32_t)clock() - c0 < wait) {}
        asm volatile("cp.async.ca.shared.global.L2::128B [%0], [%1], 4;" ::"r"(bars + SINK_AT + (threadIdx.x & 31) * 4), "l"(p) : "memory");
    }
    if (threadIdx.x == 0) TRV(0, 63, t_entry);

    const int warp = uniform(threadIdx.x >> 5);
    const int lane = threadIdx.x & 31;
    const uint32_t rank    = blockIdx.x & 1;
    const uint32_t cluster = blockIdx.x >> 1;

    if (warp < NUM_WG * 4) {
        asm volatile("setmaxnreg.inc.sync.aligned.u32 160;");
        const int wg = warp >> 2;
        const int wq = warp & 3;
        const uint32_t bias_lo = bias[slice_channel(rank, wg) + wq * 16 + (lane >> 2)] * 0x10001u;
        const uint32_t bias_hi = bias[slice_channel(rank, wg) + wq * 16 + (lane >> 2) + 8] * 0x10001u;

        cluster_wait();
        TRE(1 + wg, 63);
        mbar_wait(bars + BAR_W + 8 * wg, 0);
        TRE(4 + wg, 63);
        uint32_t wreg[96];
        {
            const int r = lane & 7, m = lane >> 3;
            const uint32_t base = smem + w_stage(wg) + ((m >> 1) * 8 + r) * 128 + (((2 * wq + (m & 1)) ^ r) << 4);
#pragma unroll
            for (int ks = 0; ks < 24; ks++) {
                asm volatile("ldmatrix.sync.aligned.m8n8.x4.trans.shared.b16 {%0, %1, %2, %3}, [%4];"
                             : "=r"(wreg[ks * 4 + 0]), "=r"(wreg[ks * 4 + 1]), "=r"(wreg[ks * 4 + 2]), "=r"(wreg[ks * 4 + 3])
                             : "r"(base + ks * 2048) : "memory");
            }
        }
        uint32_t dep = 0;
#pragma unroll
        for (int ks = 0; ks < 24; ks++) dep ^= wreg[ks * 4];
        dep = uniform(dep & (num_tiles >> 31));
        if (lane < 6 && wg < 2) mbar_arrive_cta(bars + BAR_EMPTY + 8 * (wg + 1) + dep, lane & 1);
        asm volatile("cp.async.wait_all;" ::: "memory");
        TRE(1 + wg, 60);

        const uint32_t wg_bars = bars + wg * 8;
        const uint32_t st_addr = smem + SMEM_OUT + wg * SLICE_BYTES + ((lane >> 4) * 8 + (lane & 7)) * 128 +
                                 (((2 * wq + ((lane >> 3) & 1)) ^ (lane & 7)) << 4);
        const uint64_t desc_base =
            (uint64_t)((smem & 0x3FFFF) >> 4) | ((uint64_t)1 << 16) | ((uint64_t)(6144 >> 4) << 32) | ((uint64_t)1 << 62);
        const int next_turn = 4 + (wg + 1) % NUM_WG;

        float acc[32];
        uint32_t packed[16];
        Ring r = {0, dep}, o = r;
        bool held = false;
        for (uint32_t i = 0, id = cluster; id < num_tiles; i++, id += num_clusters, r.advance()) {
            mbar_wait(bars + BAR_FULL + 8 * r.s, r.parity);
            if ((i | wg) != 0) asm volatile("bar.sync %0, 256;" ::"r"(4 + wg) : "memory");
            TRE(1 + wg * 2, i);
            const uint64_t desc = desc_base + (uint64_t)(r.s * (STAGE_BYTES >> 4));
            asm volatile("wgmma.fence.sync.aligned;" ::: "memory");
#pragma unroll
            for (int ks = 0; ks < 24; ks++) {
                wgmma_rs_n64(acc, &wreg[ks * 4], desc + (uint64_t)((ks >> 2) * 64 + (ks & 3) * 2), ks != 0);
                if (ks + 1 == HAND_AT) asm volatile("bar.arrive %0, 256;" ::"r"(next_turn) : "memory");
            }
            asm volatile("wgmma.commit_group.sync.aligned;" ::: "memory");
            asm volatile("wgmma.wait_group.sync.aligned 0;" ::: "memory");
#pragma unroll
            for (int j = 0; j < 32; j++) asm volatile("" : "+f"(acc[j])::"memory");
            TRE(2 + wg * 2, i);
            if (lane < 2) mbar_arrive_cta(bars + BAR_EMPTY + 8 * r.s, lane);

            if (held) write_out(wg_bars, st_addr, o, packed);
            o = r;
#pragma unroll
            for (int j = 0; j < 16; j++) packed[j] = pack_bias(acc[2 * j], acc[2 * j + 1], j & 1 ? bias_hi : bias_lo);
            held = !mbar_test(wg_bars + BAR_OFREE + o.s * 32, o.parity ^ 1);
            if (!held) write_out(wg_bars, st_addr, o, packed);
            TRE(8 + wg, i);
        }
        if (held) write_out(wg_bars, st_addr, o, packed);
        if (wg == 0) asm volatile("bar.sync 4, 256;" ::: "memory");
        TRE(1 + wg, 62);
    } else {
        asm volatile("setmaxnreg.dec.sync.aligned.u32 32;");
        if (warp == NUM_WG * 4) {
#pragma unroll
            for (int j = 0; j < NUM_WG; j++) mbar_init_1(bars + BAR_W + 8 * j, 1);
            publish_barriers();
            cluster_arrive();
#pragma unroll
            for (int j = 0; j < NUM_WG; j++) {
                mbar_expect_tx_1(bars + BAR_W + 8 * j, STAGE_BYTES);
                tma_load_w_1(smem + w_stage(j), &maps.w, bars + BAR_W + 8 * j, slice_channel(rank, j));
                if (j == 0) TR(2, 61);
            }
            cluster_wait();
            TR(0, 0);
            mbar_expect_tx_1(bars + BAR_FULL, STAGE_BYTES);
            tma_load_x_1(smem + rank * HALF_BYTES, &maps.x, bars + BAR_FULL, cluster * 8 + rank * 4);
            Ring r = {1, 0};
#pragma unroll 1
            for (uint32_t i = 1, id = cluster + num_clusters; id < num_tiles; i++, id += num_clusters, r.advance()) {
                mbar_wait(bars + BAR_EMPTY + 8 * r.s, r.parity ^ (r.s == 0));
                sts32(bars + ISSUED_AT, id);
                sts32(bars + STAMP_AT + 4 * r.s, timer_ns());
                TR(0, i);
                TRV(15, i, id);
                const uint32_t full = bars + BAR_FULL + 8 * r.s;
                const uint32_t dst = smem + r.s * STAGE_BYTES + rank * HALF_BYTES;
                mbar_expect_tx_1(full, STAGE_BYTES);
                if (id + tune.EF_TAIL < num_tiles) tma_load_x_1(dst, &maps.x, full, id * 8 + rank * 4);
                else tma_load_x_evict_first_1(dst, &maps.x, full, id * 8 + rank * 4);
            }
#pragma unroll 1
            for (int k = 0; k < STAGES; k++, r.advance()) mbar_wait(bars + BAR_EMPTY + 8 * r.s, r.parity ^ (r.s == 0));
        } else if (warp == NUM_WG * 4 + 1) {
#pragma unroll
            for (int s = 0; s < STAGES; s++) {
                mbar_init_1(bars + BAR_FULL + 8 * s, 1);
                mbar_init_1(bars + BAR_EMPTY + 8 * s, NUM_WG * 4 * 2);
            }
            publish_barriers();
            cluster_arrive();
            TR(0, 61);
            cluster_wait();
            prefetch_map_1(&maps.out);
            uint32_t delay = 0;
            Ring r = {0, 0};
#pragma unroll 1
            for (uint32_t i = 0, id = cluster; id < num_tiles; i++, id += num_clusters, r.advance()) {
                mbar_wait(bars + BAR_FULL + 8 * r.s, r.parity);
                TR(7, i);
                const int late = (int)(timer_ns() - lds32(bars + STAMP_AT + 4 * r.s) - tune.CC_L0);
                if (i >= tune.CC_AT && late > 0) {
                    delay = min(delay + late, tune.CC_CAP);
                    sts32(bars + DELAY_AT, delay);
                }
            }
        } else if (warp == NUM_WG * 4 + 2) {
            sts32(bars + DELAY_AT, 0);
#pragma unroll
            for (int b = 0; b < STAGES; b++) {
#pragma unroll
                for (int w = 0; w < NUM_WG; w++) {
                    mbar_init_1(bars + BAR_OFREE + b * 32 + w * 8, 1);
                    mbar_init_1(bars + BAR_OFULL + b * 32 + w * 8, 4);
                }
            }
            publish_barriers();
            cluster_arrive();
            cluster_wait();
            const uint32_t first = tune.ST_AT * num_clusters;
            const uint32_t n3 = max((int)(num_tiles - first - tune.ST_N1 - tune.ST_N2 - tune.ST_END), 0);
            auto release_time = [&](uint32_t id) {
                if (id < first) return t_entry;
                uint32_t rest = id - first, t = 0;
                auto segment = [&](uint32_t ids, uint32_t per_round) {
                    const uint32_t n = min(rest, ids);
                    t += n * per_round;
                    rest -= n;
                };
                segment(tune.ST_N1, tune.ST_S1);
                segment(tune.ST_N2, tune.ST_S2);
                segment(n3, tune.ST_S3);
                segment(tune.ST_N4, tune.ST_S4);
                segment(tune.ST_N5, tune.ST_S5);
                segment(tune.ST_END - tune.ST_N4 - tune.ST_N5 - tune.ST_N7, tune.ST_S6);
                return t_entry + tune.ST_T0 + t / num_clusters;
            };
            const uint32_t lane_full = bars + BAR_OFULL + min(lane, NUM_WG - 1) * 8;
            uint32_t open = 0, due = release_time(cluster);
            Ring o = {0, 0};
#pragma unroll 1
            for (uint32_t j = 0, id = cluster; id < num_tiles; j++, id += num_clusters, o.advance()) {
                const uint32_t obar = bars + o.s * 32;
                const uint32_t src = smem + SMEM_OUT + o.s * HALF_BYTES;
                auto store = [&](int w) {
                    if (id + tune.SE_TAIL < num_tiles) tma_store_1(&maps.out, src + w * SLICE_BYTES, slice_channel(rank, w), id * TILE_PIX);
                    else tma_store_evict_first_1(&maps.out, src + w * SLICE_BYTES, slice_channel(rank, w), id * TILE_PIX);
                };
                bool whole;
#pragma unroll 1
                for (uint32_t spins = 0; spins < SPIN_LIMIT; spins++) {
                    const uint32_t delay = lds32(bars + DELAY_AT);
                    whole = mbar_test(lane_full + o.s * 32, o.parity);
                    if (reached(timer_ns(), due + uniform(delay))) break;
                    hand_back<0>(open);
                    __nanosleep(20);
                }
                if (whole) {
                    TR(11, j);
#pragma unroll
                    for (int w = 0; w < NUM_WG; w++) store(w);
                    due = release_time(id + num_clusters);
                    hand_back<3>(open);
                    stores_read_wait<2>();
                    TR(12, j);
                    mbar_arrive_1(obar + BAR_OFREE);
                    stores_read_wait<1>();
                    TR(13, j);
                    mbar_arrive_1(obar + BAR_OFREE + 8);
                    open = obar + BAR_OFREE + 16;
                } else {
#pragma unroll 1
                    for (uint32_t w = 0; w < NUM_WG; w++) {
                        if (!mbar_test(obar + BAR_OFULL + w * 8, o.parity)) {
                            hand_back<0>(open);
                            mbar_wait(obar + BAR_OFULL + w * 8, o.parity);
                        }
                        TR(11 + w, j);
                        store(w);
                        hand_back<1>(open);
                        open = obar + BAR_OFREE + w * 8;
                    }
                    due = release_time(id + num_clusters);
                }
            }
            stores_read_wait<0>();
            TR(4, 62);
            TRV(6, 62, lds32(bars + DELAY_AT));
        } else {
            sts32(bars + ISSUED_AT, 0);
            cluster_arrive();
            uint32_t due = t_entry + tune.PM_T0 + (blockIdx.x & 3) * tune.PM_STAG;
            const uint32_t step = num_clusters / 2;
#pragma unroll 1
            for (uint32_t piece = 1;; piece++) {
                const uint32_t t = cluster + piece / 2 * num_clusters;
                if (t >= num_tiles) break;
                const bool last = t + tune.LEAD_T >= num_tiles;
                uint32_t now, issued;
#pragma unroll 1
                for (uint32_t spins = 0; spins < 16384; spins++) {
                    issued = uniform(lds32(bars + ISSUED_AT));
                    now = timer_ns();
                    const int lead = max((int)(last ? tune.LEAD_C : tune.LEAD_B), (int)tune.LEAD_A - (max((int)issued - (int)tune.LEAD_F, 0) * (int)tune.LEAD_S >> 4));
                    if (reached(now, due)) {
                        if (cluster + piece * step <= issued + lead) break;
                        due = now;
                    }
                    __nanosleep(20);
                }
                if (t < issued) continue;
                if (reached(now - tune.PM_SLACK, due)) due = now - tune.PM_SLACK;
                due += piece < tune.PM_E1 ? tune.PM_DT1 : piece < tune.PM_E2 ? tune.PM_DT2 : last ? tune.PM_DT4 : tune.PM_DT3;
                const uint8_t* p = x_raw + (size_t)t * STAGE_BYTES + rank * HALF_BYTES + (piece % 2) * PIECE_BYTES + lane * 128;
#pragma unroll
                for (int k = 0; k < PIECE_BYTES / 4096; k++) prefetch_l2(p + k * 4096);
                if (piece % 2 == 0) TR(14, piece / 2);
            }
            cluster_wait();
        }
    }
}

typedef CUresult (*EncodeTiledFn)(CUtensorMap*, CUtensorMapDataType, cuuint32_t, void*, const cuuint64_t*,
                                  const cuuint64_t*, const cuuint32_t*, const cuuint32_t*, CUtensorMapInterleave,
                                  CUtensorMapSwizzle, CUtensorMapL2promotion, CUtensorMapFloatOOBfill);

}

extern "C" void kernel_launch(void* const* d_in, const int* in_sizes, int n_in, void* d_out, int out_size) {
    (void)n_in;
    (void)out_size;
    void* x = d_in[0];
    void* w = d_in[1];
    const uint16_t* b = (const uint16_t*)d_in[2];
    const int M = in_sizes[0] / C;
    const int num_tiles = M / TILE_PIX;

    static EncodeTiledFn encode = nullptr;
    static int sms = 0;
    if (!encode) {
        void* fn = nullptr;
        cudaDriverEntryPointQueryResult q;
        cudaGetDriverEntryPoint("cuTensorMapEncodeTiled", &fn, cudaEnableDefault, &q);
        encode = (EncodeTiledFn)fn;
        cudaDeviceGetAttribute(&sms, cudaDevAttrMultiProcessorCount, 0);
        cudaFuncSetAttribute(conv1x1_kernel, cudaFuncAttributeMaxDynamicSharedMemorySize, SMEM_TOTAL);
    }

    Maps maps;
    const cuuint32_t ones[4] = {1, 1, 1, 1};
    auto make = [&](CUtensorMap* map, int rank, void* base, const cuuint64_t* dims, const cuuint64_t* strides,
                    const cuuint32_t* box, CUtensorMapL2promotion promo) {
        encode(map, CU_TENSOR_MAP_DATA_TYPE_BFLOAT16, rank, base, dims, strides, box, ones, CU_TENSOR_MAP_INTERLEAVE_NONE,
               CU_TENSOR_MAP_SWIZZLE_128B, promo, CU_TENSOR_MAP_FLOAT_OOB_FILL_NONE);
    };
    {
        const cuuint64_t dims[4]    = {64, 8, 6, (cuuint64_t)(M / 8)};
        const cuuint64_t strides[3] = {C * 2, 128, 8 * C * 2};
        const cuuint32_t box[4]     = {64, 8, 6, TILE_PIX / 16};
        make(&maps.x, 4, x, dims, strides, box, CU_TENSOR_MAP_L2_PROMOTION_L2_128B);
    }
    {
        const cuuint64_t dims[3]    = {C, C / 2, 2};
        const cuuint64_t strides[2] = {C * 2, C * C};
        const cuuint32_t box[3]     = {64, C / 2, 2};
        make(&maps.w, 3, w, dims, strides, box, CU_TENSOR_MAP_L2_PROMOTION_L2_128B);
    }
    {
        const cuuint64_t dims[2]    = {C, (cuuint64_t)M};
        const cuuint64_t strides[1] = {C * 2};
        const cuuint32_t box[2]     = {64, TILE_PIX};
        make(&maps.out, 2, d_out, dims, strides, box, CU_TENSOR_MAP_L2_PROMOTION_NONE);
    }

    const Tune tune;
    int clusters = sms / 2;
    if (clusters > num_tiles) clusters = num_tiles;
    conv1x1_kernel<<<clusters * 2, THREADS, SMEM_TOTAL>>>((const uint8_t*)x, (const uint8_t*)w, b, (uint32_t)num_tiles,
                                                          (uint32_t)clusters, maps, tune);
}
```

```cpp
#include <cuda_runtime.h>
#include <cuda_bf16.h>
#include <cuda.h>
#include <stdint.h>

#define TUNABLES(F) \
    F(PM_T0, 350)        \
    F(PM_STAG, 90)       \
    F(PM_DT1, 415)       \
    F(PM_E1, 8) \
    F(PM_DT2, 485) \
    F(PM_E2, 23) \
    F(PM_DT3, 860) \
    F(PM_SLACK, 500)     \
    F(LEAD_A, 351)       \
    F(LEAD_S, 10)        \
    F(LEAD_B, 151)       \
    F(LEAD_T, 264)       \
    F(LEAD_C, 170)       \
    F(PM_DT4, 700)       \
    F(EF_TAIL, 500)      \
    F(ST_AT, 2)          \
    F(ST_T0, 6830)       \
    F(ST_S1, 2040)       \
    F(ST_N1, 448) \
    F(ST_S2, 1860) \
    F(ST_N2, 594) \
    F(ST_S3, 1970)       \
    F(ST_END, 613) \
    F(ST_S4, 1500)       \
    F(ST_N4, 96) \
    F(ST_S5, 1100) \
    F(ST_N5, 85) \
    F(ST_S6, 950) \
    F(ST_N7, 22)         \
    F(SE_TAIL, 400)      \
    F(CC_AT, 22)         \
    F(CC_L0, 1300)       \
    F(CC_CAP, 1330)

struct Tune {
#define F(n, v) uint32_t n = v;
    TUNABLES(F)
#undef F
};

#define TRV(slot, idx, v)
#define TR(slot, idx)
#define TRE(slot, idx)
#define TRACE_BYTES 0

namespace {

constexpr int C            = 384;
constexpr int TILE_PIX     = 64;
constexpr int STAGES       = 3;
constexpr int STAGE_BYTES  = TILE_PIX * C * 2;
constexpr int HALF_BYTES   = STAGE_BYTES / 2;
constexpr int PIECE_BYTES  = HALF_BYTES / 2;
constexpr int SLICE_BYTES  = TILE_PIX * 128;
constexpr int NUM_WG       = 3;
constexpr int THREADS      = (NUM_WG + 1) * 128;
constexpr int SMEM_OUT     = STAGES * STAGE_BYTES;
constexpr int SMEM_BAR     = SMEM_OUT + STAGES * HALF_BYTES;
constexpr int SMEM_TOTAL   = SMEM_BAR + 512 + TRACE_BYTES + 1024;
constexpr int HAND_AT      = 18;
constexpr int W_LINES      = C * C * 2 / 128;
constexpr int PRE_W        = 64;
constexpr int PRE_DT       = 330;
constexpr uint32_t SPIN_LIMIT = 1u << 22;
constexpr uint32_t PACE_LIMIT = 1u << 14;
constexpr int BAR_W     = 0;
constexpr int BAR_FULL  = 32;
constexpr int BAR_EMPTY = 64;
constexpr int BAR_OFREE = 96;
constexpr int BAR_OFULL = BAR_OFREE + 32 * STAGES;
constexpr int ISSUED_AT = BAR_OFULL + 32 * STAGES;
constexpr int DELAY_AT  = ISSUED_AT + 4;
constexpr int STAMP_AT  = DELAY_AT + 4;
constexpr int SINK_AT   = 384;

struct Maps {
    CUtensorMap w, x, out;
};

#define ELECT "{\n.reg .pred e;\nelect.sync _|e, 0xffffffff;\n@e "

__device__ __forceinline__ uint32_t smem_u32(const void* p) {
    return (uint32_t)__cvta_generic_to_shared(p);
}
__device__ __forceinline__ void mbar_init_1(uint32_t bar, uint32_t count) {
    asm volatile(ELECT "mbarrier.init.shared::cta.b64 [%0], %1;\n}" ::"r"(bar), "r"(count) : "memory");
}
__device__ __forceinline__ void mbar_expect_tx_1(uint32_t bar, uint32_t bytes) {
    asm volatile(ELECT "mbarrier.arrive.expect_tx.shared::cta.b64 _, [%0], %1;\n}" ::"r"(bar), "r"(bytes) : "memory");
}
__device__ __forceinline__ void mbar_arrive_1(uint32_t bar) {
    asm volatile(ELECT "mbarrier.arrive.shared::cta.b64 _, [%0];\n}" ::"r"(bar) : "memory");
}
__device__ __forceinline__ void mbar_wait(uint32_t bar, uint32_t parity) {
    uint32_t done;
    uint32_t spins = 0;
    do {
        asm volatile(
            "{\n.reg .pred p;\n"
            "mbarrier.try_wait.parity.shared::cta.b64 p, [%1], %2;\n"
            "selp.u32 %0, 1, 0, p;\n}"
            : "=r"(done) : "r"(bar), "r"(parity) : "memory");
    } while (!done && ++spins < SPIN_LIMIT);
    __syncwarp();
}
__device__ __forceinline__ bool mbar_test(uint32_t bar, uint32_t parity) {
    uint32_t done;
    asm volatile(
        "{\n.reg .pred p;\n"
        "mbarrier.test_wait.parity.shared::cta.b64 p, [%1], %2;\n"
        "selp.u32 %0, 1, 0, p;\n}"
        : "=r"(done) : "r"(bar), "r"(parity) : "memory");
    return __all_sync(0xffffffffu, done);
}
__device__ __forceinline__ void mbar_arrive_cta(uint32_t bar, uint32_t cta) {
    asm volatile(
        "{\n.reg .b32 ra;\n"
        "mapa.shared::cluster.u32 ra, %0, %1;\n"
        "mbarrier.arrive.shared::cluster.b64 _, [ra];\n}"
        ::"r"(bar), "r"(cta) : "memory");
}
__device__ __forceinline__ uint32_t lds32(uint32_t addr) {
    uint32_t v;
    asm volatile("ld.volatile.shared.b32 %0, [%1];" : "=r"(v) : "r"(addr) : "memory");
    return v;
}
__device__ __forceinline__ void sts32(uint32_t addr, uint32_t v) {
    asm volatile("st.volatile.shared.b32 [%0], %1;" ::"r"(addr), "r"(v) : "memory");
}
__device__ __forceinline__ uint32_t uniform(uint32_t v) {
    return __shfl_sync(0xffffffffu, v, 0);
}
__device__ __forceinline__ void tma_load_w_1(uint32_t dst, const CUtensorMap* map, uint32_t bar, int n) {
    asm volatile(
        ELECT "cp.async.bulk.tensor.3d.shared::cluster.global.mbarrier::complete_tx::bytes [%0], [%1, {%3, %4, %4}], [%2];\n}"
        ::"r"(dst), "l"(map), "r"(bar), "r"(n), "r"(0) : "memory");
}
__device__ __forceinline__ void tma_load_x_1(uint32_t dst, const CUtensorMap* map, uint32_t bar, int group) {
    asm volatile(
        ELECT "cp.async.bulk.tensor.4d.shared::cluster.global.mbarrier::complete_tx::bytes.multicast::cluster"
        " [%0], [%1, {%3, %3, %3, %4}], [%2], %5;\n}"
        ::"r"(dst), "l"(map), "r"(bar), "r"(0), "r"(group), "h"((uint16_t)3) : "memory");
}
__device__ __forceinline__ void tma_load_x_evict_first_1(uint32_t dst, const CUtensorMap* map, uint32_t bar, int group) {
    asm volatile(
        "{\n.reg .b64 pol;\n"
        "createpolicy.fractional.L2::evict_first.b64 pol, 1.0;\n"
        ELECT "cp.async.bulk.tensor.4d.shared::cluster.global.mbarrier::complete_tx::bytes.multicast::cluster.L2::cache_hint"
        " [%0], [%1, {%3, %3, %3, %4}], [%2], %5, pol;\n}\n}"
        ::"r"(dst), "l"(map), "r"(bar), "r"(0), "r"(group), "h"((uint16_t)3) : "memory");
}
__device__ __forceinline__ void tma_store_1(const CUtensorMap* map, uint32_t src, int ch, int pix) {
    asm volatile(
        ELECT "cp.async.bulk.tensor.2d.global.shared::cta.bulk_group [%0, {%2, %3}], [%1];\n}\n"
        "cp.async.bulk.commit_group;"
        ::"l"(map), "r"(src), "r"(ch), "r"(pix) : "memory");
}
__device__ __forceinline__ void tma_store_evict_first_1(const CUtensorMap* map, uint32_t src, int ch, int pix) {
    asm volatile(
        "{\n.reg .b64 pol;\n"
        "createpolicy.fractional.L2::evict_first.b64 pol, 1.0;\n"
        ELECT "cp.async.bulk.tensor.2d.global.shared::cta.bulk_group.L2::cache_hint [%0, {%2, %3}], [%1], pol;\n}\n}\n"
        "cp.async.bulk.commit_group;"
        ::"l"(map), "r"(src), "r"(ch), "r"(pix) : "memory");
}
template <int N>
__device__ __forceinline__ void stores_read_wait() {
    asm volatile("cp.async.bulk.wait_group.read %0;" ::"n"(N) : "memory");
}
__device__ __forceinline__ void prefetch_map_1(const CUtensorMap* map) {
    asm volatile(ELECT "prefetch.tensormap [%0];\n}" ::"l"(map) : "memory");
}
__device__ __forceinline__ void prefetch_l2(const void* p) {
    asm volatile("prefetch.global.L2 [%0];" ::"l"(p) : "memory");
}
__device__ __forceinline__ uint32_t timer_ns() {
    uint32_t t;
    asm volatile("mov.u32 %0, %%globaltimer_lo;" : "=r"(t)::"memory");
    return t;
}
__device__ __forceinline__ bool reached(uint32_t now, uint32_t t) {
    return (int32_t)(now - t) >= 0;
}
__device__ __forceinline__ void cluster_arrive() {
    asm volatile("barrier.cluster.arrive.relaxed.aligned;" ::: "memory");
}
__device__ __forceinline__ void cluster_wait() {
    asm volatile("barrier.cluster.wait.aligned;" ::: "memory");
}
__device__ __forceinline__ void publish_barriers() {
    asm volatile("fence.mbarrier_init.release.cluster;" ::: "memory");
    asm volatile("fence.proxy.async.shared::cta;" ::: "memory");
}

__device__ __forceinline__ void wgmma_rs_n64(float (&d)[32], const uint32_t* a, uint64_t desc, int scale_d) {
    asm volatile(
        "{\n.reg .pred p;\n"
        "setp.ne.b32 p, %37, 0;\n"
        "wgmma.mma_async.sync.aligned.m64n64k16.f32.bf16.bf16 "
        "{%0, %1, %2, %3, %4, %5, %6, %7, %8, %9, %10, %11, %12, %13, %14, %15, "
        "%16, %17, %18, %19, %20, %21, %22, %23, %24, %25, %26, %27, %28, %29, %30, %31}, "
        "{%32, %33, %34, %35}, %36, p, 1, 1, 0;\n}"
        : "+f"(d[0]), "+f"(d[1]), "+f"(d[2]), "+f"(d[3]), "+f"(d[4]), "+f"(d[5]), "+f"(d[6]), "+f"(d[7]),
          "+f"(d[8]), "+f"(d[9]), "+f"(d[10]), "+f"(d[11]), "+f"(d[12]), "+f"(d[13]), "+f"(d[14]), "+f"(d[15]),
          "+f"(d[16]), "+f"(d[17]), "+f"(d[18]), "+f"(d[19]), "+f"(d[20]), "+f"(d[21]), "+f"(d[22]), "+f"(d[23]),
          "+f"(d[24]), "+f"(d[25]), "+f"(d[26]), "+f"(d[27]), "+f"(d[28]), "+f"(d[29]), "+f"(d[30]), "+f"(d[31])
        : "r"(a[0]), "r"(a[1]), "r"(a[2]), "r"(a[3]), "l"(desc), "r"(scale_d));
}

__device__ __forceinline__ uint32_t pack_bias(float lo, float hi, uint32_t bias2) {
    uint32_t r;
    asm("{\n.reg .b32 t;\n"
        "cvt.rn.bf16x2.f32 t, %2, %1;\n"
        "add.rn.bf16x2 %0, t, %3;\n}"
        : "=r"(r) : "f"(lo), "f"(hi), "r"(bias2));
    return r;
}

__device__ __forceinline__ int slice_channel(uint32_t rank, int wg) {
    return (wg * 2 + rank) * 64;
}
__device__ __forceinline__ uint32_t w_stage(int wg) {
    return (wg + 1) * STAGE_BYTES + (wg == 2 ? HALF_BYTES : 0);
}

struct Ring {
    uint32_t s, parity;
    __device__ __forceinline__ void advance() {
        if (++s == STAGES) {
            s = 0;
            parity ^= 1;
        }
    }
};

__device__ __forceinline__ void write_out(uint32_t wg_bars, uint32_t st_addr, const Ring& r, const uint32_t (&v)[16]) {
    mbar_wait(wg_bars + BAR_OFREE + r.s * 32, r.parity ^ 1);
    const uint32_t dst = st_addr + r.s * HALF_BYTES;
#pragma unroll
    for (int j = 0; j < 4; j++) {
        asm volatile("stmatrix.sync.aligned.m8n8.x4.trans.shared.b16 [%0], {%1, %2, %3, %4};"
                     ::"r"(dst + j * 2048), "r"(v[4 * j]), "r"(v[4 * j + 1]), "r"(v[4 * j + 2]), "r"(v[4 * j + 3]) : "memory");
    }
    asm volatile("fence.proxy.async.shared::cta;" ::: "memory");
    __syncwarp();
    mbar_arrive_1(wg_bars + BAR_OFULL + r.s * 32);
}

template <int N>
__device__ __forceinline__ void hand_back(uint32_t& open) {
    if (open != 0) {
        stores_read_wait<N>();
        mbar_arrive_1(open);
        open = 0;
    }
}

__global__ void __cluster_dims__(2, 1, 1) __launch_bounds__(THREADS, 1)
conv1x1_kernel(const uint8_t* __restrict__ x_raw,
               const uint8_t* __restrict__ w_raw,
               const uint16_t* __restrict__ bias,
               uint32_t num_tiles,
               uint32_t num_clusters,
               const __grid_constant__ Maps maps,
               const __grid_constant__ Tune tune) {
    const uint32_t t_entry = timer_ns();
    extern __shared__ uint8_t smem_raw[];
    const uint32_t smem = (smem_u32(smem_raw) + 1023u) & ~1023u;
    const uint32_t bars = smem + SMEM_BAR;

    if (threadIdx.x < PRE_W) {
        prefetch_l2(w_raw + (blockIdx.x % (W_LINES / PRE_W) * PRE_W + threadIdx.x) * 128);
    } else if (threadIdx.x >= 96 && threadIdx.x < 128) {
        prefetch_map_1(&maps.w);
        prefetch_map_1(&maps.x);
    }
    if (threadIdx.x < NUM_WG * 128) cluster_arrive();
    if (threadIdx.x >= 128 && threadIdx.x < 128 + PIECE_BYTES / 128) {
        const uint8_t* p = x_raw + (size_t)blockIdx.x * HALF_BYTES + (threadIdx.x - 128) * 128;
        const uint32_t wait = ((threadIdx.x - 128) >> 5) * PRE_DT;
        const uint32_t c0 = (uint32_t)clock();
        while ((uint32_t)clock() - c0 < wait) {}
        asm volatile("cp.async.ca.shared.global.L2::128B [%0], [%1], 4;" ::"r"(bars + SINK_AT + (threadIdx.x & 31) * 4), "l"(p) : "memory");
    }
    if (threadIdx.x == 0) TRV(0, 63, t_entry);

    const int warp = uniform(threadIdx.x >> 5);
    const int lane = threadIdx.x & 31;
    const uint32_t rank    = blockIdx.x & 1;
    const uint32_t cluster = blockIdx.x >> 1;

    if (warp < NUM_WG * 4) {
        asm volatile("setmaxnreg.inc.sync.aligned.u32 160;");
        const int wg = warp >> 2;
        const int wq = warp & 3;
        const uint32_t bias_lo = bias[slice_channel(rank, wg) + wq * 16 + (lane >> 2)] * 0x10001u;
        const uint32_t bias_hi = bias[slice_channel(rank, wg) + wq * 16 + (lane >> 2) + 8] * 0x10001u;

        cluster_wait();
        TRE(1 + wg, 63);
        mbar_wait(bars + BAR_W + 8 * wg, 0);
        TRE(4 + wg, 63);
        uint32_t wreg[96];
        {
            const int r = lane & 7, m = lane >> 3;
            const uint32_t base = smem + w_stage(wg) + ((m >> 1) * 8 + r) * 128 + (((2 * wq + (m & 1)) ^ r) << 4);
#pragma unroll
            for (int ks = 0; ks < 24; ks++) {
                asm volatile("ldmatrix.sync.aligned.m8n8.x4.trans.shared.b16 {%0, %1, %2, %3}, [%4];"
                             : "=r"(wreg[ks * 4 + 0]), "=r"(wreg[ks * 4 + 1]), "=r"(wreg[ks * 4 + 2]), "=r"(wreg[ks * 4 + 3])
                             : "r"(base + ks * 2048) : "memory");
            }
        }
        uint32_t dep = 0;
#pragma unroll
        for (int ks = 0; ks < 24; ks++) dep ^= wreg[ks * 4];
        dep = uniform(dep & (num_tiles >> 31));
        if (lane < 6 && wg < 2) mbar_arrive_cta(bars + BAR_EMPTY + 8 * (wg + 1) + dep, lane & 1);
        asm volatile("cp.async.wait_all;" ::: "memory");
        TRE(1 + wg, 60);

        const uint32_t wg_bars = bars + wg * 8;
        const uint32_t st_addr = smem + SMEM_OUT + wg * SLICE_BYTES + ((lane >> 4) * 8 + (lane & 7)) * 128 +
                                 (((2 * wq + ((lane >> 3) & 1)) ^ (lane & 7)) << 4);
        const uint64_t desc_base =
            (uint64_t)((smem & 0x3FFFF) >> 4) | ((uint64_t)1 << 16) | ((uint64_t)(6144 >> 4) << 32) | ((uint64_t)1 << 62);
        const int next_turn = 4 + (wg + 1) % NUM_WG;

        float acc[32];
        uint32_t packed[16];
        Ring r = {0, dep}, o = r;
        bool held = false;
        for (uint32_t i = 0, id = cluster; id < num_tiles; i++, id += num_clusters, r.advance()) {
            mbar_wait(bars + BAR_FULL + 8 * r.s, r.parity);
            if ((i | wg) != 0) asm volatile("bar.sync %0, 256;" ::"r"(4 + wg) : "memory");
            TRE(1 + wg * 2, i);
            const uint64_t desc = desc_base + (uint64_t)(r.s * (STAGE_BYTES >> 4));
            asm volatile("wgmma.fence.sync.aligned;" ::: "memory");
#pragma unroll
            for (int ks = 0; ks < 24; ks++) {
                wgmma_rs_n64(acc, &wreg[ks * 4], desc + (uint64_t)((ks >> 2) * 64 + (ks & 3) * 2), ks != 0);
                if (ks + 1 == HAND_AT) asm volatile("bar.arrive %0, 256;" ::"r"(next_turn) : "memory");
            }
            asm volatile("wgmma.commit_group.sync.aligned;" ::: "memory");
            asm volatile("wgmma.wait_group.sync.aligned 0;" ::: "memory");
#pragma unroll
            for (int j = 0; j < 32; j++) asm volatile("" : "+f"(acc[j])::"memory");
            TRE(2 + wg * 2, i);
            if (lane < 2) mbar_arrive_cta(bars + BAR_EMPTY + 8 * r.s, lane);

            if (held) write_out(wg_bars, st_addr, o, packed);
            o = r;
#pragma unroll
            for (int j = 0; j < 16; j++) packed[j] = pack_bias(acc[2 * j], acc[2 * j + 1], j & 1 ? bias_hi : bias_lo);
            held = !mbar_test(wg_bars + BAR_OFREE + o.s * 32, o.parity ^ 1);
            if (!held) write_out(wg_bars, st_addr, o, packed);
            TRE(8 + wg, i);
        }
        if (held) write_out(wg_bars, st_addr, o, packed);
        if (wg == 0) asm volatile("bar.sync 4, 256;" ::: "memory");
        TRE(1 + wg, 62);
    } else {
        asm volatile("setmaxnreg.dec.sync.aligned.u32 32;");
        if (warp == NUM_WG * 4) {
#pragma unroll
            for (int j = 0; j < NUM_WG; j++) mbar_init_1(bars + BAR_W + 8 * j, 1);
            publish_barriers();
            cluster_arrive();
#pragma unroll
            for (int j = 0; j < NUM_WG; j++) {
                mbar_expect_tx_1(bars + BAR_W + 8 * j, STAGE_BYTES);
                tma_load_w_1(smem + w_stage(j), &maps.w, bars + BAR_W + 8 * j, slice_channel(rank, j));
                if (j == 0) TR(2, 61);
            }
            cluster_wait();
            TR(0, 0);
            mbar_expect_tx_1(bars + BAR_FULL, STAGE_BYTES);
            tma_load_x_1(smem + rank * HALF_BYTES, &maps.x, bars + BAR_FULL, cluster * 8 + rank * 4);
            Ring r = {1, 0};
#pragma unroll 1
            for (uint32_t i = 1, id = cluster + num_clusters; id < num_tiles; i++, id += num_clusters, r.advance()) {
                mbar_wait(bars + BAR_EMPTY + 8 * r.s, r.parity ^ (r.s == 0));
                sts32(bars + ISSUED_AT, id);
                sts32(bars + STAMP_AT + 4 * r.s, timer_ns());
                TR(0, i);
                TRV(15, i, id);
                const uint32_t full = bars + BAR_FULL + 8 * r.s;
                const uint32_t dst = smem + r.s * STAGE_BYTES + rank * HALF_BYTES;
                mbar_expect_tx_1(full, STAGE_BYTES);
                if (id + tune.EF_TAIL < num_tiles) tma_load_x_1(dst, &maps.x, full, id * 8 + rank * 4);
                else tma_load_x_evict_first_1(dst, &maps.x, full, id * 8 + rank * 4);
            }
#pragma unroll 1
            for (int k = 0; k < STAGES; k++, r.advance()) mbar_wait(bars + BAR_EMPTY + 8 * r.s, r.parity ^ (r.s == 0));
        } else if (warp == NUM_WG * 4 + 1) {
#pragma unroll
            for (int s = 0; s < STAGES; s++) {
                mbar_init_1(bars + BAR_FULL + 8 * s, 1);
                mbar_init_1(bars + BAR_EMPTY + 8 * s, NUM_WG * 4 * 2);
            }
            publish_barriers();
            cluster_arrive();
            TR(0, 61);
            cluster_wait();
            prefetch_map_1(&maps.out);
            uint32_t delay = 0;
            Ring r = {0, 0};
#pragma unroll 1
            for (uint32_t i = 0, id = cluster; id < num_tiles; i++, id += num_clusters, r.advance()) {
                mbar_wait(bars + BAR_FULL + 8 * r.s, r.parity);
                TR(7, i);
                const int late = (int)(timer_ns() - lds32(bars + STAMP_AT + 4 * r.s) - tune.CC_L0);
                if (i >= tune.CC_AT && late > 0) {
                    delay = min(delay + late, tune.CC_CAP);
                    sts32(bars + DELAY_AT, delay);
                }
            }
        } else if (warp == NUM_WG * 4 + 2) {
            sts32(bars + DELAY_AT, 0);
#pragma unroll
            for (int b = 0; b < STAGES; b++) {
#pragma unroll
                for (int w = 0; w < NUM_WG; w++) {
                    mbar_init_1(bars + BAR_OFREE + b * 32 + w * 8, 1);
                    mbar_init_1(bars + BAR_OFULL + b * 32 + w * 8, 4);
                }
            }
            publish_barriers();
            cluster_arrive();
            cluster_wait();
            const uint32_t first = tune.ST_AT * num_clusters;
            const uint32_t n3 = max((int)(num_tiles - first - tune.ST_N1 - tune.ST_N2 - tune.ST_END), 0);
            auto release_time = [&](uint32_t id) {
                if (id < first) return t_entry;
                uint32_t rest = id - first, t = 0;
                auto segment = [&](uint32_t ids, uint32_t per_round) {
                    const uint32_t n = min(rest, ids);
                    t += n * per_round;
                    rest -= n;
                };
                segment(tune.ST_N1, tune.ST_S1);
                segment(tune.ST_N2, tune.ST_S2);
                segment(n3, tune.ST_S3);
                segment(tune.ST_N4, tune.ST_S4);
                segment(tune.ST_N5, tune.ST_S5);
                segment(tune.ST_END - tune.ST_N4 - tune.ST_N5 - tune.ST_N7, tune.ST_S6);
                return t_entry + tune.ST_T0 + t / num_clusters;
            };
            const uint32_t lane_full = bars + BAR_OFULL + min(lane, NUM_WG - 1) * 8;
            uint32_t open = 0, due = release_time(cluster);
            Ring o = {0, 0};
#pragma unroll 1
            for (uint32_t j = 0, id = cluster; id < num_tiles; j++, id += num_clusters, o.advance()) {
                const uint32_t obar = bars + o.s * 32;
                const uint32_t src = smem + SMEM_OUT + o.s * HALF_BYTES;
                auto store = [&](int w) {
                    if (id + tune.SE_TAIL < num_tiles) tma_store_1(&maps.out, src + w * SLICE_BYTES, slice_channel(rank, w), id * TILE_PIX);
                    else tma_store_evict_first_1(&maps.out, src + w * SLICE_BYTES, slice_channel(rank, w), id * TILE_PIX);
                };
                bool whole;
#pragma unroll 1
                for (uint32_t spins = 0; spins < PACE_LIMIT; spins++) {
                    const uint32_t delay = lds32(bars + DELAY_AT);
                    whole = mbar_test(lane_full + o.s * 32, o.parity);
                    if (reached(timer_ns(), due + uniform(delay))) break;
                    hand_back<0>(open);
                    __nanosleep(20);
                }
                if (whole) {
                    __syncwarp();
                    TR(11, j);
#pragma unroll
                    for (int w = 0; w < NUM_WG; w++) store(w);
                    due = release_time(id + num_clusters);
                    hand_back<3>(open);
                    stores_read_wait<2>();
                    TR(12, j);
                    mbar_arrive_1(obar + BAR_OFREE);
                    stores_read_wait<1>();
                    TR(13, j);
                    mbar_arrive_1(obar + BAR_OFREE + 8);
                    open = obar + BAR_OFREE + 16;
                } else {
#pragma unroll 1
                    for (uint32_t w = 0; w < NUM_WG; w++) {
                        if (!mbar_test(obar + BAR_OFULL + w * 8, o.parity)) {
                            hand_back<0>(open);
                            mbar_wait(obar + BAR_OFULL + w * 8, o.parity);
                        }
                        TR(11 + w, j);
                        store(w);
                        hand_back<1>(open);
                        open = obar + BAR_OFREE + w * 8;
                    }
                    due = release_time(id + num_clusters);
                }
            }
            stores_read_wait<0>();
            TR(4, 62);
            TRV(6, 62, lds32(bars + DELAY_AT));
        } else {
            sts32(bars + ISSUED_AT, 0);
            cluster_arrive();
            uint32_t due = t_entry + tune.PM_T0 + (blockIdx.x & 3) * tune.PM_STAG;
            const uint32_t step = num_clusters / 2;
#pragma unroll 1
            for (uint32_t piece = 1;; piece++) {
                const uint32_t t = cluster + piece / 2 * num_clusters;
                if (t >= num_tiles) break;
                const bool last = t + tune.LEAD_T >= num_tiles;
                uint32_t now, issued;
#pragma unroll 1
                for (uint32_t spins = 0; spins < PACE_LIMIT; spins++) {
                    issued = uniform(lds32(bars + ISSUED_AT));
                    now = timer_ns();
                    const int lead = max((int)(last ? tune.LEAD_C : tune.LEAD_B), (int)tune.LEAD_A - (int)(issued * tune.LEAD_S >> 6));
                    if (reached(now, due)) {
                        if (cluster + piece * step <= issued + lead) break;
                        due = now;
                    }
                    __nanosleep(20);
                }
                if (t < issued) continue;
                if (reached(now - tune.PM_SLACK, due)) due = now - tune.PM_SLACK;
                due += piece < tune.PM_E1 ? tune.PM_DT1 : piece < tune.PM_E2 ? tune.PM_DT2 : last ? tune.PM_DT4 : tune.PM_DT3;
                const uint8_t* p = x_raw + (size_t)t * STAGE_BYTES + rank * HALF_BYTES + (piece % 2) * PIECE_BYTES + lane * 128;
#pragma unroll
                for (int k = 0; k < PIECE_BYTES / 4096; k++) prefetch_l2(p + k * 4096);
                if (piece % 2 == 0) TR(14, piece / 2);
            }
            cluster_wait();
        }
    }
}

typedef CUresult (*EncodeTiledFn)(CUtensorMap*, CUtensorMapDataType, cuuint32_t, void*, const cuuint64_t*,
                                  const cuuint64_t*, const cuuint32_t*, const cuuint32_t*, CUtensorMapInterleave,
                                  CUtensorMapSwizzle, CUtensorMapL2promotion, CUtensorMapFloatOOBfill);

}

extern "C" void kernel_launch(void* const* d_in, const int* in_sizes, int n_in, void* d_out, int out_size) {
    (void)n_in;
    (void)out_size;
    void* x = d_in[0];
    void* w = d_in[1];
    const uint16_t* b = (const uint16_t*)d_in[2];
    const int M = in_sizes[0] / C;
    const int num_tiles = M / TILE_PIX;

    static EncodeTiledFn encode = nullptr;
    static int sms = 0;
    if (!encode) {
        void* fn = nullptr;
        cudaDriverEntryPointQueryResult q;
        cudaGetDriverEntryPoint("cuTensorMapEncodeTiled", &fn, cudaEnableDefault, &q);
        encode = (EncodeTiledFn)fn;
        cudaDeviceGetAttribute(&sms, cudaDevAttrMultiProcessorCount, 0);
        cudaFuncSetAttribute(conv1x1_kernel, cudaFuncAttributeMaxDynamicSharedMemorySize, SMEM_TOTAL);
    }

    Maps maps;
    const cuuint32_t ones[4] = {1, 1, 1, 1};
    auto make = [&](CUtensorMap* map, int rank, void* base, const cuuint64_t* dims, const cuuint64_t* strides,
                    const cuuint32_t* box, CUtensorMapL2promotion promo) {
        encode(map, CU_TENSOR_MAP_DATA_TYPE_BFLOAT16, rank, base, dims, strides, box, ones, CU_TENSOR_MAP_INTERLEAVE_NONE,
               CU_TENSOR_MAP_SWIZZLE_128B, promo, CU_TENSOR_MAP_FLOAT_OOB_FILL_NONE);
    };
    {
        const cuuint64_t dims[4]    = {64, 8, 6, (cuuint64_t)(M / 8)};
        const cuuint64_t strides[3] = {C * 2, 128, 8 * C * 2};
        const cuuint32_t box[4]     = {64, 8, 6, TILE_PIX / 16};
        make(&maps.x, 4, x, dims, strides, box, CU_TENSOR_MAP_L2_PROMOTION_L2_128B);
    }
    {
        const cuuint64_t dims[3]    = {C, C / 2, 2};
        const cuuint64_t strides[2] = {C * 2, C * C};
        const cuuint32_t box[3]     = {64, C / 2, 2};
        make(&maps.w, 3, w, dims, strides, box, CU_TENSOR_MAP_L2_PROMOTION_L2_128B);
    }
    {
        const cuuint64_t dims[2]    = {C, (cuuint64_t)M};
        const cuuint64_t strides[1] = {C * 2};
        const cuuint32_t box[2]     = {64, TILE_PIX};
        make(&maps.out, 2, d_out, dims, strides, box, CU_TENSOR_MAP_L2_PROMOTION_NONE);
    }

    const Tune tune;
    int clusters = sms / 2;
    if (clusters > num_tiles) clusters = num_tiles;
    conv1x1_kernel<<<clusters * 2, THREADS, SMEM_TOTAL>>>((const uint8_t*)x, (const uint8_t*)w, b, (uint32_t)num_tiles,
                                                          (uint32_t)clusters, maps, tune);
}
```

```cpp
#include <cuda_runtime.h>
#include <cuda_bf16.h>
#include <cuda.h>
#include <stdint.h>

#define TUNABLES(F) \
    F(PM_T0, 280)        \
    F(PM_STAG, 120)       \
    F(PM_DT1, 415)       \
    F(PM_E1, 8) \
    F(PM_DT2, 485) \
    F(PM_E2, 23) \
    F(PM_DT3, 860) \
    F(PM_SLACK, 700)     \
    F(LEAD_A, 351)       \
    F(LEAD_S, 10)        \
    F(LEAD_B, 151)       \
    F(LEAD_T, 264)       \
    F(LEAD_C, 170)       \
    F(PM_DT4, 700)       \
    F(EF_TAIL, 440)      \
    F(ST_AT, 2)          \
    F(ST_T0, 6830)       \
    F(ST_S1, 2040)       \
    F(ST_N1, 448) \
    F(ST_S2, 1960) \
    F(ST_N2, 594) \
    F(ST_S3, 2020)       \
    F(ST_END, 613) \
    F(ST_S4, 1450)       \
    F(ST_N4, 96) \
    F(ST_S5, 1100) \
    F(ST_N5, 85) \
    F(ST_S6, 950) \
    F(ST_N7, 22)         \
    F(SE_TAIL, 400)

struct Tune {
#define F(n, v) uint32_t n = v;
    TUNABLES(F)
#undef F
};

#define TRV(slot, idx, v)
#define TR(slot, idx)
#define TRE(slot, idx)
#define TRACE_BYTES 0

namespace {

constexpr int C            = 384;
constexpr int TILE_PIX     = 64;
constexpr int STAGES       = 3;
constexpr int STAGE_BYTES  = TILE_PIX * C * 2;
constexpr int HALF_BYTES   = STAGE_BYTES / 2;
constexpr int PIECE_BYTES  = HALF_BYTES / 2;
constexpr int SLICE_BYTES  = TILE_PIX * 128;
constexpr int NUM_WG       = 3;
constexpr int THREADS      = (NUM_WG + 1) * 128;
constexpr int SMEM_OUT     = STAGES * STAGE_BYTES;
constexpr int SMEM_BAR     = SMEM_OUT + STAGES * HALF_BYTES;
constexpr int SMEM_TOTAL   = SMEM_BAR + 512 + TRACE_BYTES + 1024;
constexpr int HAND_AT      = 18;
constexpr int W_LINES      = C * C * 2 / 128;
constexpr int PRE_W        = 64;
constexpr int PRE_DT       = 330;
constexpr uint32_t SPIN_LIMIT = 1u << 22;
constexpr uint32_t PACE_LIMIT = 1u << 14;
constexpr int BAR_W     = 0;
constexpr int BAR_FULL  = 32;
constexpr int BAR_EMPTY = 64;
constexpr int BAR_OFREE = 96;
constexpr int BAR_OFULL = BAR_OFREE + 32 * STAGES;
constexpr int ISSUED_AT = BAR_OFULL + 32 * STAGES;
constexpr int SINK_AT   = 384;

struct Maps {
    CUtensorMap w, x, out;
};

#define ELECT "{\n.reg .pred e;\nelect.sync _|e, 0xffffffff;\n@e "

__device__ __forceinline__ uint32_t smem_u32(const void* p) {
    return (uint32_t)__cvta_generic_to_shared(p);
}
__device__ __forceinline__ void mbar_init_1(uint32_t bar, uint32_t count) {
    asm volatile(ELECT "mbarrier.init.shared::cta.b64 [%0], %1;\n}" ::"r"(bar), "r"(count) : "memory");
}
__device__ __forceinline__ void mbar_expect_tx_1(uint32_t bar, uint32_t bytes) {
    asm volatile(ELECT "mbarrier.arrive.expect_tx.shared::cta.b64 _, [%0], %1;\n}" ::"r"(bar), "r"(bytes) : "memory");
}
__device__ __forceinline__ void mbar_arrive_1(uint32_t bar) {
    asm volatile(ELECT "mbarrier.arrive.shared::cta.b64 _, [%0];\n}" ::"r"(bar) : "memory");
}
__device__ __forceinline__ void mbar_wait(uint32_t bar, uint32_t parity) {
    uint32_t done;
    uint32_t spins = 0;
    do {
        asm volatile(
            "{\n.reg .pred p;\n"
            "mbarrier.try_wait.parity.shared::cta.b64 p, [%1], %2;\n"
            "selp.u32 %0, 1, 0, p;\n}"
            : "=r"(done) : "r"(bar), "r"(parity) : "memory");
    } while (!done && ++spins < SPIN_LIMIT);
    __syncwarp();
}
__device__ __forceinline__ bool mbar_test(uint32_t bar, uint32_t parity) {
    uint32_t done;
    asm volatile(
        "{\n.reg .pred p;\n"
        "mbarrier.test_wait.parity.shared::cta.b64 p, [%1], %2;\n"
        "selp.u32 %0, 1, 0, p;\n}"
        : "=r"(done) : "r"(bar), "r"(parity) : "memory");
    return __all_sync(0xffffffffu, done);
}
__device__ __forceinline__ void mbar_arrive_cta(uint32_t bar, uint32_t cta) {
    asm volatile(
        "{\n.reg .b32 ra;\n"
        "mapa.shared::cluster.u32 ra, %0, %1;\n"
        "mbarrier.arrive.shared::cluster.b64 _, [ra];\n}"
        ::"r"(bar), "r"(cta) : "memory");
}
__device__ __forceinline__ uint32_t lds32(uint32_t addr) {
    uint32_t v;
    asm volatile("ld.volatile.shared.b32 %0, [%1];" : "=r"(v) : "r"(addr) : "memory");
    return v;
}
__device__ __forceinline__ void sts32(uint32_t addr, uint32_t v) {
    asm volatile("st.volatile.shared.b32 [%0], %1;" ::"r"(addr), "r"(v) : "memory");
}
__device__ __forceinline__ uint32_t uniform(uint32_t v) {
    return __shfl_sync(0xffffffffu, v, 0);
}
__device__ __forceinline__ void tma_load_w_1(uint32_t dst, const CUtensorMap* map, uint32_t bar, int n) {
    asm volatile(
        ELECT "cp.async.bulk.tensor.3d.shared::cluster.global.mbarrier::complete_tx::bytes [%0], [%1, {%3, %4, %4}], [%2];\n}"
        ::"r"(dst), "l"(map), "r"(bar), "r"(n), "r"(0) : "memory");
}
__device__ __forceinline__ void tma_load_x_1(uint32_t dst, const CUtensorMap* map, uint32_t bar, int group) {
    asm volatile(
        ELECT "cp.async.bulk.tensor.4d.shared::cluster.global.mbarrier::complete_tx::bytes.multicast::cluster"
        " [%0], [%1, {%3, %3, %3, %4}], [%2], %5;\n}"
        ::"r"(dst), "l"(map), "r"(bar), "r"(0), "r"(group), "h"((uint16_t)3) : "memory");
}
__device__ __forceinline__ void tma_load_x_evict_first_1(uint32_t dst, const CUtensorMap* map, uint32_t bar, int group) {
    asm volatile(
        "{\n.reg .b64 pol;\n"
        "createpolicy.fractional.L2::evict_first.b64 pol, 1.0;\n"
        ELECT "cp.async.bulk.tensor.4d.shared::cluster.global.mbarrier::complete_tx::bytes.multicast::cluster.L2::cache_hint"
        " [%0], [%1, {%3, %3, %3, %4}], [%2], %5, pol;\n}\n}"
        ::"r"(dst), "l"(map), "r"(bar), "r"(0), "r"(group), "h"((uint16_t)3) : "memory");
}
__device__ __forceinline__ void tma_store_1(const CUtensorMap* map, uint32_t src, int ch, int pix) {
    asm volatile(
        ELECT "cp.async.bulk.tensor.2d.global.shared::cta.bulk_group [%0, {%2, %3}], [%1];\n}\n"
        "cp.async.bulk.commit_group;"
        ::"l"(map), "r"(src), "r"(ch), "r"(pix) : "memory");
}
__device__ __forceinline__ void tma_store_evict_first_1(const CUtensorMap* map, uint32_t src, int ch, int pix) {
    asm volatile(
        "{\n.reg .b64 pol;\n"
        "createpolicy.fractional.L2::evict_first.b64 pol, 1.0;\n"
        ELECT "cp.async.bulk.tensor.2d.global.shared::cta.bulk_group.L2::cache_hint [%0, {%2, %3}], [%1], pol;\n}\n}\n"
        "cp.async.bulk.commit_group;"
        ::"l"(map), "r"(src), "r"(ch), "r"(pix) : "memory");
}
template <int N>
__device__ __forceinline__ void stores_read_wait() {
    asm volatile("cp.async.bulk.wait_group.read %0;" ::"n"(N) : "memory");
}
__device__ __forceinline__ void prefetch_map_1(const CUtensorMap* map) {
    asm volatile(ELECT "prefetch.tensormap [%0];\n}" ::"l"(map) : "memory");
}
__device__ __forceinline__ void prefetch_l2(const void* p) {
    asm volatile("prefetch.global.L2 [%0];" ::"l"(p) : "memory");
}
__device__ __forceinline__ uint32_t timer_ns() {
    uint32_t t;
    asm volatile("mov.u32 %0, %%globaltimer_lo;" : "=r"(t)::"memory");
    return t;
}
__device__ __forceinline__ bool reached(uint32_t now, uint32_t t) {
    return (int32_t)(now - t) >= 0;
}
__device__ __forceinline__ void cluster_arrive() {
    asm volatile("barrier.cluster.arrive.relaxed.aligned;" ::: "memory");
}
__device__ __forceinline__ void cluster_wait() {
    asm volatile("barrier.cluster.wait.aligned;" ::: "memory");
}
__device__ __forceinline__ void publish_barriers() {
    asm volatile("fence.mbarrier_init.release.cluster;" ::: "memory");
    asm volatile("fence.proxy.async.shared::cta;" ::: "memory");
}

__device__ __forceinline__ void wgmma_rs_n64(float (&d)[32], const uint32_t* a, uint64_t desc, int scale_d) {
    asm volatile(
        "{\n.reg .pred p;\n"
        "setp.ne.b32 p, %37, 0;\n"
        "wgmma.mma_async.sync.aligned.m64n64k16.f32.bf16.bf16 "
        "{%0, %1, %2, %3, %4, %5, %6, %7, %8, %9, %10, %11, %12, %13, %14, %15, "
        "%16, %17, %18, %19, %20, %21, %22, %23, %24, %25, %26, %27, %28, %29, %30, %31}, "
        "{%32, %33, %34, %35}, %36, p, 1, 1, 0;\n}"
        : "+f"(d[0]), "+f"(d[1]), "+f"(d[2]), "+f"(d[3]), "+f"(d[4]), "+f"(d[5]), "+f"(d[6]), "+f"(d[7]),
          "+f"(d[8]), "+f"(d[9]), "+f"(d[10]), "+f"(d[11]), "+f"(d[12]), "+f"(d[13]), "+f"(d[14]), "+f"(d[15]),
          "+f"(d[16]), "+f"(d[17]), "+f"(d[18]), "+f"(d[19]), "+f"(d[20]), "+f"(d[21]), "+f"(d[22]), "+f"(d[23]),
          "+f"(d[24]), "+f"(d[25]), "+f"(d[26]), "+f"(d[27]), "+f"(d[28]), "+f"(d[29]), "+f"(d[30]), "+f"(d[31])
        : "r"(a[0]), "r"(a[1]), "r"(a[2]), "r"(a[3]), "l"(desc), "r"(scale_d));
}

__device__ __forceinline__ uint32_t pack_bias(float lo, float hi, uint32_t bias2) {
    uint32_t r;
    asm("{\n.reg .b32 t;\n"
        "cvt.rn.bf16x2.f32 t, %2, %1;\n"
        "add.rn.bf16x2 %0, t, %3;\n}"
        : "=r"(r) : "f"(lo), "f"(hi), "r"(bias2));
    return r;
}

__device__ __forceinline__ int slice_channel(uint32_t rank, int wg) {
    return (wg * 2 + rank) * 64;
}
__device__ __forceinline__ uint32_t w_stage(int wg) {
    return (wg + 1) * STAGE_BYTES + (wg == 2 ? HALF_BYTES : 0);
}

struct Ring {
    uint32_t s, parity;
    __device__ __forceinline__ void advance() {
        if (++s == STAGES) {
            s = 0;
            parity ^= 1;
        }
    }
};

__device__ __forceinline__ void write_out(uint32_t wg_bars, uint32_t st_addr, const Ring& r, const uint32_t (&v)[16]) {
    mbar_wait(wg_bars + BAR_OFREE + r.s * 32, r.parity ^ 1);
    const uint32_t dst = st_addr + r.s * HALF_BYTES;
#pragma unroll
    for (int j = 0; j < 4; j++) {
        asm volatile("stmatrix.sync.aligned.m8n8.x4.trans.shared.b16 [%0], {%1, %2, %3, %4};"
                     ::"r"(dst + j * 2048), "r"(v[4 * j]), "r"(v[4 * j + 1]), "r"(v[4 * j + 2]), "r"(v[4 * j + 3]) : "memory");
    }
    asm volatile("fence.proxy.async.shared::cta;" ::: "memory");
    __syncwarp();
    mbar_arrive_1(wg_bars + BAR_OFULL + r.s * 32);
}

template <int N>
__device__ __forceinline__ void hand_back(uint32_t& open) {
    if (open != 0) {
        stores_read_wait<N>();
        mbar_arrive_1(open);
        open = 0;
    }
}

__global__ void __cluster_dims__(2, 1, 1) __launch_bounds__(THREADS, 1)
conv1x1_kernel(const uint8_t* __restrict__ x_raw,
               const uint8_t* __restrict__ w_raw,
               const uint16_t* __restrict__ bias,
               uint32_t num_tiles,
               uint32_t num_clusters,
               const __grid_constant__ Maps maps,
               const __grid_constant__ Tune tune) {
    const uint32_t t_entry = timer_ns();
    extern __shared__ uint8_t smem_raw[];
    const uint32_t smem = (smem_u32(smem_raw) + 1023u) & ~1023u;
    const uint32_t bars = smem + SMEM_BAR;

    if (threadIdx.x < PRE_W) {
        prefetch_l2(w_raw + (blockIdx.x % (W_LINES / PRE_W) * PRE_W + threadIdx.x) * 128);
    } else if (threadIdx.x >= 96 && threadIdx.x < 128) {
        prefetch_map_1(&maps.w);
        prefetch_map_1(&maps.x);
    }
    if (threadIdx.x < NUM_WG * 128) cluster_arrive();
    if (threadIdx.x >= 128 && threadIdx.x < 128 + PIECE_BYTES / 128) {
        const uint8_t* p = x_raw + (size_t)blockIdx.x * HALF_BYTES + (threadIdx.x - 128) * 128;
        const uint32_t wait = ((threadIdx.x - 128) >> 5) * PRE_DT;
        const uint32_t c0 = (uint32_t)clock();
        while ((uint32_t)clock() - c0 < wait) {}
        asm volatile("cp.async.ca.shared.global.L2::128B [%0], [%1], 4;" ::"r"(bars + SINK_AT + (threadIdx.x & 31) * 4), "l"(p) : "memory");
    }
    if (threadIdx.x == 0) TRV(0, 63, t_entry);

    const int warp = uniform(threadIdx.x >> 5);
    const int lane = threadIdx.x & 31;
    const uint32_t rank    = blockIdx.x & 1;
    const uint32_t cluster = blockIdx.x >> 1;

    if (warp < NUM_WG * 4) {
        asm volatile("setmaxnreg.inc.sync.aligned.u32 160;");
        const int wg = warp >> 2;
        const int wq = warp & 3;
        const uint32_t bias_lo = bias[slice_channel(rank, wg) + wq * 16 + (lane >> 2)] * 0x10001u;
        const uint32_t bias_hi = bias[slice_channel(rank, wg) + wq * 16 + (lane >> 2) + 8] * 0x10001u;

        cluster_wait();
        TRE(1 + wg, 63);
        mbar_wait(bars + BAR_W + 8 * wg, 0);
        TRE(4 + wg, 63);
        uint32_t wreg[96];
        {
            const int r = lane & 7, m = lane >> 3;
            const uint32_t base = smem + w_stage(wg) + ((m >> 1) * 8 + r) * 128 + (((2 * wq + (m & 1)) ^ r) << 4);
#pragma unroll
            for (int ks = 0; ks < 24; ks++) {
                asm volatile("ldmatrix.sync.aligned.m8n8.x4.trans.shared.b16 {%0, %1, %2, %3}, [%4];"
                             : "=r"(wreg[ks * 4 + 0]), "=r"(wreg[ks * 4 + 1]), "=r"(wreg[ks * 4 + 2]), "=r"(wreg[ks * 4 + 3])
                             : "r"(base + ks * 2048) : "memory");
            }
        }
        uint32_t dep = 0;
#pragma unroll
        for (int ks = 0; ks < 24; ks++) dep ^= wreg[ks * 4];
        dep = uniform(dep & (num_tiles >> 31));
        if (lane < 6 && wg < 2) mbar_arrive_cta(bars + BAR_EMPTY + 8 * (wg + 1) + dep, lane & 1);
        asm volatile("cp.async.wait_all;" ::: "memory");
        TRE(1 + wg, 60);

        const uint32_t wg_bars = bars + wg * 8;
        const uint32_t st_addr = smem + SMEM_OUT + wg * SLICE_BYTES + ((lane >> 4) * 8 + (lane & 7)) * 128 +
                                 (((2 * wq + ((lane >> 3) & 1)) ^ (lane & 7)) << 4);
        const uint64_t desc_base =
            (uint64_t)((smem & 0x3FFFF) >> 4) | ((uint64_t)1 << 16) | ((uint64_t)(6144 >> 4) << 32) | ((uint64_t)1 << 62);
        const int next_turn = 4 + (wg + 1) % NUM_WG;

        float acc[32];
        uint32_t packed[16];
        Ring r = {0, dep}, o = r;
        bool held = false;
        for (uint32_t i = 0, id = cluster; id < num_tiles; i++, id += num_clusters, r.advance()) {
            mbar_wait(bars + BAR_FULL + 8 * r.s, r.parity);
            if ((i | wg) != 0) asm volatile("bar.sync %0, 256;" ::"r"(4 + wg) : "memory");
            TRE(1 + wg * 2, i);
            const uint64_t desc = desc_base + (uint64_t)(r.s * (STAGE_BYTES >> 4));
            asm volatile("wgmma.fence.sync.aligned;" ::: "memory");
#pragma unroll
            for (int ks = 0; ks < 24; ks++) {
                wgmma_rs_n64(acc, &wreg[ks * 4], desc + (uint64_t)((ks >> 2) * 64 + (ks & 3) * 2), ks != 0);
                if (ks + 1 == HAND_AT) asm volatile("bar.arrive %0, 256;" ::"r"(next_turn) : "memory");
            }
            asm volatile("wgmma.commit_group.sync.aligned;" ::: "memory");
            asm volatile("wgmma.wait_group.sync.aligned 0;" ::: "memory");
#pragma unroll
            for (int j = 0; j < 32; j++) asm volatile("" : "+f"(acc[j])::"memory");
            TRE(2 + wg * 2, i);
            if (lane < 2) mbar_arrive_cta(bars + BAR_EMPTY + 8 * r.s, lane);

            if (held) write_out(wg_bars, st_addr, o, packed);
            o = r;
#pragma unroll
            for (int j = 0; j < 16; j++) packed[j] = pack_bias(acc[2 * j], acc[2 * j + 1], j & 1 ? bias_hi : bias_lo);
            held = !mbar_test(wg_bars + BAR_OFREE + o.s * 32, o.parity ^ 1);
            if (!held) write_out(wg_bars, st_addr, o, packed);
            TRE(8 + wg, i);
        }
        if (held) write_out(wg_bars, st_addr, o, packed);
        if (wg == 0) asm volatile("bar.sync 4, 256;" ::: "memory");
        TRE(1 + wg, 62);
    } else {
        asm volatile("setmaxnreg.dec.sync.aligned.u32 32;");
        if (warp == NUM_WG * 4) {
#pragma unroll
            for (int j = 0; j < NUM_WG; j++) mbar_init_1(bars + BAR_W + 8 * j, 1);
            publish_barriers();
            cluster_arrive();
#pragma unroll
            for (int j = 0; j < NUM_WG; j++) {
                mbar_expect_tx_1(bars + BAR_W + 8 * j, STAGE_BYTES);
                tma_load_w_1(smem + w_stage(j), &maps.w, bars + BAR_W + 8 * j, slice_channel(rank, j));
                if (j == 0) TR(2, 61);
            }
            cluster_wait();
            TR(0, 0);
            mbar_expect_tx_1(bars + BAR_FULL, STAGE_BYTES);
            tma_load_x_1(smem + rank * HALF_BYTES, &maps.x, bars + BAR_FULL, cluster * 8 + rank * 4);
            Ring r = {1, 0};
#pragma unroll 1
            for (uint32_t i = 1, id = cluster + num_clusters; id < num_tiles; i++, id += num_clusters, r.advance()) {
                mbar_wait(bars + BAR_EMPTY + 8 * r.s, r.parity ^ (r.s == 0));
                sts32(bars + ISSUED_AT, id);
                TR(0, i);
                TRV(15, i, id);
                const uint32_t full = bars + BAR_FULL + 8 * r.s;
                const uint32_t dst = smem + r.s * STAGE_BYTES + rank * HALF_BYTES;
                mbar_expect_tx_1(full, STAGE_BYTES);
                if (id + tune.EF_TAIL < num_tiles) tma_load_x_1(dst, &maps.x, full, id * 8 + rank * 4);
                else tma_load_x_evict_first_1(dst, &maps.x, full, id * 8 + rank * 4);
            }
#pragma unroll 1
            for (int k = 0; k < STAGES; k++, r.advance()) mbar_wait(bars + BAR_EMPTY + 8 * r.s, r.parity ^ (r.s == 0));
        } else if (warp == NUM_WG * 4 + 1) {
#pragma unroll
            for (int s = 0; s < STAGES; s++) {
                mbar_init_1(bars + BAR_FULL + 8 * s, 1);
                mbar_init_1(bars + BAR_EMPTY + 8 * s, NUM_WG * 4 * 2);
            }
            publish_barriers();
            cluster_arrive();
            TR(0, 61);
            cluster_wait();
            prefetch_map_1(&maps.out);
        } else if (warp == NUM_WG * 4 + 2) {
#pragma unroll
            for (int b = 0; b < STAGES; b++) {
#pragma unroll
                for (int w = 0; w < NUM_WG; w++) {
                    mbar_init_1(bars + BAR_OFREE + b * 32 + w * 8, 1);
                    mbar_init_1(bars + BAR_OFULL + b * 32 + w * 8, 4);
                }
            }
            publish_barriers();
            cluster_arrive();
            cluster_wait();
            const uint32_t first = tune.ST_AT * num_clusters;
            const uint32_t n3 = max((int)(num_tiles - first - tune.ST_N1 - tune.ST_N2 - tune.ST_END), 0);
            auto release_time = [&](uint32_t id) {
                if (id < first) return t_entry;
                uint32_t rest = id - first, t = 0;
                auto segment = [&](uint32_t ids, uint32_t per_round) {
                    const uint32_t n = min(rest, ids);
                    t += n * per_round;
                    rest -= n;
                };
                segment(tune.ST_N1, tune.ST_S1);
                segment(tune.ST_N2, tune.ST_S2);
                segment(n3, tune.ST_S3);
                segment(tune.ST_N4, tune.ST_S4);
                segment(tune.ST_N5, tune.ST_S5);
                segment(tune.ST_END - tune.ST_N4 - tune.ST_N5 - tune.ST_N7, tune.ST_S6);
                return t_entry + tune.ST_T0 + t / num_clusters;
            };
            const uint32_t lane_full = bars + BAR_OFULL + min(lane, NUM_WG - 1) * 8;
            uint32_t open = 0, due = release_time(cluster);
            Ring o = {0, 0};
#pragma unroll 1
            for (uint32_t j = 0, id = cluster; id < num_tiles; j++, id += num_clusters, o.advance()) {
                const uint32_t obar = bars + o.s * 32;
                const uint32_t src = smem + SMEM_OUT + o.s * HALF_BYTES;
                auto store = [&](int w) {
                    if (id + tune.SE_TAIL < num_tiles) tma_store_1(&maps.out, src + w * SLICE_BYTES, slice_channel(rank, w), id * TILE_PIX);
                    else tma_store_evict_first_1(&maps.out, src + w * SLICE_BYTES, slice_channel(rank, w), id * TILE_PIX);
                };
#pragma unroll 1
                for (uint32_t spins = 0; !reached(timer_ns(), due) && spins < PACE_LIMIT; spins++) {
                    hand_back<0>(open);
                    __nanosleep(20);
                }
                if (mbar_test(lane_full + o.s * 32, o.parity)) {
                    __syncwarp();
                    TR(11, j);
#pragma unroll
                    for (int w = 0; w < NUM_WG; w++) store(w);
                    due = release_time(id + num_clusters);
                    hand_back<3>(open);
                    stores_read_wait<2>();
                    TR(12, j);
                    mbar_arrive_1(obar + BAR_OFREE);
                    stores_read_wait<1>();
                    TR(13, j);
                    mbar_arrive_1(obar + BAR_OFREE + 8);
                    open = obar + BAR_OFREE + 16;
                } else {
#pragma unroll 1
                    for (uint32_t w = 0; w < NUM_WG; w++) {
                        if (!mbar_test(obar + BAR_OFULL + w * 8, o.parity)) {
                            hand_back<0>(open);
                            mbar_wait(obar + BAR_OFULL + w * 8, o.parity);
                        }
                        TR(11 + w, j);
                        store(w);
                        hand_back<1>(open);
                        open = obar + BAR_OFREE + w * 8;
                    }
                    due = release_time(id + num_clusters);
                }
            }
            stores_read_wait<0>();
            TR(4, 62);
        } else {
            sts32(bars + ISSUED_AT, 0);
            cluster_arrive();
            uint32_t due = t_entry + tune.PM_T0 + (blockIdx.x & 3) * tune.PM_STAG;
            const uint32_t step = num_clusters / 2;
#pragma unroll 1
            for (uint32_t piece = 1;; piece++) {
                const uint32_t t = cluster + piece / 2 * num_clusters;
                if (t >= num_tiles) break;
                const bool last = t + tune.LEAD_T >= num_tiles;
                uint32_t now, issued;
#pragma unroll 1
                for (uint32_t spins = 0; spins < PACE_LIMIT; spins++) {
                    issued = uniform(lds32(bars + ISSUED_AT));
                    now = timer_ns();
                    const int lead = max((int)(last ? tune.LEAD_C : tune.LEAD_B), (int)tune.LEAD_A - (int)(issued * tune.LEAD_S >> 6));
                    if (reached(now, due)) {
                        if (cluster + piece * step <= issued + lead) break;
                        due = now;
                    }
                    __nanosleep(20);
                }
                if (t < issued) continue;
                if (reached(now - tune.PM_SLACK, due)) due = now - tune.PM_SLACK;
                due += piece < tune.PM_E1 ? tune.PM_DT1 : piece < tune.PM_E2 ? tune.PM_DT2 : last ? tune.PM_DT4 : tune.PM_DT3;
                const uint8_t* p = x_raw + (size_t)t * STAGE_BYTES + rank * HALF_BYTES + (piece % 2) * PIECE_BYTES + lane * 128;
#pragma unroll
                for (int k = 0; k < PIECE_BYTES / 4096; k++) prefetch_l2(p + k * 4096);
                if (piece % 2 == 0) TR(14, piece / 2);
            }
            cluster_wait();
        }
    }
}

typedef CUresult (*EncodeTiledFn)(CUtensorMap*, CUtensorMapDataType, cuuint32_t, void*, const cuuint64_t*,
                                  const cuuint64_t*, const cuuint32_t*, const cuuint32_t*, CUtensorMapInterleave,
                                  CUtensorMapSwizzle, CUtensorMapL2promotion, CUtensorMapFloatOOBfill);

}

extern "C" void kernel_launch(void* const* d_in, const int* in_sizes, int n_in, void* d_out, int out_size) {
    (void)n_in;
    (void)out_size;
    void* x = d_in[0];
    void* w = d_in[1];
    const uint16_t* b = (const uint16_t*)d_in[2];
    const int M = in_sizes[0] / C;
    const int num_tiles = M / TILE_PIX;

    static EncodeTiledFn encode = nullptr;
    static int sms = 0;
    if (!encode) {
        void* fn = nullptr;
        cudaDriverEntryPointQueryResult q;
        cudaGetDriverEntryPoint("cuTensorMapEncodeTiled", &fn, cudaEnableDefault, &q);
        encode = (EncodeTiledFn)fn;
        cudaDeviceGetAttribute(&sms, cudaDevAttrMultiProcessorCount, 0);
        cudaFuncSetAttribute(conv1x1_kernel, cudaFuncAttributeMaxDynamicSharedMemorySize, SMEM_TOTAL);
    }

    Maps maps;
    const cuuint32_t ones[4] = {1, 1, 1, 1};
    auto make = [&](CUtensorMap* map, int rank, void* base, const cuuint64_t* dims, const cuuint64_t* strides,
                    const cuuint32_t* box, CUtensorMapL2promotion promo) {
        encode(map, CU_TENSOR_MAP_DATA_TYPE_BFLOAT16, rank, base, dims, strides, box, ones, CU_TENSOR_MAP_INTERLEAVE_NONE,
               CU_TENSOR_MAP_SWIZZLE_128B, promo, CU_TENSOR_MAP_FLOAT_OOB_FILL_NONE);
    };
    {
        const cuuint64_t dims[4]    = {64, 8, 6, (cuuint64_t)(M / 8)};
        const cuuint64_t strides[3] = {C * 2, 128, 8 * C * 2};
        const cuuint32_t box[4]     = {64, 8, 6, TILE_PIX / 16};
        make(&maps.x, 4, x, dims, strides, box, CU_TENSOR_MAP_L2_PROMOTION_L2_128B);
    }
    {
        const cuuint64_t dims[3]    = {C, C / 2, 2};
        const cuuint64_t strides[2] = {C * 2, C * C};
        const cuuint32_t box[3]     = {64, C / 2, 2};
        make(&maps.w, 3, w, dims, strides, box, CU_TENSOR_MAP_L2_PROMOTION_L2_128B);
    }
    {
        const cuuint64_t dims[2]    = {C, (cuuint64_t)M};
        const cuuint64_t strides[1] = {C * 2};
        const cuuint32_t box[2]     = {64, TILE_PIX};
        make(&maps.out, 2, d_out, dims, strides, box, CU_TENSOR_MAP_L2_PROMOTION_NONE);
    }

    const Tune tune;
    int clusters = sms / 2;
    if (clusters > num_tiles) clusters = num_tiles;
    conv1x1_kernel<<<clusters * 2, THREADS, SMEM_TOTAL>>>((const uint8_t*)x, (const uint8_t*)w, b, (uint32_t)num_tiles,
                                                          (uint32_t)clusters, maps, tune);
}
```

```cpp
#include <cuda_runtime.h>
#include <cuda_bf16.h>
#include <cuda.h>
#include <stdint.h>
#include <initializer_list>

#define TUNABLES(F) \
    F(PM_T0, 280)        \
    F(PM_STAG, 120)      \
    F(PM_DT1, 415)       \
    F(PM_E1, 8) \
    F(PM_DT2, 485) \
    F(PM_E2, 23) \
    F(PM_DT3, 860) \
    F(PM_SLACK, 700)     \
    F(LEAD_A, 351)       \
    F(LEAD_S, 10)        \
    F(LEAD_B, 151)       \
    F(LEAD_T, 264)       \
    F(LEAD_C, 170)       \
    F(PM_DT4, 700)       \
    F(EF_TAIL, 440)      \
    F(ST_AT, 2)          \
    F(ST_T0, 6830)       \
    F(ST_S1, 2040)       \
    F(ST_N1, 448) \
    F(ST_S2, 1960) \
    F(ST_N2, 594) \
    F(ST_S3, 2020)       \
    F(ST_END, 613) \
    F(ST_S4, 1450)       \
    F(ST_N4, 96) \
    F(ST_S5, 1100) \
    F(ST_N5, 85) \
    F(ST_S6, 950) \
    F(ST_N7, 22)         \
    F(SE_TAIL, 400)

struct Tune {
#define F(n, v) uint32_t n = v;
    TUNABLES(F)
#undef F
};

#define TRV(slot, idx, v)
#define TR(slot, idx)
#define TRE(slot, idx)
#define TRACE_BYTES 0

namespace {

constexpr int C            = 384;
constexpr int TILE_PIX     = 64;
constexpr int STAGES       = 3;
constexpr int STAGE_BYTES  = TILE_PIX * C * 2;
constexpr int HALF_BYTES   = STAGE_BYTES / 2;
constexpr int PIECE_BYTES  = HALF_BYTES / 2;
constexpr int SLICE_BYTES  = TILE_PIX * 128;
constexpr int NUM_WG       = 3;
constexpr int THREADS      = (NUM_WG + 1) * 128;
constexpr int SMEM_OUT     = STAGES * STAGE_BYTES;
constexpr int SMEM_BAR     = SMEM_OUT + STAGES * HALF_BYTES;
constexpr int SMEM_TOTAL   = SMEM_BAR + 512 + TRACE_BYTES + 1024;
constexpr int HAND_AT      = 18;
constexpr int W_LINES      = C * C * 2 / 128;
constexpr int PRE_W        = 64;
constexpr int PRE_DT       = 330;
constexpr uint32_t SPIN_LIMIT = 1u << 22;
constexpr uint32_t PACE_LIMIT = 1u << 14;
constexpr int BAR_W     = 0;
constexpr int BAR_FULL  = 32;
constexpr int BAR_EMPTY = 64;
constexpr int BAR_OFREE = 96;
constexpr int BAR_OFULL = BAR_OFREE + 32 * STAGES;
constexpr int ISSUED_AT = BAR_OFULL + 32 * STAGES;
constexpr int SINK_AT   = 384;

struct Maps {
    CUtensorMap w, x, out;
};

#define ELECT "{\n.reg .pred e;\nelect.sync _|e, 0xffffffff;\n@e "

__device__ __forceinline__ uint32_t smem_u32(const void* p) {
    return (uint32_t)__cvta_generic_to_shared(p);
}
__device__ __forceinline__ void mbar_init_1(uint32_t bar, uint32_t count) {
    asm volatile(ELECT "mbarrier.init.shared::cta.b64 [%0], %1;\n}" ::"r"(bar), "r"(count) : "memory");
}
__device__ __forceinline__ void mbar_expect_tx_1(uint32_t bar, uint32_t bytes) {
    asm volatile(ELECT "mbarrier.arrive.expect_tx.shared::cta.b64 _, [%0], %1;\n}" ::"r"(bar), "r"(bytes) : "memory");
}
__device__ __forceinline__ void mbar_arrive_1(uint32_t bar) {
    asm volatile(ELECT "mbarrier.arrive.shared::cta.b64 _, [%0];\n}" ::"r"(bar) : "memory");
}
__device__ __forceinline__ void mbar_wait(uint32_t bar, uint32_t parity) {
    uint32_t done;
    uint32_t spins = 0;
    do {
        asm volatile(
            "{\n.reg .pred p;\n"
            "mbarrier.try_wait.parity.shared::cta.b64 p, [%1], %2;\n"
            "selp.u32 %0, 1, 0, p;\n}"
            : "=r"(done) : "r"(bar), "r"(parity) : "memory");
    } while (!done && ++spins < SPIN_LIMIT);
    __syncwarp();
}
__device__ __forceinline__ bool mbar_test(uint32_t bar, uint32_t parity) {
    uint32_t done;
    asm volatile(
        "{\n.reg .pred p;\n"
        "mbarrier.test_wait.parity.shared::cta.b64 p, [%1], %2;\n"
        "selp.u32 %0, 1, 0, p;\n}"
        : "=r"(done) : "r"(bar), "r"(parity) : "memory");
    return __all_sync(0xffffffffu, done);
}
__device__ __forceinline__ void mbar_arrive_cta(uint32_t bar, uint32_t cta) {
    asm volatile(
        "{\n.reg .b32 ra;\n"
        "mapa.shared::cluster.u32 ra, %0, %1;\n"
        "mbarrier.arrive.shared::cluster.b64 _, [ra];\n}"
        ::"r"(bar), "r"(cta) : "memory");
}
__device__ __forceinline__ uint32_t lds32(uint32_t addr) {
    uint32_t v;
    asm volatile("ld.volatile.shared.b32 %0, [%1];" : "=r"(v) : "r"(addr) : "memory");
    return v;
}
__device__ __forceinline__ void sts32(uint32_t addr, uint32_t v) {
    asm volatile("st.volatile.shared.b32 [%0], %1;" ::"r"(addr), "r"(v) : "memory");
}
__device__ __forceinline__ uint32_t uniform(uint32_t v) {
    return __shfl_sync(0xffffffffu, v, 0);
}
__device__ __forceinline__ void tma_load_w_1(uint32_t dst, const CUtensorMap* map, uint32_t bar, int n) {
    asm volatile(
        ELECT "cp.async.bulk.tensor.3d.shared::cluster.global.mbarrier::complete_tx::bytes [%0], [%1, {%3, %4, %4}], [%2];\n}"
        ::"r"(dst), "l"(map), "r"(bar), "r"(n), "r"(0) : "memory");
}
__device__ __forceinline__ void tma_load_x_1(uint32_t dst, const CUtensorMap* map, uint32_t bar, int group) {
    asm volatile(
        ELECT "cp.async.bulk.tensor.4d.shared::cluster.global.mbarrier::complete_tx::bytes.multicast::cluster"
        " [%0], [%1, {%3, %3, %3, %4}], [%2], %5;\n}"
        ::"r"(dst), "l"(map), "r"(bar), "r"(0), "r"(group), "h"((uint16_t)3) : "memory");
}
__device__ __forceinline__ void tma_load_x_evict_first_1(uint32_t dst, const CUtensorMap* map, uint32_t bar, int group) {
    asm volatile(
        "{\n.reg .b64 pol;\n"
        "createpolicy.fractional.L2::evict_first.b64 pol, 1.0;\n"
        ELECT "cp.async.bulk.tensor.4d.shared::cluster.global.mbarrier::complete_tx::bytes.multicast::cluster.L2::cache_hint"
        " [%0], [%1, {%3, %3, %3, %4}], [%2], %5, pol;\n}\n}"
        ::"r"(dst), "l"(map), "r"(bar), "r"(0), "r"(group), "h"((uint16_t)3) : "memory");
}
__device__ __forceinline__ void tma_store_1(const CUtensorMap* map, uint32_t src, int ch, int pix) {
    asm volatile(
        ELECT "cp.async.bulk.tensor.2d.global.shared::cta.bulk_group [%0, {%2, %3}], [%1];\n}\n"
        "cp.async.bulk.commit_group;"
        ::"l"(map), "r"(src), "r"(ch), "r"(pix) : "memory");
}
__device__ __forceinline__ void tma_store_evict_first_1(const CUtensorMap* map, uint32_t src, int ch, int pix) {
    asm volatile(
        "{\n.reg .b64 pol;\n"
        "createpolicy.fractional.L2::evict_first.b64 pol, 1.0;\n"
        ELECT "cp.async.bulk.tensor.2d.global.shared::cta.bulk_group.L2::cache_hint [%0, {%2, %3}], [%1], pol;\n}\n}\n"
        "cp.async.bulk.commit_group;"
        ::"l"(map), "r"(src), "r"(ch), "r"(pix) : "memory");
}
template <int N>
__device__ __forceinline__ void stores_read_wait() {
    asm volatile("cp.async.bulk.wait_group.read %0;" ::"n"(N) : "memory");
}
__device__ __forceinline__ void prefetch_map_1(const CUtensorMap* map) {
    asm volatile(ELECT "prefetch.tensormap [%0];\n}" ::"l"(map) : "memory");
}
__device__ __forceinline__ void prefetch_l2(const void* p) {
    asm volatile("prefetch.global.L2 [%0];" ::"l"(p) : "memory");
}
__device__ __forceinline__ uint32_t timer_ns() {
    uint32_t t;
    asm volatile("mov.u32 %0, %%globaltimer_lo;" : "=r"(t)::"memory");
    return t;
}
__device__ __forceinline__ bool reached(uint32_t now, uint32_t t) {
    return (int32_t)(now - t) >= 0;
}
__device__ __forceinline__ void cluster_arrive() {
    asm volatile("barrier.cluster.arrive.relaxed.aligned;" ::: "memory");
}
__device__ __forceinline__ void cluster_wait() {
    asm volatile("barrier.cluster.wait.aligned;" ::: "memory");
}
__device__ __forceinline__ void publish_barriers() {
    asm volatile("fence.mbarrier_init.release.cluster;" ::: "memory");
    asm volatile("fence.proxy.async.shared::cta;" ::: "memory");
}

__device__ __forceinline__ void wgmma_rs_n64(float (&d)[32], const uint32_t* a, uint64_t desc, int scale_d) {
    asm volatile(
        "{\n.reg .pred p;\n"
        "setp.ne.b32 p, %37, 0;\n"
        "wgmma.mma_async.sync.aligned.m64n64k16.f32.bf16.bf16 "
        "{%0, %1, %2, %3, %4, %5, %6, %7, %8, %9, %10, %11, %12, %13, %14, %15, "
        "%16, %17, %18, %19, %20, %21, %22, %23, %24, %25, %26, %27, %28, %29, %30, %31}, "
        "{%32, %33, %34, %35}, %36, p, 1, 1, 0;\n}"
        : "+f"(d[0]), "+f"(d[1]), "+f"(d[2]), "+f"(d[3]), "+f"(d[4]), "+f"(d[5]), "+f"(d[6]), "+f"(d[7]),
          "+f"(d[8]), "+f"(d[9]), "+f"(d[10]), "+f"(d[11]), "+f"(d[12]), "+f"(d[13]), "+f"(d[14]), "+f"(d[15]),
          "+f"(d[16]), "+f"(d[17]), "+f"(d[18]), "+f"(d[19]), "+f"(d[20]), "+f"(d[21]), "+f"(d[22]), "+f"(d[23]),
          "+f"(d[24]), "+f"(d[25]), "+f"(d[26]), "+f"(d[27]), "+f"(d[28]), "+f"(d[29]), "+f"(d[30]), "+f"(d[31])
        : "r"(a[0]), "r"(a[1]), "r"(a[2]), "r"(a[3]), "l"(desc), "r"(scale_d));
}

__device__ __forceinline__ uint32_t pack_bias(float lo, float hi, uint32_t bias2) {
    uint32_t r;
    asm("{\n.reg .b32 t;\n"
        "cvt.rn.bf16x2.f32 t, %2, %1;\n"
        "add.rn.bf16x2 %0, t, %3;\n}"
        : "=r"(r) : "f"(lo), "f"(hi), "r"(bias2));
    return r;
}

__device__ __forceinline__ int slice_channel(uint32_t rank, int wg) {
    return (wg * 2 + rank) * 64;
}
__device__ __forceinline__ uint32_t w_stage(int wg) {
    return (wg + 1) * STAGE_BYTES + (wg == 2 ? HALF_BYTES : 0);
}

struct Ring {
    uint32_t s, parity;
    __device__ __forceinline__ void advance() {
        if (++s == STAGES) {
            s = 0;
            parity ^= 1;
        }
    }
};

__device__ __forceinline__ void write_out(uint32_t wg_bars, uint32_t st_addr, const Ring& r, const uint32_t (&v)[16]) {
    mbar_wait(wg_bars + BAR_OFREE + r.s * 32, r.parity ^ 1);
    const uint32_t dst = st_addr + r.s * HALF_BYTES;
#pragma unroll
    for (int j = 0; j < 4; j++) {
        asm volatile("stmatrix.sync.aligned.m8n8.x4.trans.shared.b16 [%0], {%1, %2, %3, %4};"
                     ::"r"(dst + j * 2048), "r"(v[4 * j]), "r"(v[4 * j + 1]), "r"(v[4 * j + 2]), "r"(v[4 * j + 3]) : "memory");
    }
    asm volatile("fence.proxy.async.shared::cta;" ::: "memory");
    __syncwarp();
    mbar_arrive_1(wg_bars + BAR_OFULL + r.s * 32);
}

template <int N>
__device__ __forceinline__ void hand_back(uint32_t& open) {
    if (open != 0) {
        stores_read_wait<N>();
        mbar_arrive_1(open);
        open = 0;
    }
}

__global__ void __cluster_dims__(2, 1, 1) __launch_bounds__(THREADS, 1)
conv1x1_kernel(const uint8_t* __restrict__ x_raw,
               const uint8_t* __restrict__ w_raw,
               const uint16_t* __restrict__ bias,
               uint32_t num_tiles,
               uint32_t num_clusters,
               const __grid_constant__ Maps maps,
               const __grid_constant__ Tune tune) {
    const uint32_t t_entry = timer_ns();
    extern __shared__ uint8_t smem_raw[];
    const uint32_t smem = (smem_u32(smem_raw) + 1023u) & ~1023u;
    const uint32_t bars = smem + SMEM_BAR;

    if (threadIdx.x < PRE_W) {
        prefetch_l2(w_raw + (blockIdx.x % (W_LINES / PRE_W) * PRE_W + threadIdx.x) * 128);
    } else if (threadIdx.x >= 96 && threadIdx.x < 128) {
        prefetch_map_1(&maps.w);
        prefetch_map_1(&maps.x);
    }
    if (threadIdx.x < NUM_WG * 128) cluster_arrive();
    if (threadIdx.x >= 128 && threadIdx.x < 128 + PIECE_BYTES / 128) {
        const uint8_t* p = x_raw + (size_t)blockIdx.x * HALF_BYTES + (threadIdx.x - 128) * 128;
        const uint32_t wait = ((threadIdx.x - 128) >> 5) * PRE_DT;
        const uint32_t c0 = (uint32_t)clock();
        while ((uint32_t)clock() - c0 < wait) {}
        asm volatile("cp.async.ca.shared.global.L2::128B [%0], [%1], 4;" ::"r"(bars + SINK_AT + (threadIdx.x & 31) * 4), "l"(p) : "memory");
    }
    if (threadIdx.x == 0) TRV(0, 63, t_entry);

    const int warp = uniform(threadIdx.x >> 5);
    const int lane = threadIdx.x & 31;
    const uint32_t rank    = blockIdx.x & 1;
    const uint32_t cluster = blockIdx.x >> 1;

    if (warp < NUM_WG * 4) {
        asm volatile("setmaxnreg.inc.sync.aligned.u32 160;");
        const int wg = warp >> 2;
        const int wq = warp & 3;
        const uint32_t bias_lo = bias[slice_channel(rank, wg) + wq * 16 + (lane >> 2)] * 0x10001u;
        const uint32_t bias_hi = bias[slice_channel(rank, wg) + wq * 16 + (lane >> 2) + 8] * 0x10001u;

        cluster_wait();
        TRE(1 + wg, 63);
        mbar_wait(bars + BAR_W + 8 * wg, 0);
        TRE(4 + wg, 63);
        uint32_t wreg[96];
        {
            const int r = lane & 7, m = lane >> 3;
            const uint32_t base = smem + w_stage(wg) + ((m >> 1) * 8 + r) * 128 + (((2 * wq + (m & 1)) ^ r) << 4);
#pragma unroll
            for (int ks = 0; ks < 24; ks++) {
                asm volatile("ldmatrix.sync.aligned.m8n8.x4.trans.shared.b16 {%0, %1, %2, %3}, [%4];"
                             : "=r"(wreg[ks * 4 + 0]), "=r"(wreg[ks * 4 + 1]), "=r"(wreg[ks * 4 + 2]), "=r"(wreg[ks * 4 + 3])
                             : "r"(base + ks * 2048) : "memory");
            }
        }
        uint32_t dep = 0;
#pragma unroll
        for (int ks = 0; ks < 24; ks++) dep ^= wreg[ks * 4];
        dep = uniform(dep & (num_tiles >> 31));
        if (lane < 6 && wg < 2) mbar_arrive_cta(bars + BAR_EMPTY + 8 * (wg + 1) + dep, lane & 1);
        asm volatile("cp.async.wait_all;" ::: "memory");
        TRE(1 + wg, 60);

        const uint32_t wg_bars = bars + wg * 8;
        const uint32_t st_addr = smem + SMEM_OUT + wg * SLICE_BYTES + ((lane >> 4) * 8 + (lane & 7)) * 128 +
                                 (((2 * wq + ((lane >> 3) & 1)) ^ (lane & 7)) << 4);
        const uint64_t desc_base =
            (uint64_t)((smem & 0x3FFFF) >> 4) | ((uint64_t)1 << 16) | ((uint64_t)(6144 >> 4) << 32) | ((uint64_t)1 << 62);
        const int next_turn = 4 + (wg + 1) % NUM_WG;

        float acc[32];
        uint32_t packed[16];
        Ring r = {0, dep}, o = r;
        bool held = false;
        for (uint32_t i = 0, id = cluster; id < num_tiles; i++, id += num_clusters, r.advance()) {
            mbar_wait(bars + BAR_FULL + 8 * r.s, r.parity);
            if ((i | wg) != 0) asm volatile("bar.sync %0, 256;" ::"r"(4 + wg) : "memory");
            TRE(1 + wg * 2, i);
            const uint64_t desc = desc_base + (uint64_t)(r.s * (STAGE_BYTES >> 4));
            asm volatile("wgmma.fence.sync.aligned;" ::: "memory");
#pragma unroll
            for (int ks = 0; ks < 24; ks++) {
                wgmma_rs_n64(acc, &wreg[ks * 4], desc + (uint64_t)((ks >> 2) * 64 + (ks & 3) * 2), ks != 0);
                if (ks + 1 == HAND_AT) asm volatile("bar.arrive %0, 256;" ::"r"(next_turn) : "memory");
            }
            asm volatile("wgmma.commit_group.sync.aligned;" ::: "memory");
            asm volatile("wgmma.wait_group.sync.aligned 0;" ::: "memory");
#pragma unroll
            for (int j = 0; j < 32; j++) asm volatile("" : "+f"(acc[j])::"memory");
            TRE(2 + wg * 2, i);
            if (lane < 2) mbar_arrive_cta(bars + BAR_EMPTY + 8 * r.s, lane);

            if (held) write_out(wg_bars, st_addr, o, packed);
            o = r;
#pragma unroll
            for (int j = 0; j < 16; j++) packed[j] = pack_bias(acc[2 * j], acc[2 * j + 1], j & 1 ? bias_hi : bias_lo);
            held = !mbar_test(wg_bars + BAR_OFREE + o.s * 32, o.parity ^ 1);
            if (!held) write_out(wg_bars, st_addr, o, packed);
            TRE(8 + wg, i);
        }
        if (held) write_out(wg_bars, st_addr, o, packed);
        if (wg == 0) asm volatile("bar.sync 4, 256;" ::: "memory");
        TRE(1 + wg, 62);
    } else {
        asm volatile("setmaxnreg.dec.sync.aligned.u32 32;");
        if (warp == NUM_WG * 4) {
#pragma unroll
            for (int j = 0; j < NUM_WG; j++) mbar_init_1(bars + BAR_W + 8 * j, 1);
            publish_barriers();
            cluster_arrive();
#pragma unroll
            for (int j = 0; j < NUM_WG; j++) {
                mbar_expect_tx_1(bars + BAR_W + 8 * j, STAGE_BYTES);
                tma_load_w_1(smem + w_stage(j), &maps.w, bars + BAR_W + 8 * j, slice_channel(rank, j));
                if (j == 0) TR(2, 61);
            }
            cluster_wait();
            TR(0, 0);
            mbar_expect_tx_1(bars + BAR_FULL, STAGE_BYTES);
            tma_load_x_1(smem + rank * HALF_BYTES, &maps.x, bars + BAR_FULL, cluster * 8 + rank * 4);
            Ring r = {1, 0};
#pragma unroll 1
            for (uint32_t i = 1, id = cluster + num_clusters; id < num_tiles; i++, id += num_clusters, r.advance()) {
                mbar_wait(bars + BAR_EMPTY + 8 * r.s, r.parity ^ (r.s == 0));
                sts32(bars + ISSUED_AT, id);
                TR(0, i);
                TRV(15, i, id);
                const uint32_t full = bars + BAR_FULL + 8 * r.s;
                const uint32_t dst = smem + r.s * STAGE_BYTES + rank * HALF_BYTES;
                mbar_expect_tx_1(full, STAGE_BYTES);
                if (id + tune.EF_TAIL < num_tiles) tma_load_x_1(dst, &maps.x, full, id * 8 + rank * 4);
                else tma_load_x_evict_first_1(dst, &maps.x, full, id * 8 + rank * 4);
            }
#pragma unroll 1
            for (int k = 0; k < STAGES; k++, r.advance()) mbar_wait(bars + BAR_EMPTY + 8 * r.s, r.parity ^ (r.s == 0));
        } else if (warp == NUM_WG * 4 + 1) {
#pragma unroll
            for (int s = 0; s < STAGES; s++) {
                mbar_init_1(bars + BAR_FULL + 8 * s, 1);
                mbar_init_1(bars + BAR_EMPTY + 8 * s, NUM_WG * 4 * 2);
            }
            publish_barriers();
            cluster_arrive();
            TR(0, 61);
            cluster_wait();
            prefetch_map_1(&maps.out);
        } else if (warp == NUM_WG * 4 + 2) {
#pragma unroll
            for (int b = 0; b < STAGES; b++) {
#pragma unroll
                for (int w = 0; w < NUM_WG; w++) {
                    mbar_init_1(bars + BAR_OFREE + b * 32 + w * 8, 1);
                    mbar_init_1(bars + BAR_OFULL + b * 32 + w * 8, 4);
                }
            }
            publish_barriers();
            cluster_arrive();
            cluster_wait();
            const uint32_t first = tune.ST_AT * num_clusters;
            const uint32_t n3 = max((int)(num_tiles - first - tune.ST_N1 - tune.ST_N2 - tune.ST_END), 0);
            auto release_time = [&](uint32_t id) {
                if (id < first) return t_entry;
                uint32_t rest = id - first, t = 0;
                auto segment = [&](uint32_t ids, uint32_t per_round) {
                    const uint32_t n = min(rest, ids);
                    t += n * per_round;
                    rest -= n;
                };
                segment(tune.ST_N1, tune.ST_S1);
                segment(tune.ST_N2, tune.ST_S2);
                segment(n3, tune.ST_S3);
                segment(tune.ST_N4, tune.ST_S4);
                segment(tune.ST_N5, tune.ST_S5);
                segment(tune.ST_END - tune.ST_N4 - tune.ST_N5 - tune.ST_N7, tune.ST_S6);
                return t_entry + tune.ST_T0 + t / num_clusters;
            };
            const uint32_t lane_full = bars + BAR_OFULL + min(lane, NUM_WG - 1) * 8;
            uint32_t open = 0, due = release_time(cluster);
            Ring o = {0, 0};
#pragma unroll 1
            for (uint32_t j = 0, id = cluster; id < num_tiles; j++, id += num_clusters, o.advance()) {
                const uint32_t obar = bars + o.s * 32;
                const uint32_t src = smem + SMEM_OUT + o.s * HALF_BYTES;
                auto store = [&](int w) {
                    if (id + tune.SE_TAIL < num_tiles) tma_store_1(&maps.out, src + w * SLICE_BYTES, slice_channel(rank, w), id * TILE_PIX);
                    else tma_store_evict_first_1(&maps.out, src + w * SLICE_BYTES, slice_channel(rank, w), id * TILE_PIX);
                };
#pragma unroll 1
                for (uint32_t spins = 0; !reached(timer_ns(), due) && spins < PACE_LIMIT; spins++) {
                    hand_back<0>(open);
                    __nanosleep(20);
                }
                if (mbar_test(lane_full + o.s * 32, o.parity)) {
                    __syncwarp();
                    TR(11, j);
#pragma unroll
                    for (int w = 0; w < NUM_WG; w++) store(w);
                    due = release_time(id + num_clusters);
                    hand_back<3>(open);
                    stores_read_wait<2>();
                    TR(12, j);
                    mbar_arrive_1(obar + BAR_OFREE);
                    stores_read_wait<1>();
                    TR(13, j);
                    mbar_arrive_1(obar + BAR_OFREE + 8);
                    open = obar + BAR_OFREE + 16;
                } else {
#pragma unroll 1
                    for (uint32_t w = 0; w < NUM_WG; w++) {
                        if (!mbar_test(obar + BAR_OFULL + w * 8, o.parity)) {
                            hand_back<0>(open);
                            mbar_wait(obar + BAR_OFULL + w * 8, o.parity);
                        }
                        TR(11 + w, j);
                        store(w);
                        hand_back<1>(open);
                        open = obar + BAR_OFREE + w * 8;
                    }
                    due = release_time(id + num_clusters);
                }
            }
            stores_read_wait<0>();
            TR(4, 62);
        } else {
            sts32(bars + ISSUED_AT, 0);
            cluster_arrive();
            uint32_t due = t_entry + tune.PM_T0 + (blockIdx.x & 3) * tune.PM_STAG;
            const uint32_t step = num_clusters / 2;
#pragma unroll 1
            for (uint32_t piece = 1;; piece++) {
                const uint32_t t = cluster + piece / 2 * num_clusters;
                if (t >= num_tiles) break;
                const bool last = t + tune.LEAD_T >= num_tiles;
                uint32_t now, issued;
#pragma unroll 1
                for (uint32_t spins = 0; spins < PACE_LIMIT; spins++) {
                    issued = uniform(lds32(bars + ISSUED_AT));
                    now = timer_ns();
                    const int lead = max((int)(last ? tune.LEAD_C : tune.LEAD_B), (int)tune.LEAD_A - (int)(issued * tune.LEAD_S >> 6));
                    if (reached(now, due)) {
                        if (cluster + piece * step <= issued + lead) break;
                        due = now;
                    }
                    __nanosleep(20);
                }
                if (t < issued) continue;
                if (reached(now - tune.PM_SLACK, due)) due = now - tune.PM_SLACK;
                due += piece < tune.PM_E1 ? tune.PM_DT1 : piece < tune.PM_E2 ? tune.PM_DT2 : last ? tune.PM_DT4 : tune.PM_DT3;
                const uint8_t* p = x_raw + (size_t)t * STAGE_BYTES + rank * HALF_BYTES + (piece % 2) * PIECE_BYTES + lane * 128;
#pragma unroll
                for (int k = 0; k < PIECE_BYTES / 4096; k++) prefetch_l2(p + k * 4096);
                if (piece % 2 == 0) TR(14, piece / 2);
            }
            cluster_wait();
        }
    }
}

typedef CUresult (*EncodeTiledFn)(CUtensorMap*, CUtensorMapDataType, cuuint32_t, void*, const cuuint64_t*,
                                  const cuuint64_t*, const cuuint32_t*, const cuuint32_t*, CUtensorMapInterleave,
                                  CUtensorMapSwizzle, CUtensorMapL2promotion, CUtensorMapFloatOOBfill);

}

extern "C" void kernel_launch(void* const* d_in, const int* in_sizes, int n_in, void* d_out, int out_size) {
    (void)n_in;
    (void)out_size;
    void* x = d_in[0];
    void* w = d_in[1];
    const uint16_t* b = (const uint16_t*)d_in[2];
    const int M = in_sizes[0] / C;
    const int num_tiles = M / TILE_PIX;

    static EncodeTiledFn encode = nullptr;
    static int sms = 0, mem_khz = 0, mem_bits = 0;
    if (!encode) {
        void* fn = nullptr;
        cudaDriverEntryPointQueryResult q;
        cudaGetDriverEntryPoint("cuTensorMapEncodeTiled", &fn, cudaEnableDefault, &q);
        encode = (EncodeTiledFn)fn;
        cudaDeviceGetAttribute(&sms, cudaDevAttrMultiProcessorCount, 0);
        cudaDeviceGetAttribute(&mem_khz, cudaDevAttrMemoryClockRate, 0);
        cudaDeviceGetAttribute(&mem_bits, cudaDevAttrGlobalMemoryBusWidth, 0);
        cudaFuncSetAttribute(conv1x1_kernel, cudaFuncAttributeMaxDynamicSharedMemorySize, SMEM_TOTAL);
    }

    Maps maps;
    const cuuint32_t ones[4] = {1, 1, 1, 1};
    auto make = [&](CUtensorMap* map, int rank, void* base, const cuuint64_t* dims, const cuuint64_t* strides,
                    const cuuint32_t* box, CUtensorMapL2promotion promo) {
        encode(map, CU_TENSOR_MAP_DATA_TYPE_BFLOAT16, rank, base, dims, strides, box, ones, CU_TENSOR_MAP_INTERLEAVE_NONE,
               CU_TENSOR_MAP_SWIZZLE_128B, promo, CU_TENSOR_MAP_FLOAT_OOB_FILL_NONE);
    };
    {
        const cuuint64_t dims[4]    = {64, 8, 6, (cuuint64_t)(M / 8)};
        const cuuint64_t strides[3] = {C * 2, 128, 8 * C * 2};
        const cuuint32_t box[4]     = {64, 8, 6, TILE_PIX / 16};
        make(&maps.x, 4, x, dims, strides, box, CU_TENSOR_MAP_L2_PROMOTION_L2_128B);
    }
    {
        const cuuint64_t dims[3]    = {C, C / 2, 2};
        const cuuint64_t strides[2] = {C * 2, C * C};
        const cuuint32_t box[3]     = {64, C / 2, 2};
        make(&maps.w, 3, w, dims, strides, box, CU_TENSOR_MAP_L2_PROMOTION_L2_128B);
    }
    {
        const cuuint64_t dims[2]    = {C, (cuuint64_t)M};
        const cuuint64_t strides[1] = {C * 2};
        const cuuint32_t box[2]     = {64, TILE_PIX};
        make(&maps.out, 2, d_out, dims, strides, box, CU_TENSOR_MAP_L2_PROMOTION_NONE);
    }

    Tune tune;
    int clusters = sms / 2;
    if (clusters > num_tiles) clusters = num_tiles;
    const double ids  = clusters / 66.0;
    const double time = mem_khz > 0 && mem_bits > 0 ? ids * (2619000.0 * 5120.0) / ((double)mem_khz * mem_bits) : ids;
    for (uint32_t* v : {&tune.PM_DT1, &tune.PM_DT2, &tune.PM_DT3, &tune.PM_DT4, &tune.ST_T0, &tune.ST_S1, &tune.ST_S2,
                        &tune.ST_S3, &tune.ST_S4, &tune.ST_S5, &tune.ST_S6})
        *v = (uint32_t)(*v * time + 0.5);
    for (uint32_t* v : {&tune.LEAD_A, &tune.LEAD_B, &tune.LEAD_T, &tune.LEAD_C, &tune.ST_N1, &tune.ST_N2, &tune.ST_END,
                        &tune.ST_N4, &tune.ST_N5, &tune.ST_N7})
        *v = (uint32_t)(*v * ids + 0.5);
    conv1x1_kernel<<<clusters * 2, THREADS, SMEM_TOTAL>>>((const uint8_t*)x, (const uint8_t*)w, b, (uint32_t)num_tiles,
                                                          (uint32_t)clusters, maps, tune);
}
```
